```python
import torch

def _softmax(x, axis=-1):
    return torch.softmax(x, dim=axis)
def _gelu(x):
    return torch.nn.functional.gelu(x, approximate="tanh")
def _silu(x):
    return torch.nn.functional.silu(x)
def _sigmoid(x):
    return torch.sigmoid(x)
def _layernorm(x, axis=-1, eps=1e-5):
    m = x.mean(dim=axis, keepdim=True)
    v = x.var(dim=axis, keepdim=True, unbiased=False)
    return (x - m) / torch.sqrt(v + eps)
def _scatter_add(tgt, idx, src, axis=0):
    return tgt.clone().index_add_(axis, idx, src)
def _segment_sum(src, seg, n):
    out = torch.zeros((n,) + src.shape[1:], dtype=src.dtype)
    return out.index_add_(0, seg, src)
def _pad(x, pw):
    flat = tuple(v for pair in reversed(pw) for v in pair)
    return torch.nn.functional.pad(x, flat)

kernel_name = 'concat_heads__linear_attn_block__ssm_conv_h3__prompt'

def setup_inputs():

    _w = (lambda a: (lambda t: t.to(torch.bfloat16) if t.is_floating_point() else t)(torch.as_tensor(a)))
    def _A_setup():
        B, S, D = 1, 2048, 1024
        return {
            "x": _w((lambda *s: torch.randn(*s, dtype=torch.bfloat16) * 0.05)(B, S, D)),
            "wqkv": _w((lambda *s: torch.randn(*s, dtype=torch.bfloat16) * 1.6)(D, 3 * D)),
            "wo": _w((lambda *s: torch.randn(*s, dtype=torch.bfloat16) * 0.1)(D, D)),
        }
    _A_in = _A_setup()

    def _B_setup():
        B, S, D = 1, 2048, 1024
        ks = 4
        return {
            "q": _w((lambda *s: torch.randn(*s, dtype=torch.bfloat16) * 0.05)(B, S, D)),
            "k": _w((lambda *s: torch.randn(*s, dtype=torch.bfloat16) * 0.8)(B, S, D)),
            "v": _w((lambda *s: torch.randn(*s, dtype=torch.bfloat16) * 0.4)(B, S, D)),
            "shift_k": _w((lambda *s: torch.randn(*s, dtype=torch.bfloat16) * 0.8)(D, ks) * 0.5),
            "ssm_k": _w((lambda *s: torch.randn(*s, dtype=torch.bfloat16) * 3.2)(D, S) * (1.0 / S ** 0.5)),
            "ssm_D": _w((lambda *s: torch.randn(*s, dtype=torch.bfloat16) * 0.8)(D)),
        }
    _B_in = _B_setup()

    return {
        "A_x": _A_in["x"],
        "A_wqkv": _A_in["wqkv"],
        "A_wo": _A_in["wo"],
        "B_q": _B_in["q"],
        "B_k": _B_in["k"],
        "B_v": _B_in["v"],
        "B_shift_k": _B_in["shift_k"],
        "B_ssm_k": _B_in["ssm_k"],
        "B_ssm_D": _B_in["ssm_D"],
    }

def reference(A_x, A_wqkv, A_wo, B_q, B_k, B_v, B_shift_k, B_ssm_k, B_ssm_D):
    def _A_ref(x, wqkv, wo):
        B, S, D = x.shape
        H = 32; Dh = D // H
        qkv = (lambda x, *d: x.permute(*d))((x @ wqkv).reshape(B, S, 3, H, Dh), 2, 0, 3, 1, 4)
        q, k, v = qkv[0], qkv[1], qkv[2]
        phi = lambda t: torch.where(t > 0, t + 1, torch.exp(t)) + 1e-6
        pq, pk = phi(q), phi(k)
        kv = torch.einsum("bhsd,bhse->bhde", pk, v)
        z = torch.einsum("bhsd->bhd", pk)
        num = torch.einsum("bhqd,bhde->bhqe", pq, kv)
        den = torch.einsum("bhqd,bhd->bhq", pq, z)[..., None] + 1e-6
        o = num / den
        return (lambda x, *d: x.permute(*d))(o, 0, 2, 1, 3).reshape(B, S, D) @ wo

    def _B_ref(q, k, v, shift_k, ssm_k, ssm_D):
        B, S, D = q.shape
        ks = shift_k.shape[-1]
        k_pad = _pad(k, ((0, 0), (ks - 1, 0), (0, 0)))
        k_shift = torch.zeros_like(k)
        for t in range(ks):
            k_shift = k_shift + k_pad[:, t:t + S, :] * shift_k[:, ks - 1 - t][None, None, :]
        kv = k_shift * v
        L = 2 * S
        kv_pad = _pad(kv, ((0, 0), (0, S), (0, 0)))
        kf_pad = _pad(ssm_k, ((0, 0), (0, S)))
        kv_f = (lambda x, axes=(-2,-1): torch.fft.rfft2(x.float(), dim=axes))(kv_pad[:, None, :, :], axes=(1, 2))
        kf_f = (lambda x, axes=(-2,-1): torch.fft.rfft2(x.float(), dim=axes))(kf_pad[:, None, :], axes=(1, 2))
        kf_f = (lambda x, *d: x.permute(*d))(kf_f, 1, 2, 0)
        y_f = kv_f * kf_f[None, :, :, :]
        y = (lambda x, s, axes=(-2,-1): torch.fft.irfft2(x, s=s, dim=axes).to(torch.bfloat16))(y_f, (1, L), axes=(1, 2))[:, 0, :S, :]
        y = y + kv * ssm_D[None, None, :]
        return q * y

    a = _A_ref(A_x, A_wqkv, A_wo)
    b = _B_ref(B_q, B_k, B_v, B_shift_k, B_ssm_k, B_ssm_D)
    return torch.concatenate([a, b], axis=-1)
```

```cpp
#include <cuda.h>
#include <cuda_runtime.h>
#include <cuda_bf16.h>
#include <stdint.h>

#define DEVI __device__ __forceinline__

namespace {

DEVI void mma_nt(float* d, uint64_t da, uint64_t db, int sd) {
  asm volatile("{\n.reg .pred p;\nsetp.ne.b32 p, %66, 0;\nwgmma.mma_async.sync.aligned.m64n128k16.f32.bf16.bf16 {%0, %1, %2, %3, %4, %5, %6, %7, %8, %9, %10, %11, %12, %13, %14, %15, %16, %17, %18, %19, %20, %21, %22, %23, %24, %25, %26, %27, %28, %29, %30, %31, %32, %33, %34, %35, %36, %37, %38, %39, %40, %41, %42, %43, %44, %45, %46, %47, %48, %49, %50, %51, %52, %53, %54, %55, %56, %57, %58, %59, %60, %61, %62, %63}, %64, %65, p, 1, 1, 0, 1;\n}\n"
    : "+f"(d[0]), "+f"(d[1]), "+f"(d[2]), "+f"(d[3]), "+f"(d[4]), "+f"(d[5]), "+f"(d[6]), "+f"(d[7]), "+f"(d[8]), "+f"(d[9]), "+f"(d[10]), "+f"(d[11]), "+f"(d[12]), "+f"(d[13]), "+f"(d[14]), "+f"(d[15]), "+f"(d[16]), "+f"(d[17]), "+f"(d[18]), "+f"(d[19]), "+f"(d[20]), "+f"(d[21]), "+f"(d[22]), "+f"(d[23]), "+f"(d[24]), "+f"(d[25]), "+f"(d[26]), "+f"(d[27]), "+f"(d[28]), "+f"(d[29]), "+f"(d[30]), "+f"(d[31]), "+f"(d[32]), "+f"(d[33]), "+f"(d[34]), "+f"(d[35]), "+f"(d[36]), "+f"(d[37]), "+f"(d[38]), "+f"(d[39]), "+f"(d[40]), "+f"(d[41]), "+f"(d[42]), "+f"(d[43]), "+f"(d[44]), "+f"(d[45]), "+f"(d[46]), "+f"(d[47]), "+f"(d[48]), "+f"(d[49]), "+f"(d[50]), "+f"(d[51]), "+f"(d[52]), "+f"(d[53]), "+f"(d[54]), "+f"(d[55]), "+f"(d[56]), "+f"(d[57]), "+f"(d[58]), "+f"(d[59]), "+f"(d[60]), "+f"(d[61]), "+f"(d[62]), "+f"(d[63])
    : "l"(da), "l"(db), "r"(sd));
}
DEVI void mma_tn(float* d, uint64_t da, uint64_t db, int sd) {
  asm volatile("{\n.reg .pred p;\nsetp.ne.b32 p, %66, 0;\nwgmma.mma_async.sync.aligned.m64n128k16.f32.bf16.bf16 {%0, %1, %2, %3, %4, %5, %6, %7, %8, %9, %10, %11, %12, %13, %14, %15, %16, %17, %18, %19, %20, %21, %22, %23, %24, %25, %26, %27, %28, %29, %30, %31, %32, %33, %34, %35, %36, %37, %38, %39, %40, %41, %42, %43, %44, %45, %46, %47, %48, %49, %50, %51, %52, %53, %54, %55, %56, %57, %58, %59, %60, %61, %62, %63}, %64, %65, p, 1, 1, 1, 0;\n}\n"
    : "+f"(d[0]), "+f"(d[1]), "+f"(d[2]), "+f"(d[3]), "+f"(d[4]), "+f"(d[5]), "+f"(d[6]), "+f"(d[7]), "+f"(d[8]), "+f"(d[9]), "+f"(d[10]), "+f"(d[11]), "+f"(d[12]), "+f"(d[13]), "+f"(d[14]), "+f"(d[15]), "+f"(d[16]), "+f"(d[17]), "+f"(d[18]), "+f"(d[19]), "+f"(d[20]), "+f"(d[21]), "+f"(d[22]), "+f"(d[23]), "+f"(d[24]), "+f"(d[25]), "+f"(d[26]), "+f"(d[27]), "+f"(d[28]), "+f"(d[29]), "+f"(d[30]), "+f"(d[31]), "+f"(d[32]), "+f"(d[33]), "+f"(d[34]), "+f"(d[35]), "+f"(d[36]), "+f"(d[37]), "+f"(d[38]), "+f"(d[39]), "+f"(d[40]), "+f"(d[41]), "+f"(d[42]), "+f"(d[43]), "+f"(d[44]), "+f"(d[45]), "+f"(d[46]), "+f"(d[47]), "+f"(d[48]), "+f"(d[49]), "+f"(d[50]), "+f"(d[51]), "+f"(d[52]), "+f"(d[53]), "+f"(d[54]), "+f"(d[55]), "+f"(d[56]), "+f"(d[57]), "+f"(d[58]), "+f"(d[59]), "+f"(d[60]), "+f"(d[61]), "+f"(d[62]), "+f"(d[63])
    : "l"(da), "l"(db), "r"(sd));
}
DEVI void mma_kv_init(float* d, uint32_t a0, uint32_t a1, uint32_t a2, uint32_t a3, uint64_t db) {
  asm volatile("wgmma.mma_async.sync.aligned.m64n72k16.f32.bf16.bf16 {%0, %1, %2, %3, %4, %5, %6, %7, %8, %9, %10, %11, %12, %13, %14, %15, %16, %17, %18, %19, %20, %21, %22, %23, %24, %25, %26, %27, %28, %29, %30, %31, %32, %33, %34, %35}, {%36,%37,%38,%39}, %40, 0, 1, 1, 1;\n"
    : "=f"(d[0]), "=f"(d[1]), "=f"(d[2]), "=f"(d[3]), "=f"(d[4]), "=f"(d[5]), "=f"(d[6]), "=f"(d[7]), "=f"(d[8]), "=f"(d[9]), "=f"(d[10]), "=f"(d[11]), "=f"(d[12]), "=f"(d[13]), "=f"(d[14]), "=f"(d[15]), "=f"(d[16]), "=f"(d[17]), "=f"(d[18]), "=f"(d[19]), "=f"(d[20]), "=f"(d[21]), "=f"(d[22]), "=f"(d[23]), "=f"(d[24]), "=f"(d[25]), "=f"(d[26]), "=f"(d[27]), "=f"(d[28]), "=f"(d[29]), "=f"(d[30]), "=f"(d[31]), "=f"(d[32]), "=f"(d[33]), "=f"(d[34]), "=f"(d[35])
    : "r"(a0), "r"(a1), "r"(a2), "r"(a3), "l"(db));
}
DEVI void mma_kv_acc(float* d, uint32_t a0, uint32_t a1, uint32_t a2, uint32_t a3, uint64_t db) {
  asm volatile("wgmma.mma_async.sync.aligned.m64n72k16.f32.bf16.bf16 {%0, %1, %2, %3, %4, %5, %6, %7, %8, %9, %10, %11, %12, %13, %14, %15, %16, %17, %18, %19, %20, %21, %22, %23, %24, %25, %26, %27, %28, %29, %30, %31, %32, %33, %34, %35}, {%36,%37,%38,%39}, %40, 1, 1, 1, 1;\n"
    : "+f"(d[0]), "+f"(d[1]), "+f"(d[2]), "+f"(d[3]), "+f"(d[4]), "+f"(d[5]), "+f"(d[6]), "+f"(d[7]), "+f"(d[8]), "+f"(d[9]), "+f"(d[10]), "+f"(d[11]), "+f"(d[12]), "+f"(d[13]), "+f"(d[14]), "+f"(d[15]), "+f"(d[16]), "+f"(d[17]), "+f"(d[18]), "+f"(d[19]), "+f"(d[20]), "+f"(d[21]), "+f"(d[22]), "+f"(d[23]), "+f"(d[24]), "+f"(d[25]), "+f"(d[26]), "+f"(d[27]), "+f"(d[28]), "+f"(d[29]), "+f"(d[30]), "+f"(d[31]), "+f"(d[32]), "+f"(d[33]), "+f"(d[34]), "+f"(d[35])
    : "r"(a0), "r"(a1), "r"(a2), "r"(a3), "l"(db));
}
DEVI void mma_o_init(float* d, uint32_t a0, uint32_t a1, uint32_t a2, uint32_t a3, uint64_t db) {
  asm volatile("wgmma.mma_async.sync.aligned.m64n40k16.f32.bf16.bf16 {%0, %1, %2, %3, %4, %5, %6, %7, %8, %9, %10, %11, %12, %13, %14, %15, %16, %17, %18, %19}, {%20,%21,%22,%23}, %24, 0, 1, 1, 1;\n"
    : "=f"(d[0]), "=f"(d[1]), "=f"(d[2]), "=f"(d[3]), "=f"(d[4]), "=f"(d[5]), "=f"(d[6]), "=f"(d[7]), "=f"(d[8]), "=f"(d[9]), "=f"(d[10]), "=f"(d[11]), "=f"(d[12]), "=f"(d[13]), "=f"(d[14]), "=f"(d[15]), "=f"(d[16]), "=f"(d[17]), "=f"(d[18]), "=f"(d[19])
    : "r"(a0), "r"(a1), "r"(a2), "r"(a3), "l"(db));
}
DEVI void mma_o_acc(float* d, uint32_t a0, uint32_t a1, uint32_t a2, uint32_t a3, uint64_t db) {
  asm volatile("wgmma.mma_async.sync.aligned.m64n40k16.f32.bf16.bf16 {%0, %1, %2, %3, %4, %5, %6, %7, %8, %9, %10, %11, %12, %13, %14, %15, %16, %17, %18, %19}, {%20,%21,%22,%23}, %24, 1, 1, 1, 1;\n"
    : "+f"(d[0]), "+f"(d[1]), "+f"(d[2]), "+f"(d[3]), "+f"(d[4]), "+f"(d[5]), "+f"(d[6]), "+f"(d[7]), "+f"(d[8]), "+f"(d[9]), "+f"(d[10]), "+f"(d[11]), "+f"(d[12]), "+f"(d[13]), "+f"(d[14]), "+f"(d[15]), "+f"(d[16]), "+f"(d[17]), "+f"(d[18]), "+f"(d[19])
    : "r"(a0), "r"(a1), "r"(a2), "r"(a3), "l"(db));
}
DEVI void fft1_init(uint32_t* d, uint32_t a0, uint32_t a1, uint32_t a2, uint32_t a3, uint64_t db) {
  asm volatile("wgmma.mma_async.sync.aligned.m64n128k16.f16.f16.f16 {%0, %1, %2, %3, %4, %5, %6, %7, %8, %9, %10, %11, %12, %13, %14, %15, %16, %17, %18, %19, %20, %21, %22, %23, %24, %25, %26, %27, %28, %29, %30, %31}, {%32,%33,%34,%35}, %36, 0, 1, 1, 1;\n"
    : "=r"(d[0]), "=r"(d[1]), "=r"(d[2]), "=r"(d[3]), "=r"(d[4]), "=r"(d[5]), "=r"(d[6]), "=r"(d[7]), "=r"(d[8]), "=r"(d[9]), "=r"(d[10]), "=r"(d[11]), "=r"(d[12]), "=r"(d[13]), "=r"(d[14]), "=r"(d[15]), "=r"(d[16]), "=r"(d[17]), "=r"(d[18]), "=r"(d[19]), "=r"(d[20]), "=r"(d[21]), "=r"(d[22]), "=r"(d[23]), "=r"(d[24]), "=r"(d[25]), "=r"(d[26]), "=r"(d[27]), "=r"(d[28]), "=r"(d[29]), "=r"(d[30]), "=r"(d[31])
    : "r"(a0), "r"(a1), "r"(a2), "r"(a3), "l"(db));
}
DEVI void fft1_acc(uint32_t* d, uint32_t a0, uint32_t a1, uint32_t a2, uint32_t a3, uint64_t db) {
  asm volatile("wgmma.mma_async.sync.aligned.m64n128k16.f16.f16.f16 {%0, %1, %2, %3, %4, %5, %6, %7, %8, %9, %10, %11, %12, %13, %14, %15, %16, %17, %18, %19, %20, %21, %22, %23, %24, %25, %26, %27, %28, %29, %30, %31}, {%32,%33,%34,%35}, %36, 1, 1, 1, 1;\n"
    : "+r"(d[0]), "+r"(d[1]), "+r"(d[2]), "+r"(d[3]), "+r"(d[4]), "+r"(d[5]), "+r"(d[6]), "+r"(d[7]), "+r"(d[8]), "+r"(d[9]), "+r"(d[10]), "+r"(d[11]), "+r"(d[12]), "+r"(d[13]), "+r"(d[14]), "+r"(d[15]), "+r"(d[16]), "+r"(d[17]), "+r"(d[18]), "+r"(d[19]), "+r"(d[20]), "+r"(d[21]), "+r"(d[22]), "+r"(d[23]), "+r"(d[24]), "+r"(d[25]), "+r"(d[26]), "+r"(d[27]), "+r"(d[28]), "+r"(d[29]), "+r"(d[30]), "+r"(d[31])
    : "r"(a0), "r"(a1), "r"(a2), "r"(a3), "l"(db));
}
DEVI void fft2_init(uint32_t* d, uint32_t a0, uint32_t a1, uint32_t a2, uint32_t a3, uint64_t db) {
  asm volatile("wgmma.mma_async.sync.aligned.m64n32k16.f16.f16.f16 {%0, %1, %2, %3, %4, %5, %6, %7}, {%8,%9,%10,%11}, %12, 0, 1, 1, 0;\n"
    : "=r"(d[0]), "=r"(d[1]), "=r"(d[2]), "=r"(d[3]), "=r"(d[4]), "=r"(d[5]), "=r"(d[6]), "=r"(d[7])
    : "r"(a0), "r"(a1), "r"(a2), "r"(a3), "l"(db));
}
DEVI void fft2_acc(uint32_t* d, uint32_t a0, uint32_t a1, uint32_t a2, uint32_t a3, uint64_t db) {
  asm volatile("wgmma.mma_async.sync.aligned.m64n32k16.f16.f16.f16 {%0, %1, %2, %3, %4, %5, %6, %7}, {%8,%9,%10,%11}, %12, 1, 1, 1, 0;\n"
    : "+r"(d[0]), "+r"(d[1]), "+r"(d[2]), "+r"(d[3]), "+r"(d[4]), "+r"(d[5]), "+r"(d[6]), "+r"(d[7])
    : "r"(a0), "r"(a1), "r"(a2), "r"(a3), "l"(db));
}
DEVI void fft3_init(float* d, uint64_t da, uint64_t db) {
  asm volatile("wgmma.mma_async.sync.aligned.m64n32k16.f32.f16.f16 {%0, %1, %2, %3, %4, %5, %6, %7, %8, %9, %10, %11, %12, %13, %14, %15}, %16, %17, 0, 1, 1, 1, 0;\n"
    : "=f"(d[0]), "=f"(d[1]), "=f"(d[2]), "=f"(d[3]), "=f"(d[4]), "=f"(d[5]), "=f"(d[6]), "=f"(d[7]), "=f"(d[8]), "=f"(d[9]), "=f"(d[10]), "=f"(d[11]), "=f"(d[12]), "=f"(d[13]), "=f"(d[14]), "=f"(d[15])
    : "l"(da), "l"(db));
}
DEVI void fft3_acc(float* d, uint64_t da, uint64_t db) {
  asm volatile("wgmma.mma_async.sync.aligned.m64n32k16.f32.f16.f16 {%0, %1, %2, %3, %4, %5, %6, %7, %8, %9, %10, %11, %12, %13, %14, %15}, %16, %17, 1, 1, 1, 1, 0;\n"
    : "+f"(d[0]), "+f"(d[1]), "+f"(d[2]), "+f"(d[3]), "+f"(d[4]), "+f"(d[5]), "+f"(d[6]), "+f"(d[7]), "+f"(d[8]), "+f"(d[9]), "+f"(d[10]), "+f"(d[11]), "+f"(d[12]), "+f"(d[13]), "+f"(d[14]), "+f"(d[15])
    : "l"(da), "l"(db));
}

__device__ __align__(128) const uint32_t g_tables[2560] = {
0xa11ba1e4,0xa51ba5e4,0x18b61248,0x1cb61648,0x9f12a052,0xa311a452,0x1d7f1bdb,0x217f1fdb,0x9bdb9d7f,0x9fdba17f,0x20521f12,0x24522311,
0x924898b6,0x96489cb6,0x21e4211b,0x25e4251b,0xaa63ab5f,0xae5faf59,0x21e41bdb,0x25e41fdb,0xa86ba967,0xac6aad65,0x26e024e9,0x2ade28e8,
0xa4e9a6e0,0xa8e8aade,0x2967286b,0x2d652c6a,0x9bdba1e4,0x9fdba5e4,0x2b5f2a63,0x2f592e5f,0xadc2aea7,0xb1b6b294,0x254d1f12,0x294d2311,
0xabf6acde,0xafefb0d7,0x2a31286b,0x2e2d2c6a,0xa86baa31,0xac6aae2d,0x2cde2bf6,0x30d72fef,0x9f12a54d,0xa311a94d,0x2ea72dc2,0x329431b6,
0xb02cb0d2,0xb41ab4b7,0x27a9211b,0x2ba7251b,0xadc2af0c,0xb1b6b2f7,0x2c792a63,0x30742e5f,0xaa63ac79,0xae5fb074,0x2f0c2dc2,0x32f731b6,
0xa11ba7a9,0xa51baba7,0x30d2302c,0x34b7341a,0xb17ab257,0xb552b61a,0x290222ad,0x2d0026ad,0xaf8cb09f,0xb371b487,0x2ddc2c2e,0x31cf3029,
0xac2eaddc,0xb029b1cf,0x309f2f8c,0x34873371,0xa2ada902,0xa6adad00,0x3257317a,0x361a3552,0xb2cdb3e3,0xb682b76f,0x2a312420,0x2e2d281f,
0xb0acb1bb,0xb493b58d,0x2f3f2d2a,0x33283122,0xad2aaf3f,0xb122b328,0x31bb30ac,0x358d3493,0xa420aa31,0xa81fae2d,0x33e332cd,0x376f3682,
0xb413b4bc,0xb7a6b85a,0x2b5f24e9,0x2f5928e8,0xb194b2da,0xb56ab68d,0x30522e28,0x343e3219,0xae28b052,0xb219b43e,0x32da3194,0x368d356a,
0xa4e9ab5f,0xa8e8af59,0x34bc3413,0x385a37a6,0xb4c3b58c,0xb85fb8f3,0x2c4725b2,0x304229b1,0xb27eb3fd,0xb63cb785,0x31062f26,0x34e7330f,
0xaf26b106,0xb30fb4e7,0x33fd327e,0x3785363c,0xa5b2ac47,0xa9b1b042,0x358c34c3,0x38f3385f,0xb577b662,0xb8e5b982,0x2cde267b,0x30d72a7a,
0xb36bb493,0xb70ab83a,0x31bb3012,0x358d3402,0xb012b1bb,0xb402b58d,0x3493336b,0x383a370a,0xa67bacde,0xaa7ab0d7,0x36623577,0x398238e5,
0xb630b741,0xb962ba04,0x2d762744,0x316c2b43,0xb42eb52a,0xb7d2b8ad,0x32713092,0x3631347b,0xb092b271,0xb47bb631,0x352a342e,0x38ad37d2,
0xa744ad76,0xab43b16c,0x37413630,0x3a043962,0xb6eeb815,0xb9d6ba7a,0x2e0e2807,0x32012c06,0xb4a7b5c4,0xb84ab91b,0x33293113,0x36d234f3,
0xb113b329,0xb4f3b6d2,0x35c434a7,0x391b384a,0xa807ae0e,0xac06b201,0x381536ee,0x3a7a39d6,0xb7b4b88e,0xba41bae1,0x2ea7286b,0x32942c6a,
0xb523b662,0xb8a8b982,0x33e33194,0x376f356a,0xb194b3e3,0xb56ab76f,0x36623523,0x398238a8,0xa86baea7,0xac6ab294,0x388e37b4,0x3ae13a41,
0xb841b90f,0xbaa2bb3a,0x2f3f28d0,0x33282cce,0xb5a1b705,0xb902b9e3,0x344f3216,0x380535df,0xb216b44f,0xb5dfb805,0x370535a1,0x39e33902,
0xa8d0af3f,0xacceb328,0x390f3841,0x3b3a3aa2,0xb8acb997,0xbaf7bb83,0x2fd82935,0x33ba2d33,0xb621b7ac,0xb958ba3d,0x34ae3298,0x38503654,
0xb298b4ae,0xb654b850,0x37ac3621,0x3a3d3958,0xa935afd8,0xad33b3ba,0x399738ac,0x3b833af7,0xb91cba28,0xbb42bbbc,0x30392999,0x34262d97,
0xb6a4b82d,0xb9aaba90,0x350e331c,0x389936c6,0xb31cb50e,0xb6c6b899,0x382d36a4,0x3a9039aa,0xa999b039,0xad97b426,0x3a28391c,0x3bbc3b42,
0xb992bac3,0xbb81bbe3,0x308529fe,0x346f2dfb,0xb72ab886,0xb9f8badb,0x357033a0,0x38e03737,0xb3a0b570,0xb737b8e0,0x3886372a,0x3adb39f8,
0xa9feb085,0xadfbb46f,0x3ac33992,0x3be33b81,0x39cf3b16,0x3b9c3bf1,0xb0acaa31,0xb493ae2d,0x376f38b4,0x3a1d3afe,0xb5a1b3e3,0xb902b76f,
0x33e335a1,0x376f3902,0xb8b4b76f,0xbafeba1d,0x2a3130ac,0x2e2d3493,0xbb16b9cf,0xbbf1bb9c,0x39563a74,0x3b633bd2,0xb05fa9cc,0xb44badc9,
0x36e73859,0x39d23ab6,0xb53fb35e,0xb8bcb6ff,0x335e353f,0x36ff38bc,0xb859b6e7,0xbab6b9d2,0x29cc305f,0x2dc9344b,0xba74b956,0xbbd2bb63,
0x38e339de,0x3b1e3ba1,0xb012a967,0xb402ad65,0x36623801,0x39823a67,0xb4deb2da,0xb874b68d,0x32da34de,0x368d3874,0xb801b662,0xba67b982,
0x29673012,0x2d653402,0xb9deb8e3,0xbba1bb1e,0x38763952,0x3ace3b60,0xaf8ca902,0xb371ad00,0x35e13758,0x392e3a11,0xb47eb257,0xb82ab61a,
0x3257347e,0x361a382a,0xb758b5e1,0xba11b92e,0x29022f8c,0x2d003371,0xb952b876,0xbb60bace,0x380d38ce,0x3a733b10,0xaef3a89e,0xb2deac9c,
0x356236b3,0x38d639b3,0xb420b1d5,0xb7bdb5a5,0x31d53420,0x35a537bd,0xb6b3b562,0xb9b3b8d6,0x289e2ef3,0x2c9c32de,0xb8ceb80d,0xbb10ba73,
0x37503851,0x3a0d3ab0,0xae5aa839,0xb24bac38,0x34e53613,0x387a394f,0xb386b153,0xb721b52f,0x31533386,0x352f3721,0xb613b4e5,0xb94fb87a,
0x28392e5a,0x2c38324b,0xb851b750,0xbab0ba0d,0x368e37b4,0x399d3a41,0xadc2a7a9,0xb1b6aba7,0x346a3577,0x381a38e5,0xb2cdb0d2,0xb682b4b7,
0x30d232cd,0x34b73682,0xb577b46a,0xb8e5b81a,0x27a92dc2,0x2ba731b6,0xb7b4b68e,0xba41b99d,0x35d236d1,0x392439c5,0xad2aa6e0,0xb122aade,
0x33e334de,0x376f3874,0xb216b052,0xb5dfb43e,0x30523216,0x343e35df,0xb4deb3e3,0xb874b76f,0x26e02d2a,0x2ade3122,0xb6d1b5d2,0xb9c5b924,
0x351c35f6,0x38a3393c,0xac93a617,0xb08daa16,0x32f43448,0x36a437fe,0xb160afa5,0xb53ab389,0x2fa53160,0x3389353a,0xb448b2f4,0xb7feb6a4,
0x26172c93,0x2a16308d,0xb5f6b51c,0xb93cb8a3,0x346a3523,0x381a38a8,0xabf6a54d,0xafefa94d,0x3209336b,0x35d4370a,0xb0acaea7,0xb493b294,
0x2ea730ac,0x32943493,0xb36bb209,0xb70ab5d4,0x254d2bf6,0x294d2fef,0xb523b46a,0xb8a8b81a,0x33783456,0x3715380a,0xaac8a484,0xaec3a884,
0x3120324a,0x34ff360e,0xaff2ada9,0xb3d3b19e,0x2da92ff2,0x319e33d3,0xb24ab120,0xb60eb4ff,0x24842ac8,0x28842ec3,0xb456b378,0xb80ab715,
0x3223331c,0x35eb36c6,0xa999a376,0xad97a776,0x3039312d,0x3426350b,0xae8dacac,0xb27cb0a6,0x2cac2e8d,0x30a6327c,0xb12db039,0xb50bb426,
0x23762999,0x27762d97,0xb31cb223,0xb6c6b5eb,0x30d23194,0x34b7356a,0xa86ba1e4,0xac6aa5e4,0x2ea73012,0x32943402,0xad2aab5f,0xb122af59,
0x2b5f2d2a,0x2f593122,0xb012aea7,0xb402b294,0x21e4286b,0x25e42c6a,0xb194b0d2,0xb56ab4b7,0x2f0c3012,0x32f73402,0xa67ba052,0xaa7aa452,
0x2cde2df5,0x30d731e8,0xab91a967,0xaf8bad65,0x29672b91,0x2d652f8b,0xadf5acde,0xb1e8b0d7,0x2052267b,0x24522a7a,0xb012af0c,0xb402b2f7,
0x2c792d2a,0x30743122,0xa4209d7f,0xa81fa17f,0x2a312b91,0x2e2d2f8b,0xa8d0a6e0,0xacceaade,0x26e028d0,0x2ade2cce,0xab91aa31,0xaf8bae2d,
0x1d7f2420,0x217f281f,0xad2aac79,0xb122b074,0x27a9286b,0x2ba72c6a,0x9f1298b6,0xa3119cb6,0x254d267b,0x294d2a7a,0xa420a1e4,0xa81fa5e4,
0x21e42420,0x25e4281f,0xa67ba54d,0xaa7aa94d,0x18b61f12,0x1cb62311,0xa86ba7a9,0xac6aaba7,0x3f803f80,0x3f803f80,0x3f803f80,0x3f803f80,
0x3f803f80,0x3f803f80,0x3f803f80,0x3f803f80,0x3f803f80,0x3f803f80,0x3f803f80,0x3f803f80,0x3f803f80,0x3f803f80,0x3f803f80,0x3f803f80,
0x3f803f80,0x3f803f80,0x3f803f80,0x3f803f80,0x3f803f80,0x3f803f80,0x3f803f80,0x3f803f80,0x3f803f80,0x3f803f80,0x3f803f80,0x3f803f80,
0x3f803f80,0x3f803f80,0x3f803f80,0x3f803f80,0x3f803f80,0x3f803f80,0x3f803f80,0x3f803f80,0x3f803f80,0x3f803f80,0x3f803f80,0x3f803f80,
0x3f803f80,0x3f803f80,0x3f803f80,0x3f803f80,0x3f803f80,0x3f803f80,0x3f803f80,0x3f803f80,0x3f803f80,0x3f803f80,0x3f803f80,0x3f803f80,
0x3f803f80,0x3f803f80,0x3f803f80,0x3f803f80,0x3f803f80,0x3f803f80,0x3f803f80,0x3f803f80,0x3f803f80,0x3f803f80,0x3f803f80,0x3f803f80,
0x3f803f80,0x3f803f80,0x3f803f80,0x3f803f80,0x3f803f80,0x3f803f80,0x3f803f80,0x3f803f80,0x3f803f80,0x3f803f80,0x3f803f80,0x3f803f80,
0x3f803f80,0x3f803f80,0x3f803f80,0x3f803f80,0x3f803f80,0x3f803f80,0x3f803f80,0x3f803f80,0x3f803f80,0x3f803f80,0x3f803f80,0x3f803f80,
0x3f803f80,0x3f803f80,0x3f803f80,0x3f803f80,0x3f803f80,0x3f803f80,0x3f803f80,0x3f803f80,0x3f803f80,0x3f803f80,0x3f803f80,0x3f803f80,
0x3f803f80,0x3f803f80,0x3f803f80,0x3f803f80,0x3f803f80,0x3f803f80,0x3f803f80,0x3f803f80,0x3f803f80,0x3f803f80,0x3f803f80,0x3f803f80,
0x3f803f80,0x3f803f80,0x3f803f80,0x3f803f80,0x3f803f80,0x3f803f80,0x3f803f80,0x3f803f80,0x3f803f80,0x3f803f80,0x3f803f80,0x3f803f80,
0x3f803f80,0x3f803f80,0x3f803f80,0x3f803f80,0x3f803f80,0x3f803f80,0x3f803f80,0x3f803f80,0x3f803f80,0x3f803f80,0x3f803f80,0x3f803f80,
0x3f803f80,0x3f803f80,0x3f803f80,0x3f803f80,0x3f803f80,0x3f803f80,0x3f803f80,0x3f803f80,0x3f803f80,0x3f803f80,0x3f803f80,0x3f803f80,
0x3f803f80,0x3f803f80,0x3f803f80,0x3f803f80,0x3f803f80,0x3f803f80,0x3f803f80,0x3f803f80,0x3f803f80,0x3f803f80,0x3f803f80,0x3f803f80,
0x3f803f80,0x3f803f80,0x3f803f80,0x3f803f80,0x3f803f80,0x3f803f80,0x3f803f80,0x3f803f80,0x3f803f80,0x3f803f80,0x3f803f80,0x3f803f80,
0x3f803f80,0x3f803f80,0x3f803f80,0x3f803f80,0x3f803f80,0x3f803f80,0x3f803f80,0x3f803f80,0x3f803f80,0x3f803f80,0x3f803f80,0x3f803f80,
0x3f803f80,0x3f803f80,0x3f803f80,0x3f803f80,0x3f803f80,0x3f803f80,0x3f803f80,0x3f803f80,0x3f803f80,0x3f803f80,0x3f803f80,0x3f803f80,
0x3f803f80,0x3f803f80,0x3f803f80,0x3f803f80,0x3f803f80,0x3f803f80,0x3f803f80,0x3f803f80,0x3f803f80,0x3f803f80,0x3f803f80,0x3f803f80,
0x3f803f80,0x3f803f80,0x3f803f80,0x3f803f80,0x3f803f80,0x3f803f80,0x3f803f80,0x3f803f80,0x3f803f80,0x3f803f80,0x3f803f80,0x3f803f80,
0x3f803f80,0x3f803f80,0x3f803f80,0x3f803f80,0x3f803f80,0x3f803f80,0x3f803f80,0x3f803f80,0x3f803f80,0x3f803f80,0x3f803f80,0x3f803f80,
0x3f803f80,0x3f803f80,0x3f803f80,0x3f803f80,0x3f803f80,0x3f803f80,0x3f803f80,0x3f803f80,0x3f803f80,0x3f803f80,0x3f803f80,0x3f803f80,
0x3f803f80,0x3f803f80,0x3f803f80,0x3f803f80,0x3f803f80,0x3f803f80,0x3f803f80,0x3f803f80,0x3f803f80,0x3f803f80,0x3f803f80,0x3f803f80,
0x3f803f80,0x3f803f80,0x3f803f80,0x3f803f80,0x3f803f80,0x3f803f80,0x3f803f80,0x3f803f80,0x3f803f80,0x3f803f80,0x3f803f80,0x3f803f80,
0x3f803f80,0x3f803f80,0x3f803f80,0x3f803f80,0x3f803f80,0x3f803f80,0x3f803f80,0x3f803f80,0x3f803f80,0x3f803f80,0x3f803f80,0x3f803f80,
0x3f803f80,0x3f803f80,0x3f803f80,0x3f803f80,0x3f803f80,0x3f803f80,0x3f803f80,0x3f803f80,0x3f803f80,0x3f803f80,0x3f803f80,0x3f803f80,
0x3f803f80,0x3f803f80,0x3f803f80,0x3f803f80,0x3f803f80,0x3f803f80,0x3f803f80,0x3f803f80,0x3f803f80,0x3f803f80,0x3f803f80,0x3f803f80,
0x3f803f80,0x3f803f80,0x3f803f80,0x3f803f80,0x3f803f80,0x3f803f80,0x3f803f80,0x3f803f80,0x3f803f80,0x3f803f80,0x3f803f80,0x3f803f80,
0x3f803f80,0x3f803f80,0x3f803f80,0x3f803f80,0x3f803f80,0x3f803f80,0x3f803f80,0x3f803f80,0x3f803f80,0x3f803f80,0x3f803f80,0x3f803f80,
0x3f803f80,0x3f803f80,0x3f803f80,0x3f803f80,0x3f803f80,0x3f803f80,0x3f803f80,0x3f803f80,0x3f803f80,0x3f803f80,0x3f803f80,0x3f803f80,
0x3f803f80,0x3f803f80,0x3f803f80,0x3f803f80,0x3f803f80,0x3f803f80,0x3f803f80,0x3f803f80,0x3f803f80,0x3f803f80,0x3f803f80,0x3f803f80,
0x3f803f80,0x3f803f80,0x3f803f80,0x3f803f80,0x3f803f80,0x3f803f80,0x3f803f80,0x3f803f80,0x3f803f80,0x3f803f80,0x3f803f80,0x3f803f80,
0x3f803f80,0x3f803f80,0x3f803f80,0x3f803f80,0x3f803f80,0x3f803f80,0x3f803f80,0x3f803f80,0x3f803f80,0x3f803f80,0x3f803f80,0x3f803f80,
0x3f803f80,0x3f803f80,0x3f803f80,0x3f803f80,0x3f803f80,0x3f803f80,0x3f803f80,0x3f803f80,0x3f803f80,0x3f803f80,0x3f803f80,0x3f803f80,
0x3f803f80,0x3f803f80,0x3f803f80,0x3f803f80,0x3f803f80,0x3f803f80,0x3f803f80,0x3f803f80,0x3f803f80,0x3f803f80,0x3f803f80,0x3f803f80,
0x3f803f80,0x3f803f80,0x3f803f80,0x3f803f80,0x3f803f80,0x3f803f80,0x3f803f80,0x3f803f80,0x3f803f80,0x3f803f80,0x3f803f80,0x3f803f80,
0x3f803f80,0x3f803f80,0x3f803f80,0x3f803f80,0x3f803f80,0x3f803f80,0x3f803f80,0x3f803f80,0x3f803f80,0x3f803f80,0x3f803f80,0x3f803f80,
0x3f803f80,0x3f803f80,0x3f803f80,0x3f803f80,0x3f803f80,0x3f803f80,0x3f803f80,0x3f803f80,0x3f803f80,0x3f803f80,0x3f803f80,0x3f803f80,
0x3f803f80,0x3f803f80,0x3f803f80,0x3f803f80,0x3f803f80,0x3f803f80,0x3f803f80,0x3f803f80,0x3f803f80,0x3f803f80,0x3f803f80,0x3f803f80,
0x3f803f80,0x3f803f80,0x3f803f80,0x3f803f80,0x3f803f80,0x3f803f80,0x3f803f80,0x3f803f80,0x3f803f80,0x3f803f80,0x3f803f80,0x3f803f80,
0x3f803f80,0x3f803f80,0x3f803f80,0x3f803f80,0x3f803f80,0x3f803f80,0x3f803f80,0x3f803f80,0x3f803f80,0x3f803f80,0x3f803f80,0x3f803f80,
0x3f803f80,0x3f803f80,0x3f803f80,0x3f803f80,0x3f803f80,0x3f803f80,0x3f803f80,0x3f803f80,0x3f803f80,0x3f803f80,0x3f803f80,0x3f803f80,
0x3f803f80,0x3f803f80,0x3f803f80,0x3f803f80,0x3f803f80,0x3f803f80,0x3f803f80,0x3f803f80,0x3f803f80,0x3f803f80,0x3f803f80,0x3f803f80,
0x3f803f80,0x3f803f80,0x3f803f80,0x3f803f80,0x3f803f80,0x3f803f80,0x3f803f80,0x3f803f80,0x3f803f80,0x3f803f80,0x3f803f80,0x3f803f80,
0x3f803f80,0x3f803f80,0x3f803f80,0x3f803f80,0x3bf23bff,0x3ba53bd4,0x3b163b65,0x3a493ab6,0x3b7c3bfb,0x38bc3a60,0x2b43356a,0xb7f3b359,
0x3a933bf1,0x9cb63764,0xba9eb785,0xbb73bbf3,0x39463be2,0xb8cc28e8,0xbb42bbc2,0x3328b70a,0x374e3bcf,0xbbabb648,0xaec3baa9,0x3bfa3994,
0x33403bb7,0xbb85b9fc,0x3a64b0be,0x2c6a3b47,0xa4523b9a,0xb86abbae,0x3b6a3911,0xbbd0ad65,0xb4263b78,0x2adebbe6,0x30f03bfd,0xb5b1bbbc,
0x2f5925e4,0x34b73294,0x376f361a,0x38f3385a,0x35a52c9c,0x3a7338d6,0x3bfd3b87,0x3af13bc9,0x388e2fbd,0x3c003b18,0x387f3b10,0xb5d42f27,
0x3a04316c,0x3a673bfe,0xb6bb33d3,0xbbccbb2f,0x3b1e32f7,0x34933b5c,0xbbf5b86f,0x2d00b9bc,0x3bcb343e,0xb576394f,0xb8d1bbe9,0x3bfb36a4,
0x3c0034ff,0xbaac347b,0x3602ba31,0x32de3bf9,0x3bba35bc,0xbbfdb109,0x3be7aa7a,0xbb7a341a,0x394639cd,0x381538b2,0x358136dd,0x3153341a,
0xbb1eb9c9,0xbbf5bbdd,0xba39bb65,0xb4f3b889,0xb340b93c,0x3966340e,0x3bec3b87,0x37213a7e,0x3c003a4d,0x32193a21,0xbb5eb785,0xb894bbb0,
0xb426389e,0xbb37bb45,0x38b7b3d3,0x397d3bfc,0xbafebac1,0x3b13217f,0xadc93aa9,0xba49bb59,0x3979b7e8,0xb0d73b32,0xb6f4bbe9,0x3af139da,
0x38553b24,0xb9a1ba3d,0x3ab03911,0xbb73b759,0x3a043982,0x3ae13a7a,0x3b833b3a,0x3be33bbc,0x374e3986,0xae9131e8,0xb907b61a,0xbb9cba97,
0xbbcbba0d,0xb9e7bbbd,0x3074b56a,0x3b2a38ad,0x2452b8ee,0x3bda3924,0x363c3b10,0xba90b46f,0x3bba3a89,0xb6e836af,0xba76bbc2,0x39d2ac06,
0xb7c8384a,0xb77abc00,0x3bf8386f,0xb8f33654,0xb9d6baf4,0x3be836ff,0xbb3530be,0x37f3b974,0x3abab737,0xb9af3902,0x3865ba31,0xb5d43b1b,
0x32c62fbd,0x363134cf,0x38653785,0x398b38fd,0xb715b16c,0xbae1b970,0xbbfebbc2,0xba85bb92,0x392e32f7,0x3bf53b6c,0x37a63aa9,0xb7422311,
0xba81b43e,0xb9e7bbfc,0x380fb0be,0x3b963b7f,0x3b7134ff,0x32193b04,0xbc00b911,0x319eb929,0xbbefb5bc,0x36e8b8b2,0x382a3bfd,0xbbffb805,
0x3bf23676,0xbb1331e8,0x376fb9aa,0x2f8b3bde,0xbb7cb72c,0x3be8340e,0xbbfdaa16,0x3bb8b122,0xbbd2bbf1,0xbb60bba1,0xbab0bb10,0xb9c5ba41,
0x3b2c3be2,0x381539df,0xa94d33d3,0xb8a3b52f,0xba19bbcf,0x2e91b5f7,0x3b07386f,0x3b213c00,0x38a83bb7,0xb966aba7,0xbae5bbe9,0x3517b599,
0xb5dfbb9a,0x3bda37b2,0x1fdb3a31,0xbbe0ba1d,0x30293b78,0xbb37ba7a,0x3ad5aa7a,0xa7763aeb,0x2f59bb52,0x377a3bdd,0xbb16b9a6,0x3bf231cf,
0xb5a53b27,0x30d7bbbd,0x2b433bfe,0xb432bbe5,0x3a813a0d,0x3b3f3ae8,0x3bbf3b87,0x3bfb3be5,0xb5dfb8ee,0x3263ad97,0x399d3785,0x3bd03b01,
0xbbefba89,0xb958bb81,0x3389b3d3,0x3b7a394a,0xaf59384a,0xbbf7b9b8,0xb4c3baa9,0x3afb35eb,0x3b7c3af4,0xb825353a,0xb9f8bbe9,0x3a542884,
0x388eb737,0x360e3bf4,0xbbdcb911,0x398bb4db,0xb946bb4f,0x3bc03830,0xbb832a7a,0x38a3b8db,0xbb1e35c8,0x3a35b85f,0xb90739aa,0x3742bab6,
0xb8a8b93c,0xb6c6b80a,0xb402b56a,0xac6ab122,0xbb71ba4d,0xbbd7bbf8,0xb9b3bb10,0xb2deb7bd,0x3029389e,0xb9f4b58d,0xbbc6bbc2,0xb5b1ba00,
0x3bf23ac1,0x2dfb3999,0xbba3b86f,0xb7d2bb6f,0x35a5b7e8,0x3ad83b90,0xb95430be,0xb8e5bbff,0xba93bb24,0x3b682ef5,0xb2013a31,0xb9c5bb9f,
0xba043682,0x33ebbad1,0x35813bfd,0xba85ba5c,0x374e3b76,0xb90cbab3,0x3a3939a6,0xbb21b85a,0xb7c83b52,0x391bba9b,0xba2539aa,0x3afbb889,
0xb9793b27,0x3bc5b80a,0xbb8eaa16,0x38e538ad,0xbaba3af7,0x3b60ad97,0xb27cba2d,0xb98b3bb0,0xbb943ac4,0x3815358d,0x39e3bbea,0xba852c06,
0xbbf93a8c,0xae9139b8,0x3bacb874,0x3742bb59,0xbbe43a50,0xb9663b90,0x340233ba,0x3b96b974,0xbb573a11,0xbbda3bf4,0xb99d3b0d,0xb19e3759,
0xba5839cd,0xbb373ad1,0xbbc63b89,0xbbff3bee,0x3afe3676,0xba29b884,0x391f39a6,0xb7d2ba97,0x39d6372c,0xb3a2bae8,0xb5463bfe,0x3a54ba7e,
0x385537dd,0x3631bbf8,0xbbd63916,0x39c5346f,0x35233845,0x3ae1bb81,0xb96bb0a6,0xb8a33bfc,0x2d333899,0x3bf5b999,0x3487baa5,0xbb213654,
0xb13b38ea,0x39e7b53a,0x3bbfbbc3,0x3517b9da,0xb65f3937,0x32192ef5,0x39b3b790,0x3be0bb1b,0xb8e03982,0xb6e83830,0xb389355e,0xa7763042,
0xbb943682,0x3bebb371,0xbbfe2a7a,0x3bcc3042,0xad33bb76,0xb79b3bd4,0x3b07b9aa,0xbbfa32ad,0x3be4b50b,0xb6c6b8d6,0xb80f3bfe,0x3bfbb835,
0xb65f3bb5,0x3bd7b764,0x9fdbba2d,0xbbd03a41,0xba58330f,0xb9f43bfe,0x382a30a6,0x3b7abb92,0x3a45bbe1,0xadfbb648,0xbb163874,0xbafb3c00,
0x3699afef,0x3ad8b94f,0x3bfdbbc3,0x3a54bb7f,0xbbdf3bfa,0xbb683bae,0xba9e3b0d,0xb98b3a1d,0x35233b4f,0xb08dbbc8,0xa94d3bfd,0x3328bbee,
0xbbf935c8,0x3b0a3294,0xb7a6b9a6,0xad003bd3,0x313bbb98,0xbb3f3a60,0x3ae52a16,0xac6abace,0x3b57b44b,0x3263bb18,0xbc003916,0x32de38fd,
0xb8e03bce,0x3958a8e8,0x3ad5bbea,0xb5b1b52f,0xb8f83185,0xbbf73b5c,0xb76f3aa5,0x37d2a311,0x3b4abbf0,0x3825b9fc,0xab43b3ba,0xb8e53599,
0x31b6acce,0x360eb47b,0x387fb790,0x39c5b929,0x3a9337dd,0xb9a1b924,0x387f3a2d,0xb66bbb01,0xb946b845,0x308d3b45,0x36bbbbea,0xbac73a00,
0x374e3899,0x379bbc00,0xbbf53874,0x393335eb,0xb340b8ea,0xbb3f3b32,0x38d133ba,0x3941bbff,0xa4523937,0x3bd7b902,0x3602bb0d,0xbabd34db,
0x3426b982,0xb9583371,0xbbe73b89,0xb68d3a5c,0xb7c839c9,0x2dfb3294,0x391fb625,0x3bb3bab6,0x3979ba0d,0x3825b8d6,0x3546b6d2,0x3010b359,
0x388ebaf7,0xb9af3a21,0x3a9eb916,0xbb5437bd,0xba043ac4,0x3bebb6af,0xbb42b0a6,0x3840394a,0x3b1eba8c,0xbb0aa17f,0x2ec33aa5,0x3a15bb6f,
0xbbcb3a50,0x36c636ff,0x3a64bbc3,0xba09a884,0x3c00ba11,0x3263ba3d,0xbb6a3790,0xb8503b9f,0xbbba39cd,0xb9f43bc8,0x30f0355e,0x3b4cb8db,
0x3afeb986,0x3bf7bbd4,0x3a25bb63,0x3457b85a,0xb9d6393c,0xbad83a60,0xbb8e3b3d,0xbbef3bc9,0x33403b98,0xa9b1bbed,0xb0743bfe,0x3517bbc9,
0x3c00b44b,0xbaa2b4cf,0x363c3a2d,0x319ebbf3,0x3426bbce,0xbb8b39df,0x3a7630a6,0x2776bb2f,0xbafe3185,0xb4b73b6c,0x3bf8b874,0xaf8bb994,
0xb9793bf0,0x38bc2ba7,0x3b35bbc3,0xb432b6a4,0x3855acce,0x3c00bb04,0x3865bb0d,0xb66bad65,0x3b94bbff,0x38ccba7a,0x294db55e,0xb840341a,
0xad33a5e4,0xb49331e8,0xb7a63625,0xb9333889,0x3bcbb50b,0xbbfe305b,0x3bec2a16,0xbb96b359,0x2452bbb5,0xb87a3ba1,0x3b5eb916,0xbbe02f27,
0xbbba330f,0x35523970,0x38b7bbea,0xbbff370a,0xb7c83be1,0x3ba5b5f7,0x2dc9baa5,0xbbf239bc,0x39d6afef,0x3a73bbfc,0xb6f4b3ba,0xbbb83b47,
0x3ababbfa,0x1cb6b7b2,0xbab03790,0xbb543bf9,0xb52326ad,0xba6738b2,0xbbfe3b89,0xbac73bbc,0xbbf93bff,0xbbab3bdd,0xbb073b63,0xba153a97,
0xb8f83986,0xb77a385f,0xb4c33625,0xaf8b32ad,0xb699393c,0x30d7305b,0x3954b6d2,0x3bb8bace,0xb1b638ee,0x39afb4cf,0x3bdcbba7,0x366bba41,
0x2c38389e,0x3bebb970,0x3581bade,0xbac7352f,0x34e7384a,0x3b0abb6c,0xb907b24b,0xb9333c00,0x383a37e8,0x36c6bbfc,0xbbec38c1,0x39413599,
0x39c03737,0xb263bb04,0xb63c3bf6,0x3abdba1d,0x3aee3682,0xb9f4b8b2,0x38b739f0,0xb68dbaeb,0xba4539c9,0xbb133ab3,0xbba33b63,0xbbf23bd3,
0xbb4a3a0d,0xbbe83bed,0xb9f83b3d,0xb4323835,0xbbdf3a4d,0xb9a13ba1,0x320134ab,0x3b54b8fd,0xbbfc3a89,0xb08d39df,0x3b83b81a,0x3840bb92,
0xbb9e3ac1,0x379b35f7,0x3a39bbd8,0xba15a311,0xbacb3af4,0x3b3faba7,0xb074ba6f,0xba093b7f,0xb9903b24,0x3bd7b7b2,0xbb5eae5f,0x38503929,
0xb7fe3b4f,0x3958ba7a,0xba76395d,0x3b4cb805,0x2c3826ad,0x33ebb109,0x36bbb55e,0x38a3b805,0x3b9ebbff,0x390cba9b,0x2ec3b625,0xb74231cf,
0xb83a2c9c,0xbbfe3ae8,0xb8d13b3d,0x35173122,0xb9903bf1,0x387a2d97,0x3b6abba7,0xb19eb7bd,0x3aeeb16c,0x3552bb81,0xbbe7381a,0x27763a00,
0x3463bbcf,0xbba539b8,0x3a25324b,0x2f8bbb6f,0xbbff343e,0x3a73353a,0xb546ba6f,0xb4323bff,0x32c63b9a,0x9cb6bbf4,0xb27c3bf6,0x366bbb9f,
0xbbfc3bff,0xbbc03be6,0xbb423b89,0xba853aeb,0x34e7a5e4,0x3a35b884,0x3bf5bb63,0x3b21bbde,0x3acbbbfb,0x29b1b80a,0xba6436d2,0xbb963be5,
0xb9c02fbd,0xbaa23bf8,0x360234ab,0x3be0bb01,0xb7fe3be2,0x3b8bb58d,0x30f0bade,0xbbff394a,0x3bb2b2f7,0xb4b7b999,0xb91f3bd8,0x3bf2b5eb,
0x281fbbb7,0xb8bc3b90,0x3b8eb8c1,0xbbb82884,0xbbd234ff,0x3c00aef5,0xbbd6ae5f,0x3b5434db,0xbaba3a4d,0xbb683b18,0xbbd63ba7,0xbc003bf3,
0x3b94ba89,0x3bc0bbfe,0x396bbade,0x3153b70a,0xbbf93ac1,0xb90c3b5c,0x3487324b,0x3b9cb994,0x3be4baf4,0x29b1b94f,0xbbbf38c1,0xb7213b47,
0xbb573b24,0x387a347b,0x39b3bbf6,0xba902d65,0x3a58bb4f,0xbb8b3109,0x338939f0,0x397dbbbc,0xb8f83b76,0x3ba5b884,0xbba39648,0x38f33889,
0x3699bb98,0xb8bc3ae8,0x39f8b9eb,0xbaf138ad,0x3855b8ee,0x360eb764,0x327cb4ab,0x251baf27,0xb523389e,0x33eb28e8,0x39e3b81a,0x3be3bb2f,
0x2d33b84a,0xba353648,0xbbac3bd8,0xb4f339bc,0x313b37e8,0x3bfeb9fc,0x3402ba6f,0xbb2a36a4,0xb65fb737,0xbaa23bae,0x399d2e5f,0x3894bbf9,
0x38e03682,0x3552bbe6,0xbbc6395d,0x39d2341a,0xba45b5c8,0x34b73a9b,0x34c3bc00,0xba493a97,0x3b4a350b,0xba73b80a,0x39543962,0xb7f3ba7e,
0xbbe43bfb,0xbb853bbd,0xbae53b3d,0xba093a7e,0xb65f2fbd,0xbaac3924,0xbc003ba7,0xbabd3bb0,0x3a58bbe2,0xaadeb6af,0xbad5381a,0xbb4c3bfc,
0x3a45b2f7,0x3a29bc00,0xb76fb24b,0xbbb33b59,0xb6993bb7,0x3bc5b6ff,0x2b43ba6f,0xbbef39da,0xbbdf34ff,0x36313902,0x387fbbf6,0xbc003759,
0xac38bb78,0xb8153bc8,0x3b42b95d,0xbbe33042,0x3b9eb676,0xbbf53294,0x3bf51648,0xbb9cb2ad,0xb13b2c9c,0xb576340e,0xb80f36d2,0xb94138ad,
0x3b57bbf1,0x386aba21,0x1fdbb4ab,0xb850346f,0x38e0b16c,0x3bfdbb45,0x382abade,0xb68dac06,0xb8f83bcf,0x391ba17f,0x3b16bbd8,0xb457b654,
0xbb4a343e,0xb3a23b32,0x3bfdb8c1,0xb010b974,0x31b6bb9a,0xbb603a3d,0x3a9e2e5f,0x251bbb1b,0x3bfcb5bc,0xbae1b371,0x36bb39f0,0x3153bbee,
0x34e73b52,0xae91bbd4,0xaec33c00,0x34f3bbd3,0x3bb235c8,0xbbf7b1e8,0x3bf81648,0xbbb331cf,0x3bff350b,0xbad8340e,0x36f4b9eb,0x30103be5,
0x3bd2344b,0xb60e3924,0xb865bbf6,0x3c0037bd,0x3b2c330f,0x33eb3b45,0xbbfeb8c7,0x3153b94a,0x3a193185,0x3a353c00,0xb7a63232,0xbb9cbb6f,
0x38a82fef,0x3bfe3b32,0x380f3adb,0xb7212884,0x35df2cce,0x3aa23902,0x3c003ba9,0x3a903b9f,0x302926ad,0x35523371,0x382a36dd,0x397d38db,
0xb4633b76,0x2dfbbbdd,0x2dc93c00,0xb457bbde,0xa81f3b98,0xb825bbbd,0x3b353962,0xbbefb122,0x32c63bb5,0xbb68ba21,0x3ab0ae2d,0xa51b3b01,
0x37153bce,0xbbc0b6af,0xa94dba6b,0x3be33a00,0x392e3be1,0xb90c217f,0xbb07bbd9,0x34f3b5eb,0x3a813bf0,0xa9b136ff,0xbae5b820,0xbb2abbff,
0x3b713bfa,0x387a3a3d,0x9fdb349f,0xb894b4db,0x3bef3bff,0x3b8b3bc8,0x3ad53b3a,0x39d23a5c,0x3b2cb5bc,0xba673830,0x396bb95d,0xb8403a5c,
0xb92ebb52,0x3bab385f,0xbbac9648,0x3933b85a,0xb8a8372c,0xb576bbed,0x3bbf3962,0xba093359,0x3b713af7,0xb86a34cf,0xb99dbbf6,0x3abd2f27,
0x3029b845,0x3bfd39df,0x33893a6b,0xbb4cb70a,0xbbf2ba8c,0xb91bbb6c,0x34c3b232,0x3bb339bc,0x35a538ea,0xb3a22ba7,0xb9f8b820,0xbbefbb47,
0x3a933a11,0x3b603b04,0x3bdc3ba9,0x3c003bf9,0x37153b78,0xb8ccbad1,0x39e339f0,0xbac7b8db,0x3a19b676,0xb4933ab3,0xb487bc00,0x3a153ab6,
0xba81bb27,0x3b85305b,0xb40239eb,0xb941bbc9,0xb5df37dd,0xbaacbba1,0x39b3ae2d,0x38503bf3,0x3bef3ac4,0x2ade3970,0xbbc6b8c7,0xb68dbb2f,
0xaf59b899,0x3a2935f7,0x3ba33bd9,0x34573994,0xbb7cba50,0xbbc5bbfc,0xb954badb,0xb010b6a4,0x388e3937,0x363137b2,0x3201349f,0xa51b2d65,
0xb1b63bb5,0x9cb6bbf8,0x32013bf6,0xb5d4bbb0,0xac38bbce,0x38cc3b81,0xbb83b8c7,0x3bcc2c06,0x34e73be1,0xbbabb999,0x3a39b232,0x2d003b59,
0xb83abbf0,0x3b85353a,0x30743adb,0xbbfbb974,0x39c03bfa,0xb86a2ef5,0xbb5ebba9,0x32deb759,0xbaeebbff,0xaadeb830,0x3a7636dd,0x3b7a3bee,
0x3bb23bff,0x391b3ab3,0x2dc9361a,0xb7d2b2ad,0xbbffbbfb,0xbbc5bbed,0xbb35bb87,0xba54bace,0xbbdfb44b,0x3c002d97,0xbbdc2e2d,0x3b73b46f,
0x3bfc330f,0xba67358d,0x3581ba6b,0x33283bfc,0xbb9eb185,0x3493b9b8,0x39073bd9,0xbbfab654,0x3acb2fef,0x35763b90,0xbbecb820,0x2c6ab9da,
0xb990acce,0xbaacbbf4,0x363cb49f,0x3bd03b1b,0x37fe26ad,0x3bfd3ad1,0x38b73b3a,0xb5b13042,0xb46325e4,0xba29b85f,0xbbf8bb65,0xbafbbbd3,
0x281fac9c,0x33a2305b,0x36f4356a,0x38e53835,0x383a3b27,0xb966ba60,0x3a643962,0xbb2ab835,0xb99037dd,0x3219bb18,0x36023bf6,0xba90ba41,
0xbaeebac4,0x3b3728e8,0xb0f03a6b,0xb9d2bb92,0x3463b899,0x3b133b5c,0xb91f3232,0xb8f3bc00,0x3bff3a50,0x30d739fc,0xbb8eb820,0xb7f3bb7f,
0x32c63937,0xb9a1b47b,0xbbd6bba9,0xb5d4ba1d,0xbb2cb9cd,0xbbebbbe6,0xb9e3bb3a,0xb328b805,0xb92eb9c9,0xb79bb884,0xb487b61a,0xad00b1cf,
0xbacb372c,0x39e7b8d6,0xb8d139eb,0x3721bace,0xb9c0baf7,0x3bda3764,0xbb6a2e2d,0x3894b8fd,0x37feb845,0x36e83bfe,0xbbe7b8c7,0x397db52f,
0x3bb23a8c,0xb77a3648,0xba25bbd9,0x3a492311,0xa81f38ea,0xbbe8b94f,0xb546badb,0x3af13599,0xbbd2ba11,0xb9afbbae,0x327cb49f,0x3b733929,
0xb715b982,0x308db109,0x396b36dd,0x3bcc3aeb,0x3a193986,0x3b0a3a9b,0x3bac3b65,0x3bfa3bde,0x30003000,0x30003000,0x30003000,0x30003000,
0x2f643000,0x2a1f2da8,0xaa1f0000,0xaf64ada8,0x2da83000,0xada80000,0xada8b000,0x2da88000,0x2a1f3000,0xaf64ada8,0x2f648000,0xaa1f2da8,
0x00003000,0x8000b000,0x00003000,0x8000b000,0xaa1f3000,0x2f64ada8,0xaf640000,0x2a1f2da8,0xada83000,0x2da88000,0x2da8b000,0xada80000,
0xaf643000,0xaa1f2da8,0x2a1f8000,0x2f64ada8,0x30003000,0x30003000,0x30003000,0x30003000,0xaf64b000,0xaa1fada8,0x2a1f8000,0x2f642da8,
0x2da83000,0xada80000,0xada8b000,0x2da88000,0xaa1fb000,0x2f642da8,0xaf640000,0x2a1fada8,0x00003000,0x8000b000,0x00003000,0x8000b000,
0x2a1fb000,0xaf642da8,0x2f648000,0xaa1fada8,0xada83000,0x2da88000,0x2da8b000,0xada80000,0x2f64b000,0x2a1fada8,0xaa1f0000,0xaf642da8,
0x80008000,0x80008000,0x80008000,0x80008000,0xaa1f8000,0xaf64ada8,0xaf64b000,0xaa1fada8,0xada88000,0xada8b000,0x2da88000,0x2da83000,
0xaf648000,0x2a1fada8,0x2a1f3000,0xaf64ada8,0xb0008000,0x30008000,0xb0008000,0x30008000,0xaf648000,0x2a1f2da8,0x2a1fb000,0xaf642da8,
0xada88000,0xada83000,0x2da88000,0x2da8b000,0xaa1f8000,0xaf642da8,0xaf643000,0xaa1f2da8,0x80008000,0x80008000,0x80008000,0x80008000,
0x2a1f8000,0x2f642da8,0x2f643000,0x2a1f2da8,0xada88000,0xada8b000,0x2da88000,0x2da83000,0x2f648000,0xaa1f2da8,0xaa1fb000,0x2f642da8,
0xb0008000,0x30008000,0xb0008000,0x30008000,0x2f648000,0xaa1fada8,0xaa1f3000,0x2f64ada8,0xada88000,0xada83000,0x2da88000,0x2da8b000,
0x2a1f8000,0x2f64ada8,0x2f64b000,0x2a1fada8,0xb0003000,0xb0003000,0xb0003000,0xb0003000,0xaf643000,0xaa1f2da8,0x2a1f0000,0x2f64ada8,
0xada83000,0x2da80000,0x2da8b000,0xada88000,0xaa1f3000,0x2f64ada8,0xaf648000,0x2a1f2da8,0x80003000,0x0000b000,0x80003000,0x0000b000,
0x2a1f3000,0xaf64ada8,0x2f640000,0xaa1f2da8,0x2da83000,0xada88000,0xada8b000,0x2da80000,0x2f643000,0x2a1f2da8,0xaa1f8000,0xaf64ada8,
0xb0003000,0xb0003000,0xb0003000,0xb0003000,0x2f64b000,0x2a1fada8,0xaa1f8000,0xaf642da8,0xada83000,0x2da80000,0x2da8b000,0xada88000,
0x2a1fb000,0xaf642da8,0x2f640000,0xaa1fada8,0x80003000,0x0000b000,0x80003000,0x0000b000,0xaa1fb000,0x2f642da8,0xaf648000,0x2a1fada8,
0x2da83000,0xada88000,0xada8b000,0x2da80000,0xaf64b000,0xaa1fada8,0x2a1f0000,0x2f642da8,0x80008000,0x80008000,0x80008000,0x80008000,
0x2a1f8000,0x2f64ada8,0x2f64b000,0x2a1fada8,0x2da88000,0x2da8b000,0xada88000,0xada83000,0x2f648000,0xaa1fada8,0xaa1f3000,0x2f64ada8,
0x30008000,0xb0008000,0x30008000,0xb0008000,0x2f648000,0xaa1f2da8,0xaa1fb000,0x2f642da8,0x2da88000,0x2da83000,0xada88000,0xada8b000,
0x2a1f8000,0x2f642da8,0x2f643000,0x2a1f2da8,0x80008000,0x80008000,0x80008000,0x80008000,0xaa1f8000,0xaf642da8,0xaf643000,0xaa1f2da8,
0x2da88000,0x2da8b000,0xada88000,0xada83000,0xaf648000,0x2a1f2da8,0x2a1fb000,0xaf642da8,0x30008000,0xb0008000,0x30008000,0xb0008000,
0xaf648000,0x2a1fada8,0x2a1f3000,0xaf64ada8,0x2da88000,0x2da83000,0xada88000,0xada8b000,0xaa1f8000,0xaf64ada8,0xaf64b000,0xaa1fada8,
0x00000000,0x00000000,0x00000000,0x00000000,0x2a1f0000,0x2f642da8,0x2f643000,0x2a1f2da8,0x2da80000,0x2da83000,0xada80000,0xada8b000,
0x2f640000,0xaa1f2da8,0xaa1fb000,0x2f642da8,0x30000000,0xb0000000,0x30000000,0xb0000000,0x2f640000,0xaa1fada8,0xaa1f3000,0x2f64ada8,
0x2da80000,0x2da8b000,0xada80000,0xada83000,0x2a1f0000,0x2f64ada8,0x2f64b000,0x2a1fada8,0x00000000,0x00000000,0x00000000,0x00000000,
0xaa1f0000,0xaf64ada8,0xaf64b000,0xaa1fada8,0x2da80000,0x2da83000,0xada80000,0xada8b000,0xaf640000,0x2a1fada8,0x2a1f3000,0xaf64ada8,
0x30000000,0xb0000000,0x30000000,0xb0000000,0xaf640000,0x2a1f2da8,0x2a1fb000,0xaf642da8,0x2da80000,0x2da8b000,0xada80000,0xada83000,
0xaa1f0000,0xaf642da8,0xaf643000,0xaa1f2da8,0x30003000,0x30003000,0x30003000,0x30003000,0x2f643000,0x2a1f2da8,0xaa1f0000,0xaf64ada8,
0x2da83000,0xada80000,0xada8b000,0x2da88000,0x2a1f3000,0xaf64ada8,0x2f648000,0xaa1f2da8,0x00003000,0x8000b000,0x00003000,0x8000b000,
0xaa1f3000,0x2f64ada8,0xaf640000,0x2a1f2da8,0xada83000,0x2da88000,0x2da8b000,0xada80000,0xaf643000,0xaa1f2da8,0x2a1f8000,0x2f64ada8,
0x30003000,0x30003000,0x30003000,0x30003000,0xaf64b000,0xaa1fada8,0x2a1f8000,0x2f642da8,0x2da83000,0xada80000,0xada8b000,0x2da88000,
0xaa1fb000,0x2f642da8,0xaf640000,0x2a1fada8,0x00003000,0x8000b000,0x00003000,0x8000b000,0x2a1fb000,0xaf642da8,0x2f648000,0xaa1fada8,
0xada83000,0x2da88000,0x2da8b000,0xada80000,0x2f64b000,0x2a1fada8,0xaa1f0000,0xaf642da8,0x00000000,0x00000000,0x00000000,0x00000000,
0xaa1f0000,0xaf642da8,0xaf643000,0xaa1f2da8,0xada80000,0xada83000,0x2da80000,0x2da8b000,0xaf640000,0x2a1f2da8,0x2a1fb000,0xaf642da8,
0xb0000000,0x30000000,0xb0000000,0x30000000,0xaf640000,0x2a1fada8,0x2a1f3000,0xaf64ada8,0xada80000,0xada8b000,0x2da80000,0x2da83000,
0xaa1f0000,0xaf64ada8,0xaf64b000,0xaa1fada8,0x00000000,0x00000000,0x00000000,0x00000000,0x2a1f0000,0x2f64ada8,0x2f64b000,0x2a1fada8,
0xada80000,0xada83000,0x2da80000,0x2da8b000,0x2f640000,0xaa1fada8,0xaa1f3000,0x2f64ada8,0xb0000000,0x30000000,0xb0000000,0x30000000,
0x2f640000,0xaa1f2da8,0xaa1fb000,0x2f642da8,0xada80000,0xada8b000,0x2da80000,0x2da83000,0x2a1f0000,0x2f642da8,0x2f643000,0x2a1f2da8,
0xb0003000,0xb0003000,0xb0003000,0xb0003000,0xaf643000,0xaa1f2da8,0x2a1f0000,0x2f64ada8,0xada83000,0x2da80000,0x2da8b000,0xada88000,
0xaa1f3000,0x2f64ada8,0xaf648000,0x2a1f2da8,0x80003000,0x0000b000,0x80003000,0x0000b000,0x2a1f3000,0xaf64ada8,0x2f640000,0xaa1f2da8,
0x2da83000,0xada88000,0xada8b000,0x2da80000,0x2f643000,0x2a1f2da8,0xaa1f8000,0xaf64ada8,0xb0003000,0xb0003000,0xb0003000,0xb0003000,
0x2f64b000,0x2a1fada8,0xaa1f8000,0xaf642da8,0xada83000,0x2da80000,0x2da8b000,0xada88000,0x2a1fb000,0xaf642da8,0x2f640000,0xaa1fada8,
0x80003000,0x0000b000,0x80003000,0x0000b000,0xaa1fb000,0x2f642da8,0xaf648000,0x2a1fada8,0x2da83000,0xada88000,0xada8b000,0x2da80000,
0xaf64b000,0xaa1fada8,0x2a1f0000,0x2f642da8};

constexpr int kThreads = 384;
constexpr int kCtas = 128;

constexpr uint32_t QKV_STAGE = 32768;
constexpr uint32_t SLOT = 16384;
constexpr uint32_t SM_KV = 2 * SLOT;
constexpr uint32_t SM_SIG = 131072;
constexpr uint32_t SM_Q = SM_SIG + SLOT;
constexpr uint32_t SM_STG = 196608;
constexpr uint32_t SM_Y0 = SM_STG;
constexpr uint32_t SM_YT = SM_STG + 16384;
constexpr uint32_t SM_TW = SM_STG + 24576, SM_ONES = SM_TW + 2048, SM_F1 = SM_ONES + 2048, SM_F2 = SM_F1 + 4096;
constexpr uint32_t SM_BAR = SM_F2 + 2048;
constexpr uint32_t SM_SC = SM_BAR + 512;
constexpr uint32_t SM_TOTAL = 232448;
constexpr uint32_t A_SLOTS = 0xB2310, B_SLOTS = 0xA7654;

enum Bar { B_QKV_FULL = 0, B_QKV_EMPTY = 4, B_OUT_FULL = 8, B_OUT_EMPTY = 13, B_QKV_DONE = 18, B_CONV_DONE = 19, B_PREP_FULL = 20,
           B_PREP_EMPTY = 23, B_SIG_READY = 27, B_ZEROED = 28, B_KVP = 29, B_KV_READY = 30, B_O_WRITTEN = 31,
           B_OT_FREE = 33, B_SEG = 35, B_RDY0 = 39, B_RDY1 = 40, B_YIN0 = 42, B_YIN1 = 44, B_Q_FULL = 45, B_H_FULL = 49 };

constexpr int KV_ELEMS = 4224;

struct Params {
  CUtensorMap x, w, wo, outa, k, v, q, outb;
  const __nv_bfloat16* shift_k;
  const __nv_bfloat16* ssm_k;
  const __nv_bfloat16* ssm_d;
  const __nv_bfloat16* q_ptr;
  const __nv_bfloat16* k_ptr;
  const __nv_bfloat16* v_ptr;
  const __nv_bfloat16* wo_ptr;
};

__device__ __align__(128) float g_kv[8][KV_ELEMS];
__device__ unsigned g_kvflag[8 * 32], g_zflag[8 * 32];
__device__ __align__(32) unsigned g_oflag[128];
__device__ unsigned g_epoch[kCtas];
__device__ __align__(128) uint8_t g_o[kCtas * 2][SLOT];

#define TSTAMP(cond, i) do { } while (0)
#define GSTAMP(cond, i) do { } while (0)
#define LOOPSTAMP(id, cond, i) do { } while (0)

constexpr int kSpinLimit = 1 << 17;

DEVI void mbar_init(uint32_t a, uint32_t c) { asm volatile("mbarrier.init.shared::cta.b64 [%0], %1;" :: "r"(a), "r"(c) : "memory"); }
DEVI void mbar_expect(uint32_t a, uint32_t b) { asm volatile("mbarrier.arrive.expect_tx.shared::cta.b64 _, [%0], %1;" :: "r"(a), "r"(b) : "memory"); }
DEVI void mbar_arrive(uint32_t a) { asm volatile("mbarrier.arrive.shared::cta.b64 _, [%0];" :: "r"(a) : "memory"); }
DEVI void mbar_arrive_if(uint32_t a, bool pred) {
  asm volatile("{\n.reg .pred p;\nsetp.ne.b32 p, %1, 0;\n@p mbarrier.arrive.shared::cta.b64 _, [%0];\n}" :: "r"(a), "r"((int)pred) : "memory");
}
DEVI void mbar_wait(uint32_t a, uint32_t parity) {
  asm volatile("{\n.reg .pred p;\n.reg .u32 n;\nmov.u32 n, 0;\nW_LOOP:\n"
               "mbarrier.try_wait.parity.shared::cta.b64 p, [%0], %1;\n@p bra W_DONE;\n"
               "add.u32 n, n, 1;\nsetp.lt.u32 p, n, %2;\n@p bra W_LOOP;\nW_DONE:\n}"
               :: "r"(a), "r"(parity), "n"(kSpinLimit) : "memory");
}
DEVI void mbar_wait_long(uint32_t a, uint32_t parity) {
  asm volatile("{\n.reg .pred p;\n.reg .u32 n;\nmov.u32 n, 0;\nW_LOOP:\n"
               "mbarrier.try_wait.parity.shared::cta.b64 p, [%0], %1, %3;\n@p bra W_DONE;\n"
               "add.u32 n, n, 1;\nsetp.lt.u32 p, n, %2;\n@p bra W_LOOP;\nW_DONE:\n}"
               :: "r"(a), "r"(parity), "n"(kSpinLimit), "r"(4000) : "memory");
}
DEVI bool mbar_test(uint32_t a, uint32_t parity) {
  uint32_t ok;
  asm volatile("{\n.reg .pred p;\nmbarrier.test_wait.parity.shared::cta.b64 p, [%1], %2;\nselp.u32 %0, 1, 0, p;\n}" : "=r"(ok) : "r"(a), "r"(parity) : "memory");
  return ok;
}
DEVI bool elect() {
  uint32_t ok;
  asm volatile("{\n.reg .pred p;\nelect.sync _|p, 0xffffffff;\nselp.u32 %0, 1, 0, p;\n}" : "=r"(ok));
  return ok;
}
DEVI void flag_wait(const unsigned* p, unsigned target) {
  int n = 0; unsigned v;
  do {
    asm volatile("ld.acquire.gpu.global.u32 %0, [%1];" : "=r"(v) : "l"(p) : "memory");
  } while ((int)(v - target) < 0 && ++n < kSpinLimit);
}
DEVI void flag_set(unsigned* p, unsigned v) {
  asm volatile("fence.release.gpu;\nst.relaxed.gpu.global.u32 [%0], %1;" :: "l"(p), "r"(v) : "memory");
}
DEVI void flag_add(unsigned* p) {
  asm volatile("fence.release.gpu;\nred.relaxed.gpu.global.add.u32 [%0], 1;" :: "l"(p) : "memory");
}
DEVI unsigned load_epoch(int cta) {
  unsigned v; asm volatile("ld.relaxed.gpu.global.u32 %0, [%1];" : "=r"(v) : "l"(&g_epoch[cta]) : "memory"); return v;
}
DEVI void fence_async_smem() { asm volatile("fence.proxy.async.shared::cta;" ::: "memory"); }
DEVI void bar_sync(int id, int n) { asm volatile("bar.sync %0, %1;" :: "r"(id), "r"(n) : "memory"); }
DEVI void cluster_sync() { asm volatile("barrier.cluster.arrive.relaxed.aligned;\nbarrier.cluster.wait.aligned;" ::: "memory"); }
DEVI void wg_fence() { asm volatile("wgmma.fence.sync.aligned;" ::: "memory"); }
DEVI void wg_commit() { asm volatile("wgmma.commit_group.sync.aligned;" ::: "memory"); }
template <int N> DEVI void wg_wait() { asm volatile("wgmma.wait_group.sync.aligned %0;" :: "n"(N) : "memory"); }
template <int N> DEVI void pin(uint32_t* r) {
#pragma unroll
  for (int i = 0; i < N; i++) asm volatile("" : "+r"(r[i]) :: "memory");
}
template <int N> DEVI void pin(float* r) {
#pragma unroll
  for (int i = 0; i < N; i++) asm volatile("" : "+f"(r[i]) :: "memory");
}

DEVI void tma2d(uint32_t dst, const CUtensorMap* m, int c0, int c1, uint32_t bar) {
  asm volatile("cp.async.bulk.tensor.2d.shared::cluster.global.mbarrier::complete_tx::bytes [%0], [%1, {%3, %4}], [%2];"
               :: "r"(dst), "l"(m), "r"(bar), "r"(c0), "r"(c1) : "memory");
}
DEVI void tma2d_mc(uint32_t dst, const CUtensorMap* m, int c0, int c1, uint32_t bar) {
  asm volatile("cp.async.bulk.tensor.2d.shared::cluster.global.mbarrier::complete_tx::bytes.multicast::cluster [%0], [%1, {%3, %4}], [%2], %5;"
               :: "r"(dst), "l"(m), "r"(bar), "r"(c0), "r"(c1), "h"((uint16_t)3) : "memory");
}
DEVI void tma3d(uint32_t dst, const CUtensorMap* m, int c0, int c1, int c2, uint32_t bar) {
  asm volatile("cp.async.bulk.tensor.3d.shared::cluster.global.mbarrier::complete_tx::bytes [%0], [%1, {%3, %4, %5}], [%2];"
               :: "r"(dst), "l"(m), "r"(bar), "r"(c0), "r"(c1), "r"(c2) : "memory");
}
DEVI void tma3d_mc(uint32_t dst, const CUtensorMap* m, int c0, int c1, int c2, uint32_t bar) {
  asm volatile("cp.async.bulk.tensor.3d.shared::cluster.global.mbarrier::complete_tx::bytes.multicast::cluster [%0], [%1, {%3, %4, %5}], [%2], %6;"
               :: "r"(dst), "l"(m), "r"(bar), "r"(c0), "r"(c1), "r"(c2), "h"((uint16_t)3) : "memory");
}
DEVI void tma2d_store(const CUtensorMap* m, uint32_t src, int c0, int c1) {
  asm volatile("cp.async.bulk.tensor.2d.global.shared::cta.bulk_group [%0, {%2, %3}], [%1];" :: "l"(m), "r"(src), "r"(c0), "r"(c1) : "memory");
}
DEVI void bulk_load(uint32_t dst, const void* src, uint32_t bytes, uint32_t bar) {
  asm volatile("cp.async.bulk.shared::cluster.global.mbarrier::complete_tx::bytes [%0], [%1], %2, [%3];" :: "r"(dst), "l"(src), "r"(bytes), "r"(bar) : "memory");
}
DEVI void bulk_store(void* dst, uint32_t src, uint32_t bytes) {
  asm volatile("cp.async.bulk.global.shared::cta.bulk_group [%0], [%1], %2;" :: "l"(dst), "r"(src), "r"(bytes) : "memory");
}
DEVI uint32_t peer_addr(uint32_t a, int rank) { uint32_t r; asm("mapa.shared::cluster.u32 %0, %1, %2;" : "=r"(r) : "r"(a), "r"(rank)); return r; }
DEVI void bulk_to_peer(uint32_t dst, uint32_t src, uint32_t bytes, uint32_t bar, int rank) {
  asm volatile("cp.async.bulk.shared::cluster.shared::cta.mbarrier::complete_tx::bytes [%0], [%1], %2, [%3];"
               :: "r"(peer_addr(dst, rank)), "r"(src), "r"(bytes), "r"(peer_addr(bar, rank)) : "memory");
}
DEVI void l2_prefetch(const void* p, uint32_t bytes) {
  asm volatile("cp.async.bulk.prefetch.L2.global [%0], %1;" :: "l"(p), "r"(bytes) : "memory");
}
DEVI void l2_prefetch2d(const CUtensorMap* m, int c0, int c1) {
  asm volatile("cp.async.bulk.prefetch.tensor.2d.L2.global [%0, {%1, %2}];" :: "l"(m), "r"(c0), "r"(c1) : "memory");
}
DEVI void l2_prefetch3d(const CUtensorMap* m, int c0, int c1, int c2) {
  asm volatile("cp.async.bulk.prefetch.tensor.3d.L2.global [%0, {%1, %2, %3}];" :: "l"(m), "r"(c0), "r"(c1), "r"(c2) : "memory");
}
DEVI void delay(int cycles) { const long long t = clock64(); while (clock64() - t < cycles) { } }
DEVI void bulk_commit() { asm volatile("cp.async.bulk.commit_group;" ::: "memory"); }
DEVI void bulk_wait_all() { asm volatile("cp.async.bulk.wait_group 0;" ::: "memory"); }
DEVI void bulk_wait_read() { asm volatile("cp.async.bulk.wait_group.read 0;" ::: "memory"); }
DEVI void prefetch_map(const CUtensorMap* m) { asm volatile("prefetch.tensormap [%0];" :: "l"(m) : "memory"); }
DEVI void arrive_both(uint32_t bar, int lane, bool pred = true) {
  asm volatile("{\n.reg .pred p;\n.reg .b32 r;\nsetp.ne.b32 p, %2, 0;\nmapa.shared::cluster.u32 r, %0, %1;\n@p mbarrier.arrive.shared::cluster.b64 _, [r];\n}"
               :: "r"(bar), "r"(lane & 1), "r"((int)(pred && lane < 2)) : "memory");
}

DEVI uint64_t make_desc(uint32_t addr, uint32_t lbo, uint32_t sbo, uint32_t mode) {
  return (uint64_t)((addr & 0x3FFFF) >> 4) | ((uint64_t)(lbo >> 4) << 16) | ((uint64_t)(sbo >> 4) << 32) | ((uint64_t)mode << 62);
}
DEVI uint32_t pack_bf16(float lo, float hi) { uint32_t r; asm("cvt.rn.bf16x2.f32 %0, %1, %2;" : "=r"(r) : "f"(hi), "f"(lo)); return r; }
DEVI uint32_t pack_f16(float lo, float hi) { uint32_t r; asm("cvt.rn.f16x2.f32 %0, %1, %2;" : "=r"(r) : "f"(hi), "f"(lo)); return r; }
DEVI void stsm4(uint32_t addr, uint32_t r0, uint32_t r1, uint32_t r2, uint32_t r3) {
  asm volatile("stmatrix.sync.aligned.m8n8.x4.shared.b16 [%0], {%1,%2,%3,%4};" :: "r"(addr), "r"(r0), "r"(r1), "r"(r2), "r"(r3) : "memory");
}
DEVI void stsm2(uint32_t addr, uint32_t r0, uint32_t r1) {
  asm volatile("stmatrix.sync.aligned.m8n8.x2.shared.b16 [%0], {%1,%2};" :: "r"(addr), "r"(r0), "r"(r1) : "memory");
}
DEVI void stsm4_t(uint32_t addr, uint32_t r0, uint32_t r1, uint32_t r2, uint32_t r3) {
  asm volatile("stmatrix.sync.aligned.m8n8.x4.trans.shared.b16 [%0], {%1,%2,%3,%4};" :: "r"(addr), "r"(r0), "r"(r1), "r"(r2), "r"(r3) : "memory");
}
DEVI void ldsm4(uint32_t* r, uint32_t addr) {
  asm volatile("ldmatrix.sync.aligned.m8n8.x4.shared.b16 {%0,%1,%2,%3}, [%4];" : "=r"(r[0]), "=r"(r[1]), "=r"(r[2]), "=r"(r[3]) : "r"(addr) : "memory");
}
DEVI void ldsm4_t(uint32_t* r, uint32_t addr) {
  asm volatile("ldmatrix.sync.aligned.m8n8.x4.trans.shared.b16 {%0,%1,%2,%3}, [%4];" : "=r"(r[0]), "=r"(r[1]), "=r"(r[2]), "=r"(r[3]) : "r"(addr) : "memory");
}
DEVI uint32_t lds32(uint32_t a) { uint32_t v; asm volatile("ld.shared.b32 %0, [%1];" : "=r"(v) : "r"(a) : "memory"); return v; }
DEVI uint4 lds128(uint32_t a) {
  uint4 v; asm volatile("ld.shared.v4.b32 {%0,%1,%2,%3}, [%4];" : "=r"(v.x), "=r"(v.y), "=r"(v.z), "=r"(v.w) : "r"(a) : "memory"); return v;
}
DEVI uint32_t bmul2(uint32_t a, uint32_t b) { uint32_t r; asm("mul.rn.bf16x2 %0, %1, %2;" : "=r"(r) : "r"(a), "r"(b)); return r; }
DEVI uint32_t bfma2(uint32_t a, uint32_t b, uint32_t c) { uint32_t r; asm("fma.rn.bf16x2 %0, %1, %2, %3;" : "=r"(r) : "r"(a), "r"(b), "r"(c)); return r; }
DEVI float bf_lo(uint32_t w) { return __uint_as_float(w << 16); }
DEVI float bf_hi(uint32_t w) { return __uint_as_float(w & 0xffff0000u); }
DEVI uint32_t phi2(float t0, float t1) {
  float e0, e1;
  asm("ex2.approx.ftz.f32 %0, %1;" : "=f"(e0) : "f"(t0 * 1.4426950408889634f));
  asm("ex2.approx.ftz.f32 %0, %1;" : "=f"(e1) : "f"(t1 * 1.4426950408889634f));
  uint32_t r;
  asm("{\n.reg .b32 a, b;\nmin.bf16x2 a, %1, %3;\nmax.bf16x2 b, %2, %4;\nadd.rn.bf16x2 %0, a, b;\n}"
      : "=r"(r) : "r"(pack_bf16(e0, e1)), "r"(pack_bf16(t0, t1)), "r"(0x3f803f80u), "r"(0x35863586u));
  return r;
}

DEVI uint32_t hmul(uint32_t a, uint32_t b) { uint32_t r; asm("mul.rn.f16x2 %0, %1, %2;" : "=r"(r) : "r"(a), "r"(b)); return r; }
DEVI uint32_t hfma(uint32_t a, uint32_t b, uint32_t c) { uint32_t r; asm("fma.rn.f16x2 %0, %1, %2, %3;" : "=r"(r) : "r"(a), "r"(b), "r"(c)); return r; }
DEVI uint32_t hneg(uint32_t a) { uint32_t r; asm("neg.f16x2 %0, %1;" : "=r"(r) : "r"(a)); return r; }
DEVI uint32_t hadd(uint32_t a, uint32_t b) { uint32_t r; asm("add.rn.f16x2 %0, %1, %2;" : "=r"(r) : "r"(a), "r"(b)); return r; }
DEVI uint32_t hsub(uint32_t a, uint32_t b) { uint32_t r; asm("sub.rn.f16x2 %0, %1, %2;" : "=r"(r) : "r"(a), "r"(b)); return r; }
struct Cx { uint32_t re, im; };
DEVI Cx cmul(Cx a, Cx b) { return {hfma(a.re, b.re, hneg(hmul(a.im, b.im))), hfma(a.re, b.im, hmul(a.im, b.re))}; }
DEVI Cx cfma(Cx a, Cx b, Cx c) { return {hfma(a.re, b.re, hfma(hneg(a.im), b.im, c.re)), hfma(a.re, b.im, hfma(a.im, b.re, c.im))}; }
DEVI Cx rot(Cx a, Cx t) {
  const uint32_t x = hfma(hneg(t.re), a.im, a.re), y = hfma(t.im, x, a.im);
  return {hfma(hneg(t.re), y, x), y};
}
struct Fft {
  uint32_t fa[8];
  Cx tw[2];
  uint64_t dF1, dF2;
  uint32_t vst;
  DEVI void stage1(uint32_t* d1, uint32_t slot) const {
    const uint64_t ds = make_desc(slot, 4096, 1024, 1);
    wg_fence();
    fft1_init(d1, fa[0], fa[1], fa[2], fa[3], ds);
    fft1_acc(d1, fa[4], fa[5], fa[6], fa[7], ds + (2048 >> 4));
    wg_commit();
  }
  DEVI void stage2(uint32_t* d, const Cx* t) const {
    wg_fence();
    fft2_init(d, t[0].re, t[1].re, t[2].re, t[3].re, dF2);
    fft2_acc(d, t[0].im, t[1].im, t[2].im, t[3].im, dF2 + (256 >> 4));
    wg_commit();
  }
  template <int PR> DEVI void fwd(const uint32_t* d1, uint32_t* d2) const {
    Cx t[4];
#pragma unroll
    for (int e = 0; e < 4; e++) {
      const int j = 8 * (PR & 1) + 4 * (e >> 1) + 2 * (PR >> 1) + (e & 1);
      t[e] = rot({d1[2 * j], d1[2 * j + 1]}, tw[e >> 1]);
    }
    stage2(d2 + 8 * PR, t);
  }
  static DEVI Cx U(const uint32_t* d2, int p, int hi) { return {d2[16 * (p >> 1) + 2 * hi + (p & 1)], d2[16 * (p >> 1) + 4 + 2 * hi + (p & 1)]}; }
  static DEVI Cx H(const uint32_t* d2, int p, int hi) { return U(d2 + 8, p, hi); }
  DEVI void prod01(const uint32_t* d2, Cx* p1, uint32_t* d3) const {
    Cx z[4];
#pragma unroll
    for (int hi = 0; hi < 2; hi++) {
      const Cx p0 = cmul(H(d2, 0, hi), U(d2, 0, hi));
      p1[hi] = cfma(H(d2, 1, hi), U(d2, 0, hi), cmul(H(d2, 0, hi), U(d2, 1, hi)));
      z[2 * hi] = {p0.im, p0.re};
      z[2 * hi + 1] = {hsub(p1[hi].im, p0.re), hadd(p1[hi].re, p0.im)};
    }
    stage2(d3, z);
  }
  DEVI void prod23(const uint32_t* d2, const Cx* p1, uint32_t* d3) const {
    Cx z[4];
#pragma unroll
    for (int hi = 0; hi < 2; hi++) {
      const Cx p2 = cfma(H(d2, 2, hi), U(d2, 0, hi), cfma(H(d2, 0, hi), U(d2, 2, hi), cmul(H(d2, 1, hi), U(d2, 1, hi))));
      const Cx z3 = cfma(H(d2, 3, hi), U(d2, 0, hi), cfma(H(d2, 2, hi), U(d2, 1, hi),
                    cfma(H(d2, 1, hi), U(d2, 2, hi), cfma(H(d2, 0, hi), U(d2, 3, hi), {p2.im, hneg(p2.re)}))));
      z[2 * hi] = {hsub(p2.im, p1[hi].re), hadd(p2.re, p1[hi].im)};
      z[2 * hi + 1] = {z3.im, z3.re};
    }
    stage2(d3 + 8, z);
  }
  template <int PB> DEVI void inv(const uint32_t* d3, uint32_t slot) const {
    Cx v[4];
#pragma unroll
    for (int e = 0; e < 4; e++) {
      const int r = 8 * PB + 2 * (e & 1) + (e >> 1);
      v[e] = rot({d3[r], d3[r + 4]}, tw[e & 1]);
    }
    stsm4(slot + (vst ^ (PB * 64)), v[0].im, v[1].im, v[2].im, v[3].im);
    stsm4(slot + 1024 + (vst ^ (PB * 64)), v[0].re, v[1].re, v[2].re, v[3].re);
  }
  DEVI void last(float* dy, uint32_t slot, int wg) const {
    fence_async_smem();
    bar_sync(2 + wg, 128);
    const uint64_t dv = make_desc(slot, 4096, 1024, 1);
    wg_fence();
    fft3_init(dy, dv, dF1);
#pragma unroll
    for (int ks = 1; ks < 4; ks++) fft3_acc(dy, dv + ks * (2048 >> 4), dF1 + ks * (256 >> 4));
    wg_commit();
  }
  static DEVI void store_y(const float* dy, uint32_t a) {
    stsm4_t(a, pack_bf16(dy[0], dy[1]), pack_bf16(dy[2], dy[3]), pack_bf16(dy[4], dy[5]), pack_bf16(dy[6], dy[7]));
    stsm4_t(a + 512, pack_bf16(dy[8], dy[9]), pack_bf16(dy[10], dy[11]), pack_bf16(dy[12], dy[13]), pack_bf16(dy[14], dy[15]));
  }
};
DEVI uint32_t normalize(uint32_t* x, uint32_t dst) {
  uint32_t m = x[0];
#pragma unroll
  for (int i = 1; i < 32; i++) asm("max.xorsign.abs.bf16x2 %0, %0, %1;" : "+r"(m) : "r"(x[i]));
  const uint32_t e = min(__reduce_max_sync(0xffffffffu, max(m & 0x7fffu, (m >> 16) & 0x7fffu)) >> 7, 252u);
  if (e > 140) {
#pragma unroll
    for (int i = 0; i < 32; i++) x[i] = bmul2(x[i], 15u * 0x00800080u);
  }
  const uint32_t sc = (e > 140 ? 253u - e : 141u - e) * 0x00800080u;
#pragma unroll
  for (int i = 0; i < 8; i++) {
    uint32_t y[4];
#pragma unroll
    for (int n = 0; n < 4; n++) {
      const uint32_t w = bmul2(x[4 * i + n], sc);
      y[n] = (w & 0x7fff7fffu) * 7u + w;
    }
    stsm4((dst ^ ((i >> 1) << 4)) + (i & 1) * 2048, y[0], y[1], y[2], y[3]);
  }
  return e;
}
#define CREGS 224
#define TAIL 3
#define DBG 0
#define XPF 1
#define XPFD 600
#define EARLY 1
#define KVPF 2
#define PSTART 5
#define PDELAY 1500
#define MAP 1
#define MC 7
#define HSTART 4
#define PF0 20

__global__ void __cluster_dims__(2, 1, 1) __launch_bounds__(kThreads, 1)
fused_kernel(const __grid_constant__ Params P) {
  extern __shared__ __align__(1024) uint8_t smem[];
  const uint32_t sb = (uint32_t)__cvta_generic_to_shared(smem);
  const int tid = threadIdx.x, lane = tid & 31;
  const int warp = __shfl_sync(0xffffffffu, tid >> 5, 0);
  const int cta = blockIdx.x, rho = cta & 1, cl = cta >> 1;
  const int gpc = cl < 4 ? 0 : cl < 36 ? (cl - 4) & 7 : 1 + (cl - 36) % 7, mem = cl < 4 ? 4 + cl : cl < 36 ? (cl - 4) >> 3 : 4 + (cl - 36) / 7;
  const int j = MAP == 0 ? cl >> 3 : MAP == 1 ? mem : MAP == 2 ? (gpc & 1) * 4 + (mem & 3) : MAP == 3 ? (gpc & 3) * 2 + (mem & 1) : gpc;
  const int rp = MAP == 0 ? cl & 7 : MAP == 1 ? gpc : MAP == 2 ? (gpc >> 1) * 2 + (mem >> 2) : MAP == 3 ? (gpc >> 2) * 4 + (mem >> 1) : mem;
  const int r = rp * 2 + rho;
  auto bar = [&](int i) { return sb + SM_BAR + 8u * i; };
  TSTAMP(tid == 0, 0); GSTAMP(tid == 0, 30);

  if (tid == 0) {
    for (int i = 0; i < 4; i++) { mbar_init(bar(B_QKV_FULL + i), 1); mbar_init(bar(B_QKV_EMPTY + i), MC & 1 ? 16 : 8); }
    for (int i = 0; i < 5; i++) { mbar_init(bar(B_OUT_FULL + i), 1); mbar_init(bar(B_OUT_EMPTY + i), MC & 4 ? 16 : 8); }
    mbar_init(bar(B_QKV_DONE), 16); mbar_init(bar(B_CONV_DONE), 16);
    for (int i = 0; i < 3; i++) { mbar_init(bar(B_PREP_FULL + i), 1); mbar_init(bar(B_PREP_EMPTY + i), 2); mbar_init(bar(B_H_FULL + i), 1); }
    mbar_init(bar(B_SIG_READY), 4); mbar_init(bar(B_ZEROED), 1);
    mbar_init(bar(B_KVP), 8); mbar_init(bar(B_KV_READY), 3);
    for (int i = 0; i < 2; i++) {
      mbar_init(bar(B_O_WRITTEN + i), 8); mbar_init(bar(B_OT_FREE + i), 1); mbar_init(bar(B_RDY1 + i), 1);
      mbar_init(bar(B_YIN0 + i), 1); mbar_expect(bar(B_YIN0 + i), 4096);
    }
    for (int i = 0; i < 4; i++) { mbar_init(bar(B_SEG + i), 4); mbar_init(bar(B_Q_FULL + i), 1); }
    mbar_init(bar(B_RDY0), 1); mbar_expect(bar(B_RDY0), 16);
    mbar_init(bar(B_YIN1), 1); mbar_expect(bar(B_YIN1), 8192);
    asm volatile("fence.mbarrier_init.release.cluster;" ::: "memory");
  }
  if (tid == 256) { prefetch_map(&P.x); prefetch_map(&P.w); }
  __syncwarp();
  cluster_sync();

  if (warp < 8) {
    asm volatile("setmaxnreg.inc.sync.aligned.u32 %0;" :: "n"(CREGS));
    const int wg = warp >> 2, wq = warp & 3;
    float aq[64];
    {
      float ak[64], av[64];
      auto dx = [&](uint32_t st, int kk) { return make_desc(st + kk * 32, 16, 512, 2); };
      auto dw = [&](uint32_t st, int kk) { return make_desc(st + 8192 + kk * 2048, 12288, 1024, 1); };
      const uint32_t xw = (wg * 4096) >> 4, kw = (wg * 12288 + 4096) >> 4, vw = (wg * 12288 + 8192) >> 4;
      for (int it = 0; it < 29; ++it) {
        mbar_wait(bar(B_QKV_FULL + (it & 3)), (it >> 2) & 1);
        TSTAMP(tid == 0 && it == 0, 1); LOOPSTAMP(1, tid == 0 && it < 27, 1 + it);
        const uint32_t st = sb + (it & 3) * QKV_STAGE;
        wg_fence();
#pragma unroll
        for (int kk = 0; kk < 2; kk++) {
          const int acc = (it | kk) != 0;
          mma_tn(ak, dw(st, kk) + kw, dx(st, kk), acc);
          if (EARLY && kk == 0) {
            wg_commit();
            wg_wait<1>();
            if (MC & 1) arrive_both(bar(B_QKV_EMPTY + ((it - 1) & 3)), lane, it > 0); else mbar_arrive_if(bar(B_QKV_EMPTY + ((it - 1) & 3)), it > 0 && lane == 0);
            wg_fence();
          }
          mma_tn(av, dw(st, kk) + vw, dx(st, kk), acc);
          mma_nt(aq, dx(st, kk) + xw, dw(st, kk), acc);
        }
        wg_commit();
        if (!EARLY) {
          wg_wait<1>();
          if (MC & 1) arrive_both(bar(B_QKV_EMPTY + ((it - 1) & 3)), lane, it > 0); else mbar_arrive_if(bar(B_QKV_EMPTY + ((it - 1) & 3)), it > 0 && lane == 0);
        }
      }
#pragma unroll
      for (int s = 1; s < 4; ++s) {
        mbar_wait(bar(B_QKV_FULL + s), 1);
        wg_fence();
#pragma unroll
        for (int kk = 0; kk < 2; kk++) mma_tn(ak, dw(sb + s * QKV_STAGE, kk) + kw, dx(sb + s * QKV_STAGE, kk), 1);
      }
      wg_commit();
      auto v_step = [&](int n) { const uint32_t st = sb + (1 + (n >> 1)) * QKV_STAGE; wg_fence(); mma_tn(av, dw(st, n & 1) + vw, dx(st, n & 1), 1); wg_commit(); };
      auto q_step = [&](int n) { const uint32_t st = sb + (1 + (n >> 1)) * QKV_STAGE; wg_fence(); mma_nt(aq, dx(st, n & 1) + xw, dw(st, n & 1), 1); wg_commit(); };
      v_step(0);
      wg_wait<1>();
      pin<64>(ak);
      TSTAMP(tid == 0, 2);
      bar_sync(1, 256);
      uint32_t pk[32];
#pragma unroll
      for (int n = 0; n < 11; n++) {
        if (n < 5) v_step(n + 1); else q_step(n - 5);
#pragma unroll
        for (int i = 3 * n; i < 3 * n + 3 && i < 32; i++) { pk[i] = phi2(ak[2 * i], ak[2 * i + 1]); asm volatile("" : "+r"(pk[i]) :: "memory"); }
      }
      wg_wait<6>();
      pin<64>(av);
      TSTAMP(tid == 0, 3);
      const uint32_t vv = sb + wg * SLOT;
      const uint32_t vrow = vv + ((lane >> 4) * 8 + (lane & 7)) * 128 + (((2 * wq + ((lane >> 3) & 1)) ^ (lane & 7)) << 4);
#pragma unroll
      for (int ks = 0; ks < 8; ks++) {
        const float* b = av + 8 * ks;
        stsm4_t(vrow + ks * 2048, pack_bf16(b[0], b[1]), pack_bf16(b[2], b[3]), pack_bf16(b[4], b[5]), pack_bf16(b[6], b[7]));
      }
      fence_async_smem();
      mbar_wait(bar(B_SIG_READY), 0);
      bar_sync(2 + wg, 128);
      float dkv[36];
      wg_fence();
#pragma unroll
      for (int ks = 0; ks < 8; ks++) {
        const uint32_t va = vv + ks * 2048;
        const uint64_t db = make_desc(va, sb + SM_ONES - va, 1024, 1);
        if (ks == 0) mma_kv_init(dkv, pk[0], pk[1], pk[2], pk[3], db);
        else mma_kv_acc(dkv, pk[4 * ks], pk[4 * ks + 1], pk[4 * ks + 2], pk[4 * ks + 3], db);
      }
      wg_commit();
      wg_wait<1>();
      arrive_both(bar(B_QKV_DONE), lane);
      mbar_wait(bar(B_ZEROED), 0);
      wg_wait<0>();
      pin<36>(dkv); pin<64>(aq);
      TSTAMP(tid == 0, 4);
      float* gacc = &g_kv[j][tid * 4];
      auto add4 = [&](const float* d) {
#pragma unroll
        for (int b = 0; b < 4; b++)
          asm volatile("red.relaxed.gpu.global.add.v4.f32 [%0], {%1,%2,%3,%4};" :: "l"(gacc + b * 1024), "f"(d[4 * b]), "f"(d[4 * b + 1]), "f"(d[4 * b + 2]), "f"(d[4 * b + 3]) : "memory");
      };
      if (wq < 2) add4(dkv); else add4(dkv + 16);
      if ((lane & 3) == 0)
        asm volatile("red.relaxed.gpu.global.add.v2.f32 [%0], {%1,%2};" :: "l"(&g_kv[j][4096 + (tid >> 1)]), "f"(dkv[32]), "f"(dkv[34]) : "memory");
      __syncwarp();
      mbar_arrive_if(bar(B_KVP), lane == 0);
      TSTAMP(tid == 0, 5);
    }

    const uint32_t orow = wq * 2048 + (lane & 15) * 128, ox = ((lane >> 4) ^ (lane & 7)) << 4;
    Fft F;
    ldsm4_t(F.fa, sb + SM_F1 + (lane >> 4) * 1024 + wq * 256 + (lane & 15) * 16);
    ldsm4_t(F.fa + 4, sb + SM_F1 + 2048 + (lane >> 4) * 1024 + wq * 256 + (lane & 15) * 16);
    {
      const uint4 t = lds128(sb + SM_TW + (tid & 127) * 16);
      F.tw[0] = {t.x, t.y}; F.tw[1] = {t.z, t.w};
    }
    F.dF1 = make_desc(sb + SM_F1, 128, 1024, 0); F.dF2 = make_desc(sb + SM_F2, 128, 512, 0);
    F.vst = (16 * wq + (lane & 7)) * 128 + (((lane >> 3) ^ (lane & 7)) << 4);
#pragma unroll 1
    for (int seg = 0; seg < 2; ++seg) {
      if (seg != wg) {
        pin<64>(aq);
#pragma unroll
        for (int i = 0; i < 32; i++) aq[i] = __uint_as_float(phi2(aq[2 * i], aq[2 * i + 1]));
        TSTAMP((tid & 127) == 0, 6);
      }
      if (seg) {
        float dn[4][20];
        mbar_wait(bar(B_KV_READY), 0);
        TSTAMP(tid == 0, 8);
        wg_fence();
#pragma unroll
        for (int h = 0; h < 4; h++) {
          const uint64_t db = make_desc(sb + SM_KV + h * 2560, 640, 128, 0);
          const float* a = aq + 8 * h;
          mma_o_init(dn[h], __float_as_uint(a[0]), __float_as_uint(a[1]), __float_as_uint(a[2]), __float_as_uint(a[3]), db);
          mma_o_acc(dn[h], __float_as_uint(a[4]), __float_as_uint(a[5]), __float_as_uint(a[6]), __float_as_uint(a[7]), db + (1280 >> 4));
          wg_commit();
        }
        auto head_store = [&](int h) {
          pin<20>(dn[h]);
          const float i0 = __fdividef(1.f, dn[h][16] + 1e-6f), i1 = __fdividef(1.f, dn[h][18] + 1e-6f);
#pragma unroll
          for (int hf = 0; hf < 2; hf++) {
            const float* a = dn[h] + 8 * hf;
            stsm4(sb + (h >> 1) * SLOT + wg * 8192 + orow + (ox ^ (((h & 1) * 2 + hf) << 5)),
                  pack_bf16(a[0] * i0, a[1] * i0), pack_bf16(a[2] * i1, a[3] * i1), pack_bf16(a[4] * i0, a[5] * i0), pack_bf16(a[6] * i1, a[7] * i1));
          }
          if (h & 1) { fence_async_smem(); __syncwarp(); mbar_arrive_if(bar(B_O_WRITTEN + (h >> 1)), lane == 0); }
        };
        wg_wait<3>(); head_store(0);
        wg_wait<2>(); head_store(1);
        wg_wait<1>(); head_store(2);
        wg_wait<0>(); head_store(3);
        TSTAMP(tid == 0, 9);
      }
      const int c = 4 * seg + wg;
      const uint32_t sa = sb + SM_SIG + c * 8192, sc = sa + SLOT;
      const uint32_t ya = sb + ((wq >> 1) == rho ? (seg ? SM_SIG : SM_Y0) + wg * 8192 : SM_YT + wg * 4096) + (wq & 1) * 1024 + ((lane ^ c) << 4);
      uint32_t a1[32], b1[32], a2[32], b2[32], a3[16], b3[16];
      float ay[16], by[16];
      Cx pa[2], pb[2];
      F.stage1(a1, sa);
      wg_wait<0>(); pin<32>(a1);
      bar_sync(2 + wg, 128);
      F.fwd<0>(a1, a2); F.fwd<1>(a1, a2); F.fwd<2>(a1, a2); F.fwd<3>(a1, a2);
      F.stage1(b1, sc);
      wg_wait<3>(); pin<16>(a2);
      F.prod01(a2, pa, a3);
      wg_wait<2>(); pin<16>(a2 + 16);
      F.prod23(a2, pa, a3);
      wg_wait<1>(); pin<32>(b1); pin<8>(a3);
      F.inv<0>(a3, sa);
      F.fwd<0>(b1, b2);
      wg_wait<1>(); pin<8>(a3 + 8);
      F.inv<1>(a3, sa);
      F.fwd<1>(b1, b2); F.fwd<2>(b1, b2); F.fwd<3>(b1, b2);
      F.last(ay, sa, wg);
      wg_wait<3>(); pin<16>(b2);
      F.prod01(b2, pb, b3);
      wg_wait<2>(); pin<16>(b2 + 16);
      F.prod23(b2, pb, b3);
      wg_wait<1>(); pin<8>(b3); pin<16>(ay);
      F.inv<0>(b3, sc);
      wg_wait<0>(); pin<8>(b3 + 8);
      F.inv<1>(b3, sc);
      F.last(by, sc, wg);
      mbar_wait(bar(B_RDY1 + wg), seg ^ 1);
      Fft::store_y(ay, ya);
      wg_wait<0>(); pin<16>(by);
      Fft::store_y(by, (ya ^ 32) + 2048);
      fence_async_smem();
      __syncwarp();
      mbar_arrive_if(bar(B_SEG + 2 * seg + wg), lane == 0);
      TSTAMP(tid == 0 && seg == 0, 7); TSTAMP(tid == 128 && seg == 0, 10); TSTAMP(tid == 0 && seg == 1, 11); TSTAMP(tid == 128 && seg == 1, 12);
    }
    arrive_both(bar(B_CONV_DONE), lane);

    float acc[64];
    {
      int s = 0, sprev = 0;
      uint32_t ph = 0;
      for (int ks = 0; ks < 16; ++ks) {
        asm volatile("{\n.reg .pred p;\nsetp.ne.b32 p, %0, 0;\n@p bar.sync 1, 256;\n}" :: "r"((int)(ks == 16 - TAIL && wg == 1)) : "memory");
        mbar_wait(bar(B_OUT_FULL + s), ph);
        LOOPSTAMP(2, tid == 0, 1 + ks);
        TSTAMP(tid == 0 && ks == 2, 13); TSTAMP(tid == 0 && ks == 9, 14);
        const uint64_t a = make_desc(sb + ((A_SLOTS >> (4 * s)) & 15) * SLOT + wg * 8192, 16, 1024, 1);
        const uint64_t b = make_desc(sb + ((B_SLOTS >> (4 * s)) & 15) * SLOT, 8192, 1024, 1);
        wg_fence();
        mma_nt(acc, a, b, ks != 0);
        wg_commit();
        wg_wait<1>();
        if (MC & 4) arrive_both(bar(B_OUT_EMPTY + sprev), lane, ks > 0 && ks < 12); else mbar_arrive_if(bar(B_OUT_EMPTY + sprev), ks > 0 && ks < 12 && lane == 0);
        wg_fence();
#pragma unroll
        for (int kk = 1; kk < 4; kk++) mma_nt(acc, a + 2 * kk, b + kk * (2048 >> 4), 1);
        wg_commit();
        sprev = s;
        if (++s == 5) { s = 0; ph ^= 1; }
      }
    }
    asm volatile("{\n.reg .pred p;\nsetp.eq.b32 p, %0, 0;\n@p bar.arrive 1, 256;\n}" :: "r"(wg) : "memory");
    wg_wait<0>(); pin<64>(acc);
    TSTAMP(tid == 0, 15); TSTAMP(tid == 128, 16);
#pragma unroll
    for (int hf = 0; hf < 2; hf++) {
      const uint32_t dst = sb + (1 + 2 * hf) * SLOT + wg * 8192;
#pragma unroll
      for (int t = 0; t < 4; t++) {
        const float* a = acc + 32 * hf + 8 * t;
        stsm4(dst + orow + (ox ^ (t << 5)), pack_bf16(a[0], a[1]), pack_bf16(a[2], a[3]), pack_bf16(a[4], a[5]), pack_bf16(a[6], a[7]));
      }
      fence_async_smem();
      __syncwarp();
      if (elect()) { tma2d_store(&P.outa, dst + wq * 2048, 128 * j + 64 * hf, 128 * r + 16 * warp); bulk_commit(); }
    }
    if (elect()) bulk_wait_read();
    TSTAMP(tid == 128, 17);
    __syncwarp();
    cluster_sync();
  } else {
    asm volatile("setmaxnreg.dec.sync.aligned.u32 %0;" :: "n"(504 - 2 * CREGS));
    if (warp == 8) {
      int ck = 0, cw = 0, cph = 1;
      const CUtensorMap* kvmap = rho ? &P.v : &P.k;
      auto load_kv = [&]() {
        if (elect()) {
          mbar_expect(bar(B_PREP_FULL + cw), 8704);
          tma3d_mc(sb + SM_STG + cw * 8704 + rho * 4608, kvmap, cl * 16, ck * 8 - 1 + rho, 0, bar(B_PREP_FULL + cw));
        }
        ++ck;
        if (++cw == 3) { cw = 0; cph ^= 1; }
      };
      auto load_stage = [&](int it) {
        const uint32_t st = sb + (it & 3) * QKV_STAGE, fb = bar(B_QKV_FULL + (it & 3));
        if (elect()) {
          mbar_expect(fb, QKV_STAGE);
          tma3d_mc(st + 8192 + rho * 12288, &P.w, 128 * j + 64 * rho, 32 * it, 0, fb);
          tma2d(st, &P.x, 32 * it, 128 * r, fb);
        }
      };
#pragma unroll 1
      for (int it = 0; it < 4; ++it) load_stage(it);
      if (XPF) {
        delay(XPFD);
        if (elect()) {
          l2_prefetch3d(&P.w, 128 * j + 64 * rho, 32 * (4 + ((rp - 4) & 7)), 0);
          l2_prefetch2d(&P.x, 32 * (4 + ((j - 4) & 7)), 128 * r);
        }
      }
      if (!(DBG & 1) && elect()) { mbar_expect(bar(B_H_FULL), 12288); mbar_expect(bar(B_H_FULL + 1), 12288); mbar_expect(bar(B_H_FULL + 2), 8192); }
#pragma unroll 1
      for (int it = 4; it < 32; ++it) {
        mbar_wait(bar(B_QKV_EMPTY + (it & 3)), ((it >> 2) - 1) & 1);
        load_stage(it);
        if (XPF && it < 24) {
          if ((it & 7) == rp && elect()) l2_prefetch3d(&P.w, 128 * j + 64 * rho, 32 * it + 256, 0);
          if ((it & 7) == j && elect()) l2_prefetch2d(&P.x, 32 * it + 256, 128 * r);
        }
        if (it < 12 && !(DBG & 1)) {
          if (elect()) bulk_load(sb + SM_SIG + (it - 4) * 8192 + 4096, P.ssm_k + (size_t)(cta * 8 + it - 4) * 2048, 4096, bar(B_H_FULL + (it >= 7) + (it >= 10)));
        }
        if (ck < 16 && !(DBG & 1)) {
          if (it >= PSTART && __all_sync(0xffffffffu, mbar_test(bar(B_PREP_EMPTY + cw), cph))) load_kv();
        } else if (ck < 22 && !(DBG & 8)) {
          if (elect()) l2_prefetch(ck < 18 ? P.wo_ptr + cta * 8192 + (ck - 16) * 4096 : P.q_ptr + cta * 16384 + (ck - 18) * 4096, 8192);
          ++ck;
        }
      }
#pragma unroll 1
      while (ck < 16 && !(DBG & 1)) { mbar_wait(bar(B_PREP_EMPTY + cw), cph); load_kv(); }
      const unsigned epoch = load_epoch(cta);
      if (elect()) { prefetch_map(&P.wo); prefetch_map(&P.outa); }
      auto chunk = [&](int ks) { const int c = ks >= 9, t = ks - 2 - 7 * c; return ks < 2 ? 2 * j + ks : 2 * (t + (t >= j)) + c; };
      auto load_wo = [&](int ks, int s, int c) {
        if (elect()) {
          mbar_expect(bar(B_OUT_FULL + s), ks < 2 ? SLOT : 2 * SLOT);
          tma2d_mc(sb + ((B_SLOTS >> (4 * s)) & 15) * SLOT + rho * 8192, &P.wo, 128 * j + 64 * rho, c * 64, bar(B_OUT_FULL + s));
        }
      };
      mbar_wait_long(bar(B_QKV_DONE), 0);
#pragma unroll 1
      for (int ks = 0; ks < 4; ++ks) load_wo(ks, ks, chunk(ks));
      mbar_wait_long(bar(B_O_WRITTEN + 1), 0);
      unsigned ready = 0;
      int s = 2;
      uint32_t ph = 1;
      const unsigned* flag = &g_oflag[r * 8 + ((lane >> 1) & 7)];
      const unsigned want = 2 * epoch + 1 + (lane & 1);
#pragma unroll 1
      for (int ks = 2; ks < 16; ++ks) {
        const int c = chunk(ks);
        if (ks >= 4) {
          mbar_wait(bar(ks == 4 ? B_CONV_DONE : B_OUT_EMPTY + s), ks == 4 ? 0 : ph);
          load_wo(ks, s, c);
        }
        if (ks == 5 || ks == 6) mbar_wait(bar(B_OT_FREE + s), 0);
        if (!((ready >> c) & 1)) {
          int n = 0;
          do {
            unsigned f;
            asm volatile("ld.relaxed.gpu.global.u32 %0, [%1];" : "=r"(f) : "l"(flag) : "memory");
            ready = __ballot_sync(0xffffffffu, (int)(f - want) >= 0);
          } while (!((ready >> c) & 1) && ++n < kSpinLimit);
          asm volatile("fence.acquire.gpu;\nfence.proxy.async.global;" ::: "memory");
          __syncwarp();
        }
        TSTAMP(ks == 2 && lane == 0, 18);
        if (elect()) bulk_load(sb + ((A_SLOTS >> (4 * s)) & 15) * SLOT, g_o[r * 16 + c], SLOT, bar(B_OUT_FULL + s));
        if (++s == 5) { s = 0; ph ^= 1; }
      }
    } else {
      const int at = tid - 288, aw = warp - 9, ch0 = cta * 8;
      if (at < KV_ELEMS / 64) reinterpret_cast<float4*>(&g_kv[j][r * (KV_ELEMS / 16)])[at] = make_float4(0.f, 0.f, 0.f, 0.f);
      bar_sync(4, 96);
      if (at == 64) flag_add(&g_zflag[j * 32]);
      const unsigned epoch = load_epoch(cta);
      {
        const uint32_t stg = sb + SM_STG + aw * 8704, pf = bar(B_PREP_FULL + aw), pe = bar(B_PREP_EMPTY + aw);
        const uint4 wv = __ldg(reinterpret_cast<const uint4*>(P.shift_k + (ch0 + 2 * (lane & 3)) * 4));
        const float skip = __bfloat162float(P.ssm_d[ch0 + (lane & 7)]);
        const uint32_t w0 = __byte_perm(wv.x, wv.z, 0x5410), w1 = __byte_perm(wv.x, wv.z, 0x7632);
        const uint32_t w2 = __byte_perm(wv.y, wv.w, 0x5410), w3 = __byte_perm(wv.y, wv.w, 0x7632);
        auto swz32 = [](uint32_t a) { return a ^ ((a >> 3) & 16); };
        const uint32_t kl = (lane >> 3) * 288 + (lane & 7) * 32 + rho * 16;
        const uint32_t ka = stg + swz32(kl + 32), kh = stg + swz32(kl + 12 * 288), va = stg + 4608 + swz32(lane * 32 + rho * 16);
        const uint32_t ua = sb + SM_SIG + (lane & 7) * 8192 + (((lane >> 3) ^ (lane & 7)) << 4);
        int ph = 0;
#pragma unroll 1
        for (int ck = aw; ck < 16; ck += 3, ph ^= 1) {
          if (DBG & 1) break;
          if (ck < 8 && !(DBG & 2)) {
            const uint32_t hs = sb + SM_SIG + ck * 8192 + 4096;
            uint32_t x[32];
            mbar_wait_long(bar(B_H_FULL + ck / 3), 0);
#pragma unroll
            for (int i = 0; i < 8; i++) ldsm4(x + 4 * i, hs + i * 512 + lane * 16);
            const float d = __shfl_sync(0xffffffffu, skip, ck);
            if (lane == 0) x[0] = pack_bf16(bf_lo(x[0]) + d, bf_hi(x[0]));
            const uint32_t e = normalize(x, hs + (lane >> 1) * 128 + ((((lane & 1) * 4) ^ ((lane >> 1) & 7)) << 4));
            if (lane == 0) asm volatile("st.shared.b32 [%0], %1;" :: "r"(sb + SM_SC + 64 + 4 * ck), "r"(e) : "memory");
          }
          mbar_wait_long(pf, ph);
          uint32_t k[20], v[16];
          ldsm4(k, kh);
#pragma unroll
          for (int m = 0; m < 4; m++) { ldsm4(k + 4 + 4 * m, (ka ^ ((m & 1) << 4)) + m * 1152); ldsm4(v + 4 * m, va + m * 1024); }
          pin<20>(k); pin<16>(v);
          __syncwarp();
          arrive_both(pe, lane, ck < 13);
#pragma unroll
          for (int m = 0; m < 4 && !(DBG & 16); m++) {
            uint32_t u[4];
#pragma unroll
            for (int n = 0; n < 4; n++) {
              const uint32_t* kk = k + 4 + 4 * m + n;
              u[n] = bmul2(bfma2(kk[0], w0, bfma2(kk[-1], w1, bfma2(kk[-2], w2, bmul2(kk[-3], w3)))), v[4 * m + n]);
            }
            stsm4_t((ua ^ (m << 6)) + ck * 256, u[0], u[1], u[2], u[3]);
          }
        }
        TSTAMP(at == 0, 19);
        bar_sync(4, 96);
        if (aw == 0 && elect()) {
          fence_async_smem();
          mbar_expect(bar(B_SIG_READY), 10240);
          bulk_load(sb + SM_TW, g_tables, 10240, bar(B_SIG_READY));
        }
#pragma unroll 1
        for (int c = aw; c < 8 && !(DBG & 4); c += 3) {
          const uint32_t us = sb + SM_SIG + c * 8192;
          uint32_t x[32];
#pragma unroll
          for (int i = 0; i < 8; i++) ldsm4_t(x + 4 * i, us + i * 512 + ((lane ^ c) << 4));
          const uint32_t e = normalize(x, us + (lane >> 4) * 1024 + (lane & 7) * 128 + ((((lane >> 1) & 4) ^ (lane & 7)) << 4));
          const int f = min(max((int)(e + lds32(sb + SM_SC + 64 + 4 * c)) - 125, 0), 254);
          if (lane == 0) asm volatile("st.shared.b16 [%0], %1;" :: "r"(sb + SM_SC + rho * 16 + 2 * c), "h"((uint16_t)(f << 7)) : "memory");
        }
        fence_async_smem();
        __syncwarp();
        if (lane == 0) mbar_arrive(bar(B_SIG_READY));
        bar_sync(4, 96);
        if (at == 32) {
          const uint4 s = lds128(sb + SM_SC + rho * 16);
          asm volatile("st.async.weak.shared::cluster.mbarrier::complete_tx::bytes.v4.b32 [%0], {%1,%2,%3,%4}, [%5];"
                       :: "r"(peer_addr(sb + SM_SC + rho * 16, rho ^ 1)), "r"(s.x), "r"(s.y), "r"(s.z), "r"(s.w), "r"(peer_addr(bar(B_RDY0), rho ^ 1)) : "memory");
        }
        TSTAMP(at == 0, 20);
      }
      if (at == 0) { flag_wait(&g_zflag[j * 32], 16u * (epoch + 1)); mbar_arrive(bar(B_ZEROED)); }
      mbar_wait_long(bar(B_KVP), 0);
      if (at == 0) { flag_add(&g_kvflag[j * 32]); TSTAMP(true, 21); }
      __syncwarp();
      {
        flag_wait(&g_kvflag[j * 32], 16u * (epoch + 1));
        TSTAMP(at == 32, 22);
        float4 a[3][4];
        float2 z[3];
#pragma unroll
        for (int n = 0; n < 3; n++) {
          const int t = min(aw + 3 * n, 7) * 32 + lane;
#pragma unroll
          for (int b = 0; b < 4; b++)
            asm volatile("ld.relaxed.gpu.global.v4.f32 {%0,%1,%2,%3}, [%4];" : "=f"(a[n][b].x), "=f"(a[n][b].y), "=f"(a[n][b].z), "=f"(a[n][b].w) : "l"(&g_kv[j][b * 1024 + t * 4]) : "memory");
          asm volatile("ld.relaxed.gpu.global.v2.f32 {%0,%1}, [%2];" : "=f"(z[n].x), "=f"(z[n].y) : "l"(&g_kv[j][4096 + (t >> 2) * 2]) : "memory");
        }
#pragma unroll
        for (int n = 0; n < 3; n++) {
          const uint32_t dst = sb + SM_KV + min(aw + 3 * n, 7) * 1280;
          stsm4(dst + lane * 16, pack_bf16(a[n][0].x, a[n][0].y), pack_bf16(a[n][1].x, a[n][1].y), pack_bf16(a[n][2].x, a[n][2].y), pack_bf16(a[n][3].x, a[n][3].y));
          stsm4(dst + 640 + lane * 16, pack_bf16(a[n][0].z, a[n][0].w), pack_bf16(a[n][1].z, a[n][1].w), pack_bf16(a[n][2].z, a[n][2].w), pack_bf16(a[n][3].z, a[n][3].w));
          stsm2(dst + 512 + ((lane >> 3) & 1) * 640 + (lane & 7) * 16, pack_bf16(z[n].x, z[n].x), pack_bf16(z[n].y, z[n].y));
        }
        fence_async_smem();
        __syncwarp();
        if (lane == 0) mbar_arrive(bar(B_KV_READY));
        TSTAMP(at == 32, 23);
      }
      if (warp == 9) {
        if (elect()) {
#pragma unroll 1
          for (int c = 0; c < 2; c++) {
            mbar_wait_long(bar(B_O_WRITTEN + c), 0);
            bulk_store(g_o[(r * 8 + j) * 2 + c], sb + c * SLOT, SLOT);
            bulk_commit();
            bulk_wait_all();
            mbar_arrive(bar(B_OT_FREE + c));
            flag_set(&g_oflag[r * 8 + j], 2 * epoch + 1 + c);
            TSTAMP(c == 0, 24); TSTAMP(c == 1, 25);
          }
          g_epoch[cta] = epoch + 1;
        }
      } else {
        const int w = warp - 10;
        auto load_q = [&](int n) {
          mbar_expect(bar(B_Q_FULL + (n & 3)), 4096);
          tma2d(sb + SM_Q + (n & 3) * 4096, &P.q, cl * 16, rho * 1024 + n * 128, bar(B_Q_FULL + (n & 3)));
        };
        mbar_wait_long(bar(B_RDY0), 0);
        mbar_wait_long(bar(B_SEG + w), 0);
        if (elect()) bulk_to_peer(sb + SM_Y0 + w * 8192 + 4096, sb + SM_YT + w * 4096, 4096, bar(B_YIN0 + w), rho ^ 1);
        mbar_wait_long(bar(B_YIN0 + w), 0);
        if (lane == 0) asm volatile("mbarrier.arrive.shared::cluster.b64 _, [%0];" :: "r"(peer_addr(bar(B_RDY1 + w), rho ^ 1)) : "memory");
        mbar_wait_long(bar(B_SEG + (w ^ 1)), 0);
        if (elect()) { load_q(w); load_q(w + 2); }
        mbar_wait_long(bar(B_YIN0 + (w ^ 1)), 0);
        mbar_wait_long(bar(B_SEG + 2 + w), 0);
        if (elect()) bulk_to_peer(sb + SM_SIG + w * 8192 + 4096, sb + SM_YT + w * 4096, 4096, bar(B_YIN1), rho ^ 1);
        mbar_wait_long(bar(B_SEG + 2 + (w ^ 1)), 0);
        mbar_wait_long(bar(B_YIN1), 0);
        TSTAMP(at == 32, 26);
        const int c = lane & 7;
        const uint32_t yl = sb + (c & 4 ? SM_SIG : SM_Y0) + (c & 1) * 8192 + (c & 2) * 1024 + ((lane >> 3) & 1) * 128 + (((lane >> 4) ^ c) << 4);
        const uint32_t ql = sb + SM_Q + lane * 32 + ((lane & 4) << 2);
#pragma unroll 1
        for (int n = w; n < 8; n += 2) {
          mbar_wait_long(bar(B_Q_FULL + (n & 3)), n >> 2);
#pragma unroll
          for (int src = 0; src < 2; src++) {
            const uint32_t s = lds32(sb + SM_SC + src * 16 + (lane & 3) * 4);
#pragma unroll
            for (int m = 0; m < 4; m++) {
              uint32_t y[4], q[4];
              const uint32_t qa = (ql ^ (src << 4)) + (n & 3) * 4096 + m * 1024;
              ldsm4_t(y, (yl ^ (m << 5)) + (src ^ rho) * 4096 + n * 256);
              ldsm4(q, qa);
              stsm4(qa, bmul2(q[0], bmul2(y[0], s)), bmul2(q[1], bmul2(y[1], s)), bmul2(q[2], bmul2(y[2], s)), bmul2(q[3], bmul2(y[3], s)));
            }
          }
          fence_async_smem();
          __syncwarp();
          if (elect()) {
            tma2d_store(&P.outb, sb + SM_Q + (n & 3) * 4096, 1024 + cl * 16, rho * 1024 + n * 128);
            bulk_commit();
            if (n < 4) { bulk_wait_read(); load_q(n + 4); }
          }
          __syncwarp();
        }
        if (elect()) bulk_wait_read();
        TSTAMP(at == 32, 27);
      }
    }
    __syncwarp();
    cluster_sync();
  }
  TSTAMP(tid == 0, 28); GSTAMP(tid == 0, 31);
}

typedef CUresult (*EncodeFn)(CUtensorMap*, CUtensorMapDataType, cuuint32_t, void*, const cuuint64_t*, const cuuint64_t*,
                             const cuuint32_t*, const cuuint32_t*, CUtensorMapInterleave, CUtensorMapSwizzle,
                             CUtensorMapL2promotion, CUtensorMapFloatOOBfill);

void encode(EncodeFn fn, CUtensorMap* m, const void* p, int rank, const cuuint64_t* dims, const cuuint64_t* strides,
            const cuuint32_t* box, CUtensorMapSwizzle sw) {
  const cuuint32_t es[3] = {1, 1, 1};
  fn(m, CU_TENSOR_MAP_DATA_TYPE_BFLOAT16, rank, const_cast<void*>(p), dims, strides, box, es, CU_TENSOR_MAP_INTERLEAVE_NONE, sw,
     CU_TENSOR_MAP_L2_PROMOTION_NONE, CU_TENSOR_MAP_FLOAT_OOB_FILL_NONE);
}
void encode2d(EncodeFn fn, CUtensorMap* m, const void* p, uint64_t cols, uint64_t rows, uint32_t bc, uint32_t br, CUtensorMapSwizzle sw) {
  const cuuint64_t dims[2] = {cols, rows}, strides[1] = {cols * 2};
  const cuuint32_t box[2] = {bc, br};
  encode(fn, m, p, 2, dims, strides, box, sw);
}
void encode3d(EncodeFn fn, CUtensorMap* m, const void* p, uint32_t nblk) {
  const cuuint64_t dims[3] = {1024, 128, 16}, strides[2] = {2048 * 16, 2048};
  const cuuint32_t box[3] = {16, nblk, 16};
  encode(fn, m, p, 3, dims, strides, box, CU_TENSOR_MAP_SWIZZLE_32B);
}

}

extern "C" void kernel_launch(void* const* d_in, const int* in_sizes, int n_in, void* d_out, int out_size) {
  static EncodeFn fn = nullptr;
  if (!fn) {
    cudaDriverEntryPointQueryResult qr;
    cudaGetDriverEntryPoint("cuTensorMapEncodeTiled", (void**)&fn, cudaEnableDefault, &qr);
    cudaFuncSetAttribute(fused_kernel, cudaFuncAttributeMaxDynamicSharedMemorySize, SM_TOTAL);
  }
  Params P;
  encode2d(fn, &P.x, d_in[0], 1024, 2048, 32, 128, CU_TENSOR_MAP_SWIZZLE_64B);
  {
    const cuuint64_t dims[3] = {1024, 1024, 3}, strides[2] = {6144, 2048};
    const cuuint32_t box[3] = {64, 32, 3};
    encode(fn, &P.w, d_in[1], 3, dims, strides, box, CU_TENSOR_MAP_SWIZZLE_128B);
  }
  encode2d(fn, &P.wo, d_in[2], 1024, 1024, 64, 64, CU_TENSOR_MAP_SWIZZLE_128B);
  encode2d(fn, &P.outa, d_out, 2048, 2048, 64, 16, CU_TENSOR_MAP_SWIZZLE_128B);
  encode3d(fn, &P.k, d_in[4], 9);
  encode3d(fn, &P.v, d_in[5], 8);
  encode2d(fn, &P.q, d_in[3], 1024, 2048, 16, 128, CU_TENSOR_MAP_SWIZZLE_32B);
  encode2d(fn, &P.outb, d_out, 2048, 2048, 16, 128, CU_TENSOR_MAP_SWIZZLE_32B);
  P.shift_k = (const __nv_bfloat16*)d_in[6];
  P.ssm_k = (const __nv_bfloat16*)d_in[7];
  P.ssm_d = (const __nv_bfloat16*)d_in[8];
  P.q_ptr = (const __nv_bfloat16*)d_in[3];
  P.k_ptr = (const __nv_bfloat16*)d_in[4];
  P.v_ptr = (const __nv_bfloat16*)d_in[5];
  P.wo_ptr = (const __nv_bfloat16*)d_in[2];
  fused_kernel<<<kCtas, kThreads, SM_TOTAL>>>(P);
}
```

```cpp
#include <cuda.h>
#include <cuda_runtime.h>
#include <cuda_bf16.h>
#include <stdint.h>

#define DEVI __device__ __forceinline__

namespace {

DEVI void mma_nt(float* d, uint64_t da, uint64_t db, int sd) {
  asm volatile("{\n.reg .pred p;\nsetp.ne.b32 p, %66, 0;\nwgmma.mma_async.sync.aligned.m64n128k16.f32.bf16.bf16 {%0, %1, %2, %3, %4, %5, %6, %7, %8, %9, %10, %11, %12, %13, %14, %15, %16, %17, %18, %19, %20, %21, %22, %23, %24, %25, %26, %27, %28, %29, %30, %31, %32, %33, %34, %35, %36, %37, %38, %39, %40, %41, %42, %43, %44, %45, %46, %47, %48, %49, %50, %51, %52, %53, %54, %55, %56, %57, %58, %59, %60, %61, %62, %63}, %64, %65, p, 1, 1, 0, 1;\n}\n"
    : "+f"(d[0]), "+f"(d[1]), "+f"(d[2]), "+f"(d[3]), "+f"(d[4]), "+f"(d[5]), "+f"(d[6]), "+f"(d[7]), "+f"(d[8]), "+f"(d[9]), "+f"(d[10]), "+f"(d[11]), "+f"(d[12]), "+f"(d[13]), "+f"(d[14]), "+f"(d[15]), "+f"(d[16]), "+f"(d[17]), "+f"(d[18]), "+f"(d[19]), "+f"(d[20]), "+f"(d[21]), "+f"(d[22]), "+f"(d[23]), "+f"(d[24]), "+f"(d[25]), "+f"(d[26]), "+f"(d[27]), "+f"(d[28]), "+f"(d[29]), "+f"(d[30]), "+f"(d[31]), "+f"(d[32]), "+f"(d[33]), "+f"(d[34]), "+f"(d[35]), "+f"(d[36]), "+f"(d[37]), "+f"(d[38]), "+f"(d[39]), "+f"(d[40]), "+f"(d[41]), "+f"(d[42]), "+f"(d[43]), "+f"(d[44]), "+f"(d[45]), "+f"(d[46]), "+f"(d[47]), "+f"(d[48]), "+f"(d[49]), "+f"(d[50]), "+f"(d[51]), "+f"(d[52]), "+f"(d[53]), "+f"(d[54]), "+f"(d[55]), "+f"(d[56]), "+f"(d[57]), "+f"(d[58]), "+f"(d[59]), "+f"(d[60]), "+f"(d[61]), "+f"(d[62]), "+f"(d[63])
    : "l"(da), "l"(db), "r"(sd));
}
DEVI void mma_tn(float* d, uint64_t da, uint64_t db, int sd) {
  asm volatile("{\n.reg .pred p;\nsetp.ne.b32 p, %66, 0;\nwgmma.mma_async.sync.aligned.m64n128k16.f32.bf16.bf16 {%0, %1, %2, %3, %4, %5, %6, %7, %8, %9, %10, %11, %12, %13, %14, %15, %16, %17, %18, %19, %20, %21, %22, %23, %24, %25, %26, %27, %28, %29, %30, %31, %32, %33, %34, %35, %36, %37, %38, %39, %40, %41, %42, %43, %44, %45, %46, %47, %48, %49, %50, %51, %52, %53, %54, %55, %56, %57, %58, %59, %60, %61, %62, %63}, %64, %65, p, 1, 1, 1, 0;\n}\n"
    : "+f"(d[0]), "+f"(d[1]), "+f"(d[2]), "+f"(d[3]), "+f"(d[4]), "+f"(d[5]), "+f"(d[6]), "+f"(d[7]), "+f"(d[8]), "+f"(d[9]), "+f"(d[10]), "+f"(d[11]), "+f"(d[12]), "+f"(d[13]), "+f"(d[14]), "+f"(d[15]), "+f"(d[16]), "+f"(d[17]), "+f"(d[18]), "+f"(d[19]), "+f"(d[20]), "+f"(d[21]), "+f"(d[22]), "+f"(d[23]), "+f"(d[24]), "+f"(d[25]), "+f"(d[26]), "+f"(d[27]), "+f"(d[28]), "+f"(d[29]), "+f"(d[30]), "+f"(d[31]), "+f"(d[32]), "+f"(d[33]), "+f"(d[34]), "+f"(d[35]), "+f"(d[36]), "+f"(d[37]), "+f"(d[38]), "+f"(d[39]), "+f"(d[40]), "+f"(d[41]), "+f"(d[42]), "+f"(d[43]), "+f"(d[44]), "+f"(d[45]), "+f"(d[46]), "+f"(d[47]), "+f"(d[48]), "+f"(d[49]), "+f"(d[50]), "+f"(d[51]), "+f"(d[52]), "+f"(d[53]), "+f"(d[54]), "+f"(d[55]), "+f"(d[56]), "+f"(d[57]), "+f"(d[58]), "+f"(d[59]), "+f"(d[60]), "+f"(d[61]), "+f"(d[62]), "+f"(d[63])
    : "l"(da), "l"(db), "r"(sd));
}
DEVI void mma_nt256(float* d, uint64_t da, uint64_t db, int sd) {
  asm volatile("{\n.reg .pred p;\nsetp.ne.b32 p, %130, 0;\nwgmma.mma_async.sync.aligned.m64n256k16.f32.bf16.bf16 {%0, %1, %2, %3, %4, %5, %6, %7, %8, %9, %10, %11, %12, %13, %14, %15, %16, %17, %18, %19, %20, %21, %22, %23, %24, %25, %26, %27, %28, %29, %30, %31, %32, %33, %34, %35, %36, %37, %38, %39, %40, %41, %42, %43, %44, %45, %46, %47, %48, %49, %50, %51, %52, %53, %54, %55, %56, %57, %58, %59, %60, %61, %62, %63, %64, %65, %66, %67, %68, %69, %70, %71, %72, %73, %74, %75, %76, %77, %78, %79, %80, %81, %82, %83, %84, %85, %86, %87, %88, %89, %90, %91, %92, %93, %94, %95, %96, %97, %98, %99, %100, %101, %102, %103, %104, %105, %106, %107, %108, %109, %110, %111, %112, %113, %114, %115, %116, %117, %118, %119, %120, %121, %122, %123, %124, %125, %126, %127}, %128, %129, p, 1, 1, 0, 1;\n}\n"
    : "+f"(d[0]), "+f"(d[1]), "+f"(d[2]), "+f"(d[3]), "+f"(d[4]), "+f"(d[5]), "+f"(d[6]), "+f"(d[7]), "+f"(d[8]), "+f"(d[9]), "+f"(d[10]), "+f"(d[11]), "+f"(d[12]), "+f"(d[13]), "+f"(d[14]), "+f"(d[15]), "+f"(d[16]), "+f"(d[17]), "+f"(d[18]), "+f"(d[19]), "+f"(d[20]), "+f"(d[21]), "+f"(d[22]), "+f"(d[23]), "+f"(d[24]), "+f"(d[25]), "+f"(d[26]), "+f"(d[27]), "+f"(d[28]), "+f"(d[29]), "+f"(d[30]), "+f"(d[31]), "+f"(d[32]), "+f"(d[33]), "+f"(d[34]), "+f"(d[35]), "+f"(d[36]), "+f"(d[37]), "+f"(d[38]), "+f"(d[39]), "+f"(d[40]), "+f"(d[41]), "+f"(d[42]), "+f"(d[43]), "+f"(d[44]), "+f"(d[45]), "+f"(d[46]), "+f"(d[47]), "+f"(d[48]), "+f"(d[49]), "+f"(d[50]), "+f"(d[51]), "+f"(d[52]), "+f"(d[53]), "+f"(d[54]), "+f"(d[55]), "+f"(d[56]), "+f"(d[57]), "+f"(d[58]), "+f"(d[59]), "+f"(d[60]), "+f"(d[61]), "+f"(d[62]), "+f"(d[63]), "+f"(d[64]), "+f"(d[65]), "+f"(d[66]), "+f"(d[67]), "+f"(d[68]), "+f"(d[69]), "+f"(d[70]), "+f"(d[71]), "+f"(d[72]), "+f"(d[73]), "+f"(d[74]), "+f"(d[75]), "+f"(d[76]), "+f"(d[77]), "+f"(d[78]), "+f"(d[79]), "+f"(d[80]), "+f"(d[81]), "+f"(d[82]), "+f"(d[83]), "+f"(d[84]), "+f"(d[85]), "+f"(d[86]), "+f"(d[87]), "+f"(d[88]), "+f"(d[89]), "+f"(d[90]), "+f"(d[91]), "+f"(d[92]), "+f"(d[93]), "+f"(d[94]), "+f"(d[95]), "+f"(d[96]), "+f"(d[97]), "+f"(d[98]), "+f"(d[99]), "+f"(d[100]), "+f"(d[101]), "+f"(d[102]), "+f"(d[103]), "+f"(d[104]), "+f"(d[105]), "+f"(d[106]), "+f"(d[107]), "+f"(d[108]), "+f"(d[109]), "+f"(d[110]), "+f"(d[111]), "+f"(d[112]), "+f"(d[113]), "+f"(d[114]), "+f"(d[115]), "+f"(d[116]), "+f"(d[117]), "+f"(d[118]), "+f"(d[119]), "+f"(d[120]), "+f"(d[121]), "+f"(d[122]), "+f"(d[123]), "+f"(d[124]), "+f"(d[125]), "+f"(d[126]), "+f"(d[127])
    : "l"(da), "l"(db), "r"(sd));
}
DEVI void mma_kv_init(float* d, uint32_t a0, uint32_t a1, uint32_t a2, uint32_t a3, uint64_t db) {
  asm volatile("wgmma.mma_async.sync.aligned.m64n72k16.f32.bf16.bf16 {%0, %1, %2, %3, %4, %5, %6, %7, %8, %9, %10, %11, %12, %13, %14, %15, %16, %17, %18, %19, %20, %21, %22, %23, %24, %25, %26, %27, %28, %29, %30, %31, %32, %33, %34, %35}, {%36,%37,%38,%39}, %40, 0, 1, 1, 1;\n"
    : "=f"(d[0]), "=f"(d[1]), "=f"(d[2]), "=f"(d[3]), "=f"(d[4]), "=f"(d[5]), "=f"(d[6]), "=f"(d[7]), "=f"(d[8]), "=f"(d[9]), "=f"(d[10]), "=f"(d[11]), "=f"(d[12]), "=f"(d[13]), "=f"(d[14]), "=f"(d[15]), "=f"(d[16]), "=f"(d[17]), "=f"(d[18]), "=f"(d[19]), "=f"(d[20]), "=f"(d[21]), "=f"(d[22]), "=f"(d[23]), "=f"(d[24]), "=f"(d[25]), "=f"(d[26]), "=f"(d[27]), "=f"(d[28]), "=f"(d[29]), "=f"(d[30]), "=f"(d[31]), "=f"(d[32]), "=f"(d[33]), "=f"(d[34]), "=f"(d[35])
    : "r"(a0), "r"(a1), "r"(a2), "r"(a3), "l"(db));
}
DEVI void mma_kv_acc(float* d, uint32_t a0, uint32_t a1, uint32_t a2, uint32_t a3, uint64_t db) {
  asm volatile("wgmma.mma_async.sync.aligned.m64n72k16.f32.bf16.bf16 {%0, %1, %2, %3, %4, %5, %6, %7, %8, %9, %10, %11, %12, %13, %14, %15, %16, %17, %18, %19, %20, %21, %22, %23, %24, %25, %26, %27, %28, %29, %30, %31, %32, %33, %34, %35}, {%36,%37,%38,%39}, %40, 1, 1, 1, 1;\n"
    : "+f"(d[0]), "+f"(d[1]), "+f"(d[2]), "+f"(d[3]), "+f"(d[4]), "+f"(d[5]), "+f"(d[6]), "+f"(d[7]), "+f"(d[8]), "+f"(d[9]), "+f"(d[10]), "+f"(d[11]), "+f"(d[12]), "+f"(d[13]), "+f"(d[14]), "+f"(d[15]), "+f"(d[16]), "+f"(d[17]), "+f"(d[18]), "+f"(d[19]), "+f"(d[20]), "+f"(d[21]), "+f"(d[22]), "+f"(d[23]), "+f"(d[24]), "+f"(d[25]), "+f"(d[26]), "+f"(d[27]), "+f"(d[28]), "+f"(d[29]), "+f"(d[30]), "+f"(d[31]), "+f"(d[32]), "+f"(d[33]), "+f"(d[34]), "+f"(d[35])
    : "r"(a0), "r"(a1), "r"(a2), "r"(a3), "l"(db));
}
DEVI void mma_o_init(float* d, uint32_t a0, uint32_t a1, uint32_t a2, uint32_t a3, uint64_t db) {
  asm volatile("wgmma.mma_async.sync.aligned.m64n40k16.f32.bf16.bf16 {%0, %1, %2, %3, %4, %5, %6, %7, %8, %9, %10, %11, %12, %13, %14, %15, %16, %17, %18, %19}, {%20,%21,%22,%23}, %24, 0, 1, 1, 1;\n"
    : "=f"(d[0]), "=f"(d[1]), "=f"(d[2]), "=f"(d[3]), "=f"(d[4]), "=f"(d[5]), "=f"(d[6]), "=f"(d[7]), "=f"(d[8]), "=f"(d[9]), "=f"(d[10]), "=f"(d[11]), "=f"(d[12]), "=f"(d[13]), "=f"(d[14]), "=f"(d[15]), "=f"(d[16]), "=f"(d[17]), "=f"(d[18]), "=f"(d[19])
    : "r"(a0), "r"(a1), "r"(a2), "r"(a3), "l"(db));
}
DEVI void mma_o_acc(float* d, uint32_t a0, uint32_t a1, uint32_t a2, uint32_t a3, uint64_t db) {
  asm volatile("wgmma.mma_async.sync.aligned.m64n40k16.f32.bf16.bf16 {%0, %1, %2, %3, %4, %5, %6, %7, %8, %9, %10, %11, %12, %13, %14, %15, %16, %17, %18, %19}, {%20,%21,%22,%23}, %24, 1, 1, 1, 1;\n"
    : "+f"(d[0]), "+f"(d[1]), "+f"(d[2]), "+f"(d[3]), "+f"(d[4]), "+f"(d[5]), "+f"(d[6]), "+f"(d[7]), "+f"(d[8]), "+f"(d[9]), "+f"(d[10]), "+f"(d[11]), "+f"(d[12]), "+f"(d[13]), "+f"(d[14]), "+f"(d[15]), "+f"(d[16]), "+f"(d[17]), "+f"(d[18]), "+f"(d[19])
    : "r"(a0), "r"(a1), "r"(a2), "r"(a3), "l"(db));
}
DEVI void fft1_init(uint32_t* d, uint32_t a0, uint32_t a1, uint32_t a2, uint32_t a3, uint64_t db) {
  asm volatile("wgmma.mma_async.sync.aligned.m64n128k16.f16.f16.f16 {%0, %1, %2, %3, %4, %5, %6, %7, %8, %9, %10, %11, %12, %13, %14, %15, %16, %17, %18, %19, %20, %21, %22, %23, %24, %25, %26, %27, %28, %29, %30, %31}, {%32,%33,%34,%35}, %36, 0, 1, 1, 1;\n"
    : "=r"(d[0]), "=r"(d[1]), "=r"(d[2]), "=r"(d[3]), "=r"(d[4]), "=r"(d[5]), "=r"(d[6]), "=r"(d[7]), "=r"(d[8]), "=r"(d[9]), "=r"(d[10]), "=r"(d[11]), "=r"(d[12]), "=r"(d[13]), "=r"(d[14]), "=r"(d[15]), "=r"(d[16]), "=r"(d[17]), "=r"(d[18]), "=r"(d[19]), "=r"(d[20]), "=r"(d[21]), "=r"(d[22]), "=r"(d[23]), "=r"(d[24]), "=r"(d[25]), "=r"(d[26]), "=r"(d[27]), "=r"(d[28]), "=r"(d[29]), "=r"(d[30]), "=r"(d[31])
    : "r"(a0), "r"(a1), "r"(a2), "r"(a3), "l"(db));
}
DEVI void fft1_acc(uint32_t* d, uint32_t a0, uint32_t a1, uint32_t a2, uint32_t a3, uint64_t db) {
  asm volatile("wgmma.mma_async.sync.aligned.m64n128k16.f16.f16.f16 {%0, %1, %2, %3, %4, %5, %6, %7, %8, %9, %10, %11, %12, %13, %14, %15, %16, %17, %18, %19, %20, %21, %22, %23, %24, %25, %26, %27, %28, %29, %30, %31}, {%32,%33,%34,%35}, %36, 1, 1, 1, 1;\n"
    : "+r"(d[0]), "+r"(d[1]), "+r"(d[2]), "+r"(d[3]), "+r"(d[4]), "+r"(d[5]), "+r"(d[6]), "+r"(d[7]), "+r"(d[8]), "+r"(d[9]), "+r"(d[10]), "+r"(d[11]), "+r"(d[12]), "+r"(d[13]), "+r"(d[14]), "+r"(d[15]), "+r"(d[16]), "+r"(d[17]), "+r"(d[18]), "+r"(d[19]), "+r"(d[20]), "+r"(d[21]), "+r"(d[22]), "+r"(d[23]), "+r"(d[24]), "+r"(d[25]), "+r"(d[26]), "+r"(d[27]), "+r"(d[28]), "+r"(d[29]), "+r"(d[30]), "+r"(d[31])
    : "r"(a0), "r"(a1), "r"(a2), "r"(a3), "l"(db));
}
DEVI void fft2_init(uint32_t* d, uint32_t a0, uint32_t a1, uint32_t a2, uint32_t a3, uint64_t db) {
  asm volatile("wgmma.mma_async.sync.aligned.m64n32k16.f16.f16.f16 {%0, %1, %2, %3, %4, %5, %6, %7}, {%8,%9,%10,%11}, %12, 0, 1, 1, 0;\n"
    : "=r"(d[0]), "=r"(d[1]), "=r"(d[2]), "=r"(d[3]), "=r"(d[4]), "=r"(d[5]), "=r"(d[6]), "=r"(d[7])
    : "r"(a0), "r"(a1), "r"(a2), "r"(a3), "l"(db));
}
DEVI void fft2_acc(uint32_t* d, uint32_t a0, uint32_t a1, uint32_t a2, uint32_t a3, uint64_t db) {
  asm volatile("wgmma.mma_async.sync.aligned.m64n32k16.f16.f16.f16 {%0, %1, %2, %3, %4, %5, %6, %7}, {%8,%9,%10,%11}, %12, 1, 1, 1, 0;\n"
    : "+r"(d[0]), "+r"(d[1]), "+r"(d[2]), "+r"(d[3]), "+r"(d[4]), "+r"(d[5]), "+r"(d[6]), "+r"(d[7])
    : "r"(a0), "r"(a1), "r"(a2), "r"(a3), "l"(db));
}
DEVI void fft3_init(float* d, uint64_t da, uint64_t db) {
  asm volatile("wgmma.mma_async.sync.aligned.m64n32k16.f32.f16.f16 {%0, %1, %2, %3, %4, %5, %6, %7, %8, %9, %10, %11, %12, %13, %14, %15}, %16, %17, 0, 1, 1, 1, 0;\n"
    : "=f"(d[0]), "=f"(d[1]), "=f"(d[2]), "=f"(d[3]), "=f"(d[4]), "=f"(d[5]), "=f"(d[6]), "=f"(d[7]), "=f"(d[8]), "=f"(d[9]), "=f"(d[10]), "=f"(d[11]), "=f"(d[12]), "=f"(d[13]), "=f"(d[14]), "=f"(d[15])
    : "l"(da), "l"(db));
}
DEVI void fft3_acc(float* d, uint64_t da, uint64_t db) {
  asm volatile("wgmma.mma_async.sync.aligned.m64n32k16.f32.f16.f16 {%0, %1, %2, %3, %4, %5, %6, %7, %8, %9, %10, %11, %12, %13, %14, %15}, %16, %17, 1, 1, 1, 1, 0;\n"
    : "+f"(d[0]), "+f"(d[1]), "+f"(d[2]), "+f"(d[3]), "+f"(d[4]), "+f"(d[5]), "+f"(d[6]), "+f"(d[7]), "+f"(d[8]), "+f"(d[9]), "+f"(d[10]), "+f"(d[11]), "+f"(d[12]), "+f"(d[13]), "+f"(d[14]), "+f"(d[15])
    : "l"(da), "l"(db));
}

__device__ __align__(128) const uint32_t g_tables[2560] = {
0xa11ba1e4,0xa51ba5e4,0x18b61248,0x1cb61648,0x9f12a052,0xa311a452,0x1d7f1bdb,0x217f1fdb,0x9bdb9d7f,0x9fdba17f,0x20521f12,0x24522311,
0x924898b6,0x96489cb6,0x21e4211b,0x25e4251b,0xaa63ab5f,0xae5faf59,0x21e41bdb,0x25e41fdb,0xa86ba967,0xac6aad65,0x26e024e9,0x2ade28e8,
0xa4e9a6e0,0xa8e8aade,0x2967286b,0x2d652c6a,0x9bdba1e4,0x9fdba5e4,0x2b5f2a63,0x2f592e5f,0xadc2aea7,0xb1b6b294,0x254d1f12,0x294d2311,
0xabf6acde,0xafefb0d7,0x2a31286b,0x2e2d2c6a,0xa86baa31,0xac6aae2d,0x2cde2bf6,0x30d72fef,0x9f12a54d,0xa311a94d,0x2ea72dc2,0x329431b6,
0xb02cb0d2,0xb41ab4b7,0x27a9211b,0x2ba7251b,0xadc2af0c,0xb1b6b2f7,0x2c792a63,0x30742e5f,0xaa63ac79,0xae5fb074,0x2f0c2dc2,0x32f731b6,
0xa11ba7a9,0xa51baba7,0x30d2302c,0x34b7341a,0xb17ab257,0xb552b61a,0x290222ad,0x2d0026ad,0xaf8cb09f,0xb371b487,0x2ddc2c2e,0x31cf3029,
0xac2eaddc,0xb029b1cf,0x309f2f8c,0x34873371,0xa2ada902,0xa6adad00,0x3257317a,0x361a3552,0xb2cdb3e3,0xb682b76f,0x2a312420,0x2e2d281f,
0xb0acb1bb,0xb493b58d,0x2f3f2d2a,0x33283122,0xad2aaf3f,0xb122b328,0x31bb30ac,0x358d3493,0xa420aa31,0xa81fae2d,0x33e332cd,0x376f3682,
0xb413b4bc,0xb7a6b85a,0x2b5f24e9,0x2f5928e8,0xb194b2da,0xb56ab68d,0x30522e28,0x343e3219,0xae28b052,0xb219b43e,0x32da3194,0x368d356a,
0xa4e9ab5f,0xa8e8af59,0x34bc3413,0x385a37a6,0xb4c3b58c,0xb85fb8f3,0x2c4725b2,0x304229b1,0xb27eb3fd,0xb63cb785,0x31062f26,0x34e7330f,
0xaf26b106,0xb30fb4e7,0x33fd327e,0x3785363c,0xa5b2ac47,0xa9b1b042,0x358c34c3,0x38f3385f,0xb577b662,0xb8e5b982,0x2cde267b,0x30d72a7a,
0xb36bb493,0xb70ab83a,0x31bb3012,0x358d3402,0xb012b1bb,0xb402b58d,0x3493336b,0x383a370a,0xa67bacde,0xaa7ab0d7,0x36623577,0x398238e5,
0xb630b741,0xb962ba04,0x2d762744,0x316c2b43,0xb42eb52a,0xb7d2b8ad,0x32713092,0x3631347b,0xb092b271,0xb47bb631,0x352a342e,0x38ad37d2,
0xa744ad76,0xab43b16c,0x37413630,0x3a043962,0xb6eeb815,0xb9d6ba7a,0x2e0e2807,0x32012c06,0xb4a7b5c4,0xb84ab91b,0x33293113,0x36d234f3,
0xb113b329,0xb4f3b6d2,0x35c434a7,0x391b384a,0xa807ae0e,0xac06b201,0x381536ee,0x3a7a39d6,0xb7b4b88e,0xba41bae1,0x2ea7286b,0x32942c6a,
0xb523b662,0xb8a8b982,0x33e33194,0x376f356a,0xb194b3e3,0xb56ab76f,0x36623523,0x398238a8,0xa86baea7,0xac6ab294,0x388e37b4,0x3ae13a41,
0xb841b90f,0xbaa2bb3a,0x2f3f28d0,0x33282cce,0xb5a1b705,0xb902b9e3,0x344f3216,0x380535df,0xb216b44f,0xb5dfb805,0x370535a1,0x39e33902,
0xa8d0af3f,0xacceb328,0x390f3841,0x3b3a3aa2,0xb8acb997,0xbaf7bb83,0x2fd82935,0x33ba2d33,0xb621b7ac,0xb958ba3d,0x34ae3298,0x38503654,
0xb298b4ae,0xb654b850,0x37ac3621,0x3a3d3958,0xa935afd8,0xad33b3ba,0x399738ac,0x3b833af7,0xb91cba28,0xbb42bbbc,0x30392999,0x34262d97,
0xb6a4b82d,0xb9aaba90,0x350e331c,0x389936c6,0xb31cb50e,0xb6c6b899,0x382d36a4,0x3a9039aa,0xa999b039,0xad97b426,0x3a28391c,0x3bbc3b42,
0xb992bac3,0xbb81bbe3,0x308529fe,0x346f2dfb,0xb72ab886,0xb9f8badb,0x357033a0,0x38e03737,0xb3a0b570,0xb737b8e0,0x3886372a,0x3adb39f8,
0xa9feb085,0xadfbb46f,0x3ac33992,0x3be33b81,0x39cf3b16,0x3b9c3bf1,0xb0acaa31,0xb493ae2d,0x376f38b4,0x3a1d3afe,0xb5a1b3e3,0xb902b76f,
0x33e335a1,0x376f3902,0xb8b4b76f,0xbafeba1d,0x2a3130ac,0x2e2d3493,0xbb16b9cf,0xbbf1bb9c,0x39563a74,0x3b633bd2,0xb05fa9cc,0xb44badc9,
0x36e73859,0x39d23ab6,0xb53fb35e,0xb8bcb6ff,0x335e353f,0x36ff38bc,0xb859b6e7,0xbab6b9d2,0x29cc305f,0x2dc9344b,0xba74b956,0xbbd2bb63,
0x38e339de,0x3b1e3ba1,0xb012a967,0xb402ad65,0x36623801,0x39823a67,0xb4deb2da,0xb874b68d,0x32da34de,0x368d3874,0xb801b662,0xba67b982,
0x29673012,0x2d653402,0xb9deb8e3,0xbba1bb1e,0x38763952,0x3ace3b60,0xaf8ca902,0xb371ad00,0x35e13758,0x392e3a11,0xb47eb257,0xb82ab61a,
0x3257347e,0x361a382a,0xb758b5e1,0xba11b92e,0x29022f8c,0x2d003371,0xb952b876,0xbb60bace,0x380d38ce,0x3a733b10,0xaef3a89e,0xb2deac9c,
0x356236b3,0x38d639b3,0xb420b1d5,0xb7bdb5a5,0x31d53420,0x35a537bd,0xb6b3b562,0xb9b3b8d6,0x289e2ef3,0x2c9c32de,0xb8ceb80d,0xbb10ba73,
0x37503851,0x3a0d3ab0,0xae5aa839,0xb24bac38,0x34e53613,0x387a394f,0xb386b153,0xb721b52f,0x31533386,0x352f3721,0xb613b4e5,0xb94fb87a,
0x28392e5a,0x2c38324b,0xb851b750,0xbab0ba0d,0x368e37b4,0x399d3a41,0xadc2a7a9,0xb1b6aba7,0x346a3577,0x381a38e5,0xb2cdb0d2,0xb682b4b7,
0x30d232cd,0x34b73682,0xb577b46a,0xb8e5b81a,0x27a92dc2,0x2ba731b6,0xb7b4b68e,0xba41b99d,0x35d236d1,0x392439c5,0xad2aa6e0,0xb122aade,
0x33e334de,0x376f3874,0xb216b052,0xb5dfb43e,0x30523216,0x343e35df,0xb4deb3e3,0xb874b76f,0x26e02d2a,0x2ade3122,0xb6d1b5d2,0xb9c5b924,
0x351c35f6,0x38a3393c,0xac93a617,0xb08daa16,0x32f43448,0x36a437fe,0xb160afa5,0xb53ab389,0x2fa53160,0x3389353a,0xb448b2f4,0xb7feb6a4,
0x26172c93,0x2a16308d,0xb5f6b51c,0xb93cb8a3,0x346a3523,0x381a38a8,0xabf6a54d,0xafefa94d,0x3209336b,0x35d4370a,0xb0acaea7,0xb493b294,
0x2ea730ac,0x32943493,0xb36bb209,0xb70ab5d4,0x254d2bf6,0x294d2fef,0xb523b46a,0xb8a8b81a,0x33783456,0x3715380a,0xaac8a484,0xaec3a884,
0x3120324a,0x34ff360e,0xaff2ada9,0xb3d3b19e,0x2da92ff2,0x319e33d3,0xb24ab120,0xb60eb4ff,0x24842ac8,0x28842ec3,0xb456b378,0xb80ab715,
0x3223331c,0x35eb36c6,0xa999a376,0xad97a776,0x3039312d,0x3426350b,0xae8dacac,0xb27cb0a6,0x2cac2e8d,0x30a6327c,0xb12db039,0xb50bb426,
0x23762999,0x27762d97,0xb31cb223,0xb6c6b5eb,0x30d23194,0x34b7356a,0xa86ba1e4,0xac6aa5e4,0x2ea73012,0x32943402,0xad2aab5f,0xb122af59,
0x2b5f2d2a,0x2f593122,0xb012aea7,0xb402b294,0x21e4286b,0x25e42c6a,0xb194b0d2,0xb56ab4b7,0x2f0c3012,0x32f73402,0xa67ba052,0xaa7aa452,
0x2cde2df5,0x30d731e8,0xab91a967,0xaf8bad65,0x29672b91,0x2d652f8b,0xadf5acde,0xb1e8b0d7,0x2052267b,0x24522a7a,0xb012af0c,0xb402b2f7,
0x2c792d2a,0x30743122,0xa4209d7f,0xa81fa17f,0x2a312b91,0x2e2d2f8b,0xa8d0a6e0,0xacceaade,0x26e028d0,0x2ade2cce,0xab91aa31,0xaf8bae2d,
0x1d7f2420,0x217f281f,0xad2aac79,0xb122b074,0x27a9286b,0x2ba72c6a,0x9f1298b6,0xa3119cb6,0x254d267b,0x294d2a7a,0xa420a1e4,0xa81fa5e4,
0x21e42420,0x25e4281f,0xa67ba54d,0xaa7aa94d,0x18b61f12,0x1cb62311,0xa86ba7a9,0xac6aaba7,0x3f803f80,0x3f803f80,0x3f803f80,0x3f803f80,
0x3f803f80,0x3f803f80,0x3f803f80,0x3f803f80,0x3f803f80,0x3f803f80,0x3f803f80,0x3f803f80,0x3f803f80,0x3f803f80,0x3f803f80,0x3f803f80,
0x3f803f80,0x3f803f80,0x3f803f80,0x3f803f80,0x3f803f80,0x3f803f80,0x3f803f80,0x3f803f80,0x3f803f80,0x3f803f80,0x3f803f80,0x3f803f80,
0x3f803f80,0x3f803f80,0x3f803f80,0x3f803f80,0x3f803f80,0x3f803f80,0x3f803f80,0x3f803f80,0x3f803f80,0x3f803f80,0x3f803f80,0x3f803f80,
0x3f803f80,0x3f803f80,0x3f803f80,0x3f803f80,0x3f803f80,0x3f803f80,0x3f803f80,0x3f803f80,0x3f803f80,0x3f803f80,0x3f803f80,0x3f803f80,
0x3f803f80,0x3f803f80,0x3f803f80,0x3f803f80,0x3f803f80,0x3f803f80,0x3f803f80,0x3f803f80,0x3f803f80,0x3f803f80,0x3f803f80,0x3f803f80,
0x3f803f80,0x3f803f80,0x3f803f80,0x3f803f80,0x3f803f80,0x3f803f80,0x3f803f80,0x3f803f80,0x3f803f80,0x3f803f80,0x3f803f80,0x3f803f80,
0x3f803f80,0x3f803f80,0x3f803f80,0x3f803f80,0x3f803f80,0x3f803f80,0x3f803f80,0x3f803f80,0x3f803f80,0x3f803f80,0x3f803f80,0x3f803f80,
0x3f803f80,0x3f803f80,0x3f803f80,0x3f803f80,0x3f803f80,0x3f803f80,0x3f803f80,0x3f803f80,0x3f803f80,0x3f803f80,0x3f803f80,0x3f803f80,
0x3f803f80,0x3f803f80,0x3f803f80,0x3f803f80,0x3f803f80,0x3f803f80,0x3f803f80,0x3f803f80,0x3f803f80,0x3f803f80,0x3f803f80,0x3f803f80,
0x3f803f80,0x3f803f80,0x3f803f80,0x3f803f80,0x3f803f80,0x3f803f80,0x3f803f80,0x3f803f80,0x3f803f80,0x3f803f80,0x3f803f80,0x3f803f80,
0x3f803f80,0x3f803f80,0x3f803f80,0x3f803f80,0x3f803f80,0x3f803f80,0x3f803f80,0x3f803f80,0x3f803f80,0x3f803f80,0x3f803f80,0x3f803f80,
0x3f803f80,0x3f803f80,0x3f803f80,0x3f803f80,0x3f803f80,0x3f803f80,0x3f803f80,0x3f803f80,0x3f803f80,0x3f803f80,0x3f803f80,0x3f803f80,
0x3f803f80,0x3f803f80,0x3f803f80,0x3f803f80,0x3f803f80,0x3f803f80,0x3f803f80,0x3f803f80,0x3f803f80,0x3f803f80,0x3f803f80,0x3f803f80,
0x3f803f80,0x3f803f80,0x3f803f80,0x3f803f80,0x3f803f80,0x3f803f80,0x3f803f80,0x3f803f80,0x3f803f80,0x3f803f80,0x3f803f80,0x3f803f80,
0x3f803f80,0x3f803f80,0x3f803f80,0x3f803f80,0x3f803f80,0x3f803f80,0x3f803f80,0x3f803f80,0x3f803f80,0x3f803f80,0x3f803f80,0x3f803f80,
0x3f803f80,0x3f803f80,0x3f803f80,0x3f803f80,0x3f803f80,0x3f803f80,0x3f803f80,0x3f803f80,0x3f803f80,0x3f803f80,0x3f803f80,0x3f803f80,
0x3f803f80,0x3f803f80,0x3f803f80,0x3f803f80,0x3f803f80,0x3f803f80,0x3f803f80,0x3f803f80,0x3f803f80,0x3f803f80,0x3f803f80,0x3f803f80,
0x3f803f80,0x3f803f80,0x3f803f80,0x3f803f80,0x3f803f80,0x3f803f80,0x3f803f80,0x3f803f80,0x3f803f80,0x3f803f80,0x3f803f80,0x3f803f80,
0x3f803f80,0x3f803f80,0x3f803f80,0x3f803f80,0x3f803f80,0x3f803f80,0x3f803f80,0x3f803f80,0x3f803f80,0x3f803f80,0x3f803f80,0x3f803f80,
0x3f803f80,0x3f803f80,0x3f803f80,0x3f803f80,0x3f803f80,0x3f803f80,0x3f803f80,0x3f803f80,0x3f803f80,0x3f803f80,0x3f803f80,0x3f803f80,
0x3f803f80,0x3f803f80,0x3f803f80,0x3f803f80,0x3f803f80,0x3f803f80,0x3f803f80,0x3f803f80,0x3f803f80,0x3f803f80,0x3f803f80,0x3f803f80,
0x3f803f80,0x3f803f80,0x3f803f80,0x3f803f80,0x3f803f80,0x3f803f80,0x3f803f80,0x3f803f80,0x3f803f80,0x3f803f80,0x3f803f80,0x3f803f80,
0x3f803f80,0x3f803f80,0x3f803f80,0x3f803f80,0x3f803f80,0x3f803f80,0x3f803f80,0x3f803f80,0x3f803f80,0x3f803f80,0x3f803f80,0x3f803f80,
0x3f803f80,0x3f803f80,0x3f803f80,0x3f803f80,0x3f803f80,0x3f803f80,0x3f803f80,0x3f803f80,0x3f803f80,0x3f803f80,0x3f803f80,0x3f803f80,
0x3f803f80,0x3f803f80,0x3f803f80,0x3f803f80,0x3f803f80,0x3f803f80,0x3f803f80,0x3f803f80,0x3f803f80,0x3f803f80,0x3f803f80,0x3f803f80,
0x3f803f80,0x3f803f80,0x3f803f80,0x3f803f80,0x3f803f80,0x3f803f80,0x3f803f80,0x3f803f80,0x3f803f80,0x3f803f80,0x3f803f80,0x3f803f80,
0x3f803f80,0x3f803f80,0x3f803f80,0x3f803f80,0x3f803f80,0x3f803f80,0x3f803f80,0x3f803f80,0x3f803f80,0x3f803f80,0x3f803f80,0x3f803f80,
0x3f803f80,0x3f803f80,0x3f803f80,0x3f803f80,0x3f803f80,0x3f803f80,0x3f803f80,0x3f803f80,0x3f803f80,0x3f803f80,0x3f803f80,0x3f803f80,
0x3f803f80,0x3f803f80,0x3f803f80,0x3f803f80,0x3f803f80,0x3f803f80,0x3f803f80,0x3f803f80,0x3f803f80,0x3f803f80,0x3f803f80,0x3f803f80,
0x3f803f80,0x3f803f80,0x3f803f80,0x3f803f80,0x3f803f80,0x3f803f80,0x3f803f80,0x3f803f80,0x3f803f80,0x3f803f80,0x3f803f80,0x3f803f80,
0x3f803f80,0x3f803f80,0x3f803f80,0x3f803f80,0x3f803f80,0x3f803f80,0x3f803f80,0x3f803f80,0x3f803f80,0x3f803f80,0x3f803f80,0x3f803f80,
0x3f803f80,0x3f803f80,0x3f803f80,0x3f803f80,0x3f803f80,0x3f803f80,0x3f803f80,0x3f803f80,0x3f803f80,0x3f803f80,0x3f803f80,0x3f803f80,
0x3f803f80,0x3f803f80,0x3f803f80,0x3f803f80,0x3f803f80,0x3f803f80,0x3f803f80,0x3f803f80,0x3f803f80,0x3f803f80,0x3f803f80,0x3f803f80,
0x3f803f80,0x3f803f80,0x3f803f80,0x3f803f80,0x3f803f80,0x3f803f80,0x3f803f80,0x3f803f80,0x3f803f80,0x3f803f80,0x3f803f80,0x3f803f80,
0x3f803f80,0x3f803f80,0x3f803f80,0x3f803f80,0x3f803f80,0x3f803f80,0x3f803f80,0x3f803f80,0x3f803f80,0x3f803f80,0x3f803f80,0x3f803f80,
0x3f803f80,0x3f803f80,0x3f803f80,0x3f803f80,0x3f803f80,0x3f803f80,0x3f803f80,0x3f803f80,0x3f803f80,0x3f803f80,0x3f803f80,0x3f803f80,
0x3f803f80,0x3f803f80,0x3f803f80,0x3f803f80,0x3f803f80,0x3f803f80,0x3f803f80,0x3f803f80,0x3f803f80,0x3f803f80,0x3f803f80,0x3f803f80,
0x3f803f80,0x3f803f80,0x3f803f80,0x3f803f80,0x3f803f80,0x3f803f80,0x3f803f80,0x3f803f80,0x3f803f80,0x3f803f80,0x3f803f80,0x3f803f80,
0x3f803f80,0x3f803f80,0x3f803f80,0x3f803f80,0x3f803f80,0x3f803f80,0x3f803f80,0x3f803f80,0x3f803f80,0x3f803f80,0x3f803f80,0x3f803f80,
0x3f803f80,0x3f803f80,0x3f803f80,0x3f803f80,0x3f803f80,0x3f803f80,0x3f803f80,0x3f803f80,0x3f803f80,0x3f803f80,0x3f803f80,0x3f803f80,
0x3f803f80,0x3f803f80,0x3f803f80,0x3f803f80,0x3f803f80,0x3f803f80,0x3f803f80,0x3f803f80,0x3f803f80,0x3f803f80,0x3f803f80,0x3f803f80,
0x3f803f80,0x3f803f80,0x3f803f80,0x3f803f80,0x3f803f80,0x3f803f80,0x3f803f80,0x3f803f80,0x3f803f80,0x3f803f80,0x3f803f80,0x3f803f80,
0x3f803f80,0x3f803f80,0x3f803f80,0x3f803f80,0x3bf23bff,0x3ba53bd4,0x3b163b65,0x3a493ab6,0x3b7c3bfb,0x38bc3a60,0x2b43356a,0xb7f3b359,
0x3a933bf1,0x9cb63764,0xba9eb785,0xbb73bbf3,0x39463be2,0xb8cc28e8,0xbb42bbc2,0x3328b70a,0x374e3bcf,0xbbabb648,0xaec3baa9,0x3bfa3994,
0x33403bb7,0xbb85b9fc,0x3a64b0be,0x2c6a3b47,0xa4523b9a,0xb86abbae,0x3b6a3911,0xbbd0ad65,0xb4263b78,0x2adebbe6,0x30f03bfd,0xb5b1bbbc,
0x2f5925e4,0x34b73294,0x376f361a,0x38f3385a,0x35a52c9c,0x3a7338d6,0x3bfd3b87,0x3af13bc9,0x388e2fbd,0x3c003b18,0x387f3b10,0xb5d42f27,
0x3a04316c,0x3a673bfe,0xb6bb33d3,0xbbccbb2f,0x3b1e32f7,0x34933b5c,0xbbf5b86f,0x2d00b9bc,0x3bcb343e,0xb576394f,0xb8d1bbe9,0x3bfb36a4,
0x3c0034ff,0xbaac347b,0x3602ba31,0x32de3bf9,0x3bba35bc,0xbbfdb109,0x3be7aa7a,0xbb7a341a,0x394639cd,0x381538b2,0x358136dd,0x3153341a,
0xbb1eb9c9,0xbbf5bbdd,0xba39bb65,0xb4f3b889,0xb340b93c,0x3966340e,0x3bec3b87,0x37213a7e,0x3c003a4d,0x32193a21,0xbb5eb785,0xb894bbb0,
0xb426389e,0xbb37bb45,0x38b7b3d3,0x397d3bfc,0xbafebac1,0x3b13217f,0xadc93aa9,0xba49bb59,0x3979b7e8,0xb0d73b32,0xb6f4bbe9,0x3af139da,
0x38553b24,0xb9a1ba3d,0x3ab03911,0xbb73b759,0x3a043982,0x3ae13a7a,0x3b833b3a,0x3be33bbc,0x374e3986,0xae9131e8,0xb907b61a,0xbb9cba97,
0xbbcbba0d,0xb9e7bbbd,0x3074b56a,0x3b2a38ad,0x2452b8ee,0x3bda3924,0x363c3b10,0xba90b46f,0x3bba3a89,0xb6e836af,0xba76bbc2,0x39d2ac06,
0xb7c8384a,0xb77abc00,0x3bf8386f,0xb8f33654,0xb9d6baf4,0x3be836ff,0xbb3530be,0x37f3b974,0x3abab737,0xb9af3902,0x3865ba31,0xb5d43b1b,
0x32c62fbd,0x363134cf,0x38653785,0x398b38fd,0xb715b16c,0xbae1b970,0xbbfebbc2,0xba85bb92,0x392e32f7,0x3bf53b6c,0x37a63aa9,0xb7422311,
0xba81b43e,0xb9e7bbfc,0x380fb0be,0x3b963b7f,0x3b7134ff,0x32193b04,0xbc00b911,0x319eb929,0xbbefb5bc,0x36e8b8b2,0x382a3bfd,0xbbffb805,
0x3bf23676,0xbb1331e8,0x376fb9aa,0x2f8b3bde,0xbb7cb72c,0x3be8340e,0xbbfdaa16,0x3bb8b122,0xbbd2bbf1,0xbb60bba1,0xbab0bb10,0xb9c5ba41,
0x3b2c3be2,0x381539df,0xa94d33d3,0xb8a3b52f,0xba19bbcf,0x2e91b5f7,0x3b07386f,0x3b213c00,0x38a83bb7,0xb966aba7,0xbae5bbe9,0x3517b599,
0xb5dfbb9a,0x3bda37b2,0x1fdb3a31,0xbbe0ba1d,0x30293b78,0xbb37ba7a,0x3ad5aa7a,0xa7763aeb,0x2f59bb52,0x377a3bdd,0xbb16b9a6,0x3bf231cf,
0xb5a53b27,0x30d7bbbd,0x2b433bfe,0xb432bbe5,0x3a813a0d,0x3b3f3ae8,0x3bbf3b87,0x3bfb3be5,0xb5dfb8ee,0x3263ad97,0x399d3785,0x3bd03b01,
0xbbefba89,0xb958bb81,0x3389b3d3,0x3b7a394a,0xaf59384a,0xbbf7b9b8,0xb4c3baa9,0x3afb35eb,0x3b7c3af4,0xb825353a,0xb9f8bbe9,0x3a542884,
0x388eb737,0x360e3bf4,0xbbdcb911,0x398bb4db,0xb946bb4f,0x3bc03830,0xbb832a7a,0x38a3b8db,0xbb1e35c8,0x3a35b85f,0xb90739aa,0x3742bab6,
0xb8a8b93c,0xb6c6b80a,0xb402b56a,0xac6ab122,0xbb71ba4d,0xbbd7bbf8,0xb9b3bb10,0xb2deb7bd,0x3029389e,0xb9f4b58d,0xbbc6bbc2,0xb5b1ba00,
0x3bf23ac1,0x2dfb3999,0xbba3b86f,0xb7d2bb6f,0x35a5b7e8,0x3ad83b90,0xb95430be,0xb8e5bbff,0xba93bb24,0x3b682ef5,0xb2013a31,0xb9c5bb9f,
0xba043682,0x33ebbad1,0x35813bfd,0xba85ba5c,0x374e3b76,0xb90cbab3,0x3a3939a6,0xbb21b85a,0xb7c83b52,0x391bba9b,0xba2539aa,0x3afbb889,
0xb9793b27,0x3bc5b80a,0xbb8eaa16,0x38e538ad,0xbaba3af7,0x3b60ad97,0xb27cba2d,0xb98b3bb0,0xbb943ac4,0x3815358d,0x39e3bbea,0xba852c06,
0xbbf93a8c,0xae9139b8,0x3bacb874,0x3742bb59,0xbbe43a50,0xb9663b90,0x340233ba,0x3b96b974,0xbb573a11,0xbbda3bf4,0xb99d3b0d,0xb19e3759,
0xba5839cd,0xbb373ad1,0xbbc63b89,0xbbff3bee,0x3afe3676,0xba29b884,0x391f39a6,0xb7d2ba97,0x39d6372c,0xb3a2bae8,0xb5463bfe,0x3a54ba7e,
0x385537dd,0x3631bbf8,0xbbd63916,0x39c5346f,0x35233845,0x3ae1bb81,0xb96bb0a6,0xb8a33bfc,0x2d333899,0x3bf5b999,0x3487baa5,0xbb213654,
0xb13b38ea,0x39e7b53a,0x3bbfbbc3,0x3517b9da,0xb65f3937,0x32192ef5,0x39b3b790,0x3be0bb1b,0xb8e03982,0xb6e83830,0xb389355e,0xa7763042,
0xbb943682,0x3bebb371,0xbbfe2a7a,0x3bcc3042,0xad33bb76,0xb79b3bd4,0x3b07b9aa,0xbbfa32ad,0x3be4b50b,0xb6c6b8d6,0xb80f3bfe,0x3bfbb835,
0xb65f3bb5,0x3bd7b764,0x9fdbba2d,0xbbd03a41,0xba58330f,0xb9f43bfe,0x382a30a6,0x3b7abb92,0x3a45bbe1,0xadfbb648,0xbb163874,0xbafb3c00,
0x3699afef,0x3ad8b94f,0x3bfdbbc3,0x3a54bb7f,0xbbdf3bfa,0xbb683bae,0xba9e3b0d,0xb98b3a1d,0x35233b4f,0xb08dbbc8,0xa94d3bfd,0x3328bbee,
0xbbf935c8,0x3b0a3294,0xb7a6b9a6,0xad003bd3,0x313bbb98,0xbb3f3a60,0x3ae52a16,0xac6abace,0x3b57b44b,0x3263bb18,0xbc003916,0x32de38fd,
0xb8e03bce,0x3958a8e8,0x3ad5bbea,0xb5b1b52f,0xb8f83185,0xbbf73b5c,0xb76f3aa5,0x37d2a311,0x3b4abbf0,0x3825b9fc,0xab43b3ba,0xb8e53599,
0x31b6acce,0x360eb47b,0x387fb790,0x39c5b929,0x3a9337dd,0xb9a1b924,0x387f3a2d,0xb66bbb01,0xb946b845,0x308d3b45,0x36bbbbea,0xbac73a00,
0x374e3899,0x379bbc00,0xbbf53874,0x393335eb,0xb340b8ea,0xbb3f3b32,0x38d133ba,0x3941bbff,0xa4523937,0x3bd7b902,0x3602bb0d,0xbabd34db,
0x3426b982,0xb9583371,0xbbe73b89,0xb68d3a5c,0xb7c839c9,0x2dfb3294,0x391fb625,0x3bb3bab6,0x3979ba0d,0x3825b8d6,0x3546b6d2,0x3010b359,
0x388ebaf7,0xb9af3a21,0x3a9eb916,0xbb5437bd,0xba043ac4,0x3bebb6af,0xbb42b0a6,0x3840394a,0x3b1eba8c,0xbb0aa17f,0x2ec33aa5,0x3a15bb6f,
0xbbcb3a50,0x36c636ff,0x3a64bbc3,0xba09a884,0x3c00ba11,0x3263ba3d,0xbb6a3790,0xb8503b9f,0xbbba39cd,0xb9f43bc8,0x30f0355e,0x3b4cb8db,
0x3afeb986,0x3bf7bbd4,0x3a25bb63,0x3457b85a,0xb9d6393c,0xbad83a60,0xbb8e3b3d,0xbbef3bc9,0x33403b98,0xa9b1bbed,0xb0743bfe,0x3517bbc9,
0x3c00b44b,0xbaa2b4cf,0x363c3a2d,0x319ebbf3,0x3426bbce,0xbb8b39df,0x3a7630a6,0x2776bb2f,0xbafe3185,0xb4b73b6c,0x3bf8b874,0xaf8bb994,
0xb9793bf0,0x38bc2ba7,0x3b35bbc3,0xb432b6a4,0x3855acce,0x3c00bb04,0x3865bb0d,0xb66bad65,0x3b94bbff,0x38ccba7a,0x294db55e,0xb840341a,
0xad33a5e4,0xb49331e8,0xb7a63625,0xb9333889,0x3bcbb50b,0xbbfe305b,0x3bec2a16,0xbb96b359,0x2452bbb5,0xb87a3ba1,0x3b5eb916,0xbbe02f27,
0xbbba330f,0x35523970,0x38b7bbea,0xbbff370a,0xb7c83be1,0x3ba5b5f7,0x2dc9baa5,0xbbf239bc,0x39d6afef,0x3a73bbfc,0xb6f4b3ba,0xbbb83b47,
0x3ababbfa,0x1cb6b7b2,0xbab03790,0xbb543bf9,0xb52326ad,0xba6738b2,0xbbfe3b89,0xbac73bbc,0xbbf93bff,0xbbab3bdd,0xbb073b63,0xba153a97,
0xb8f83986,0xb77a385f,0xb4c33625,0xaf8b32ad,0xb699393c,0x30d7305b,0x3954b6d2,0x3bb8bace,0xb1b638ee,0x39afb4cf,0x3bdcbba7,0x366bba41,
0x2c38389e,0x3bebb970,0x3581bade,0xbac7352f,0x34e7384a,0x3b0abb6c,0xb907b24b,0xb9333c00,0x383a37e8,0x36c6bbfc,0xbbec38c1,0x39413599,
0x39c03737,0xb263bb04,0xb63c3bf6,0x3abdba1d,0x3aee3682,0xb9f4b8b2,0x38b739f0,0xb68dbaeb,0xba4539c9,0xbb133ab3,0xbba33b63,0xbbf23bd3,
0xbb4a3a0d,0xbbe83bed,0xb9f83b3d,0xb4323835,0xbbdf3a4d,0xb9a13ba1,0x320134ab,0x3b54b8fd,0xbbfc3a89,0xb08d39df,0x3b83b81a,0x3840bb92,
0xbb9e3ac1,0x379b35f7,0x3a39bbd8,0xba15a311,0xbacb3af4,0x3b3faba7,0xb074ba6f,0xba093b7f,0xb9903b24,0x3bd7b7b2,0xbb5eae5f,0x38503929,
0xb7fe3b4f,0x3958ba7a,0xba76395d,0x3b4cb805,0x2c3826ad,0x33ebb109,0x36bbb55e,0x38a3b805,0x3b9ebbff,0x390cba9b,0x2ec3b625,0xb74231cf,
0xb83a2c9c,0xbbfe3ae8,0xb8d13b3d,0x35173122,0xb9903bf1,0x387a2d97,0x3b6abba7,0xb19eb7bd,0x3aeeb16c,0x3552bb81,0xbbe7381a,0x27763a00,
0x3463bbcf,0xbba539b8,0x3a25324b,0x2f8bbb6f,0xbbff343e,0x3a73353a,0xb546ba6f,0xb4323bff,0x32c63b9a,0x9cb6bbf4,0xb27c3bf6,0x366bbb9f,
0xbbfc3bff,0xbbc03be6,0xbb423b89,0xba853aeb,0x34e7a5e4,0x3a35b884,0x3bf5bb63,0x3b21bbde,0x3acbbbfb,0x29b1b80a,0xba6436d2,0xbb963be5,
0xb9c02fbd,0xbaa23bf8,0x360234ab,0x3be0bb01,0xb7fe3be2,0x3b8bb58d,0x30f0bade,0xbbff394a,0x3bb2b2f7,0xb4b7b999,0xb91f3bd8,0x3bf2b5eb,
0x281fbbb7,0xb8bc3b90,0x3b8eb8c1,0xbbb82884,0xbbd234ff,0x3c00aef5,0xbbd6ae5f,0x3b5434db,0xbaba3a4d,0xbb683b18,0xbbd63ba7,0xbc003bf3,
0x3b94ba89,0x3bc0bbfe,0x396bbade,0x3153b70a,0xbbf93ac1,0xb90c3b5c,0x3487324b,0x3b9cb994,0x3be4baf4,0x29b1b94f,0xbbbf38c1,0xb7213b47,
0xbb573b24,0x387a347b,0x39b3bbf6,0xba902d65,0x3a58bb4f,0xbb8b3109,0x338939f0,0x397dbbbc,0xb8f83b76,0x3ba5b884,0xbba39648,0x38f33889,
0x3699bb98,0xb8bc3ae8,0x39f8b9eb,0xbaf138ad,0x3855b8ee,0x360eb764,0x327cb4ab,0x251baf27,0xb523389e,0x33eb28e8,0x39e3b81a,0x3be3bb2f,
0x2d33b84a,0xba353648,0xbbac3bd8,0xb4f339bc,0x313b37e8,0x3bfeb9fc,0x3402ba6f,0xbb2a36a4,0xb65fb737,0xbaa23bae,0x399d2e5f,0x3894bbf9,
0x38e03682,0x3552bbe6,0xbbc6395d,0x39d2341a,0xba45b5c8,0x34b73a9b,0x34c3bc00,0xba493a97,0x3b4a350b,0xba73b80a,0x39543962,0xb7f3ba7e,
0xbbe43bfb,0xbb853bbd,0xbae53b3d,0xba093a7e,0xb65f2fbd,0xbaac3924,0xbc003ba7,0xbabd3bb0,0x3a58bbe2,0xaadeb6af,0xbad5381a,0xbb4c3bfc,
0x3a45b2f7,0x3a29bc00,0xb76fb24b,0xbbb33b59,0xb6993bb7,0x3bc5b6ff,0x2b43ba6f,0xbbef39da,0xbbdf34ff,0x36313902,0x387fbbf6,0xbc003759,
0xac38bb78,0xb8153bc8,0x3b42b95d,0xbbe33042,0x3b9eb676,0xbbf53294,0x3bf51648,0xbb9cb2ad,0xb13b2c9c,0xb576340e,0xb80f36d2,0xb94138ad,
0x3b57bbf1,0x386aba21,0x1fdbb4ab,0xb850346f,0x38e0b16c,0x3bfdbb45,0x382abade,0xb68dac06,0xb8f83bcf,0x391ba17f,0x3b16bbd8,0xb457b654,
0xbb4a343e,0xb3a23b32,0x3bfdb8c1,0xb010b974,0x31b6bb9a,0xbb603a3d,0x3a9e2e5f,0x251bbb1b,0x3bfcb5bc,0xbae1b371,0x36bb39f0,0x3153bbee,
0x34e73b52,0xae91bbd4,0xaec33c00,0x34f3bbd3,0x3bb235c8,0xbbf7b1e8,0x3bf81648,0xbbb331cf,0x3bff350b,0xbad8340e,0x36f4b9eb,0x30103be5,
0x3bd2344b,0xb60e3924,0xb865bbf6,0x3c0037bd,0x3b2c330f,0x33eb3b45,0xbbfeb8c7,0x3153b94a,0x3a193185,0x3a353c00,0xb7a63232,0xbb9cbb6f,
0x38a82fef,0x3bfe3b32,0x380f3adb,0xb7212884,0x35df2cce,0x3aa23902,0x3c003ba9,0x3a903b9f,0x302926ad,0x35523371,0x382a36dd,0x397d38db,
0xb4633b76,0x2dfbbbdd,0x2dc93c00,0xb457bbde,0xa81f3b98,0xb825bbbd,0x3b353962,0xbbefb122,0x32c63bb5,0xbb68ba21,0x3ab0ae2d,0xa51b3b01,
0x37153bce,0xbbc0b6af,0xa94dba6b,0x3be33a00,0x392e3be1,0xb90c217f,0xbb07bbd9,0x34f3b5eb,0x3a813bf0,0xa9b136ff,0xbae5b820,0xbb2abbff,
0x3b713bfa,0x387a3a3d,0x9fdb349f,0xb894b4db,0x3bef3bff,0x3b8b3bc8,0x3ad53b3a,0x39d23a5c,0x3b2cb5bc,0xba673830,0x396bb95d,0xb8403a5c,
0xb92ebb52,0x3bab385f,0xbbac9648,0x3933b85a,0xb8a8372c,0xb576bbed,0x3bbf3962,0xba093359,0x3b713af7,0xb86a34cf,0xb99dbbf6,0x3abd2f27,
0x3029b845,0x3bfd39df,0x33893a6b,0xbb4cb70a,0xbbf2ba8c,0xb91bbb6c,0x34c3b232,0x3bb339bc,0x35a538ea,0xb3a22ba7,0xb9f8b820,0xbbefbb47,
0x3a933a11,0x3b603b04,0x3bdc3ba9,0x3c003bf9,0x37153b78,0xb8ccbad1,0x39e339f0,0xbac7b8db,0x3a19b676,0xb4933ab3,0xb487bc00,0x3a153ab6,
0xba81bb27,0x3b85305b,0xb40239eb,0xb941bbc9,0xb5df37dd,0xbaacbba1,0x39b3ae2d,0x38503bf3,0x3bef3ac4,0x2ade3970,0xbbc6b8c7,0xb68dbb2f,
0xaf59b899,0x3a2935f7,0x3ba33bd9,0x34573994,0xbb7cba50,0xbbc5bbfc,0xb954badb,0xb010b6a4,0x388e3937,0x363137b2,0x3201349f,0xa51b2d65,
0xb1b63bb5,0x9cb6bbf8,0x32013bf6,0xb5d4bbb0,0xac38bbce,0x38cc3b81,0xbb83b8c7,0x3bcc2c06,0x34e73be1,0xbbabb999,0x3a39b232,0x2d003b59,
0xb83abbf0,0x3b85353a,0x30743adb,0xbbfbb974,0x39c03bfa,0xb86a2ef5,0xbb5ebba9,0x32deb759,0xbaeebbff,0xaadeb830,0x3a7636dd,0x3b7a3bee,
0x3bb23bff,0x391b3ab3,0x2dc9361a,0xb7d2b2ad,0xbbffbbfb,0xbbc5bbed,0xbb35bb87,0xba54bace,0xbbdfb44b,0x3c002d97,0xbbdc2e2d,0x3b73b46f,
0x3bfc330f,0xba67358d,0x3581ba6b,0x33283bfc,0xbb9eb185,0x3493b9b8,0x39073bd9,0xbbfab654,0x3acb2fef,0x35763b90,0xbbecb820,0x2c6ab9da,
0xb990acce,0xbaacbbf4,0x363cb49f,0x3bd03b1b,0x37fe26ad,0x3bfd3ad1,0x38b73b3a,0xb5b13042,0xb46325e4,0xba29b85f,0xbbf8bb65,0xbafbbbd3,
0x281fac9c,0x33a2305b,0x36f4356a,0x38e53835,0x383a3b27,0xb966ba60,0x3a643962,0xbb2ab835,0xb99037dd,0x3219bb18,0x36023bf6,0xba90ba41,
0xbaeebac4,0x3b3728e8,0xb0f03a6b,0xb9d2bb92,0x3463b899,0x3b133b5c,0xb91f3232,0xb8f3bc00,0x3bff3a50,0x30d739fc,0xbb8eb820,0xb7f3bb7f,
0x32c63937,0xb9a1b47b,0xbbd6bba9,0xb5d4ba1d,0xbb2cb9cd,0xbbebbbe6,0xb9e3bb3a,0xb328b805,0xb92eb9c9,0xb79bb884,0xb487b61a,0xad00b1cf,
0xbacb372c,0x39e7b8d6,0xb8d139eb,0x3721bace,0xb9c0baf7,0x3bda3764,0xbb6a2e2d,0x3894b8fd,0x37feb845,0x36e83bfe,0xbbe7b8c7,0x397db52f,
0x3bb23a8c,0xb77a3648,0xba25bbd9,0x3a492311,0xa81f38ea,0xbbe8b94f,0xb546badb,0x3af13599,0xbbd2ba11,0xb9afbbae,0x327cb49f,0x3b733929,
0xb715b982,0x308db109,0x396b36dd,0x3bcc3aeb,0x3a193986,0x3b0a3a9b,0x3bac3b65,0x3bfa3bde,0x30003000,0x30003000,0x30003000,0x30003000,
0x2f643000,0x2a1f2da8,0xaa1f0000,0xaf64ada8,0x2da83000,0xada80000,0xada8b000,0x2da88000,0x2a1f3000,0xaf64ada8,0x2f648000,0xaa1f2da8,
0x00003000,0x8000b000,0x00003000,0x8000b000,0xaa1f3000,0x2f64ada8,0xaf640000,0x2a1f2da8,0xada83000,0x2da88000,0x2da8b000,0xada80000,
0xaf643000,0xaa1f2da8,0x2a1f8000,0x2f64ada8,0x30003000,0x30003000,0x30003000,0x30003000,0xaf64b000,0xaa1fada8,0x2a1f8000,0x2f642da8,
0x2da83000,0xada80000,0xada8b000,0x2da88000,0xaa1fb000,0x2f642da8,0xaf640000,0x2a1fada8,0x00003000,0x8000b000,0x00003000,0x8000b000,
0x2a1fb000,0xaf642da8,0x2f648000,0xaa1fada8,0xada83000,0x2da88000,0x2da8b000,0xada80000,0x2f64b000,0x2a1fada8,0xaa1f0000,0xaf642da8,
0x80008000,0x80008000,0x80008000,0x80008000,0xaa1f8000,0xaf64ada8,0xaf64b000,0xaa1fada8,0xada88000,0xada8b000,0x2da88000,0x2da83000,
0xaf648000,0x2a1fada8,0x2a1f3000,0xaf64ada8,0xb0008000,0x30008000,0xb0008000,0x30008000,0xaf648000,0x2a1f2da8,0x2a1fb000,0xaf642da8,
0xada88000,0xada83000,0x2da88000,0x2da8b000,0xaa1f8000,0xaf642da8,0xaf643000,0xaa1f2da8,0x80008000,0x80008000,0x80008000,0x80008000,
0x2a1f8000,0x2f642da8,0x2f643000,0x2a1f2da8,0xada88000,0xada8b000,0x2da88000,0x2da83000,0x2f648000,0xaa1f2da8,0xaa1fb000,0x2f642da8,
0xb0008000,0x30008000,0xb0008000,0x30008000,0x2f648000,0xaa1fada8,0xaa1f3000,0x2f64ada8,0xada88000,0xada83000,0x2da88000,0x2da8b000,
0x2a1f8000,0x2f64ada8,0x2f64b000,0x2a1fada8,0xb0003000,0xb0003000,0xb0003000,0xb0003000,0xaf643000,0xaa1f2da8,0x2a1f0000,0x2f64ada8,
0xada83000,0x2da80000,0x2da8b000,0xada88000,0xaa1f3000,0x2f64ada8,0xaf648000,0x2a1f2da8,0x80003000,0x0000b000,0x80003000,0x0000b000,
0x2a1f3000,0xaf64ada8,0x2f640000,0xaa1f2da8,0x2da83000,0xada88000,0xada8b000,0x2da80000,0x2f643000,0x2a1f2da8,0xaa1f8000,0xaf64ada8,
0xb0003000,0xb0003000,0xb0003000,0xb0003000,0x2f64b000,0x2a1fada8,0xaa1f8000,0xaf642da8,0xada83000,0x2da80000,0x2da8b000,0xada88000,
0x2a1fb000,0xaf642da8,0x2f640000,0xaa1fada8,0x80003000,0x0000b000,0x80003000,0x0000b000,0xaa1fb000,0x2f642da8,0xaf648000,0x2a1fada8,
0x2da83000,0xada88000,0xada8b000,0x2da80000,0xaf64b000,0xaa1fada8,0x2a1f0000,0x2f642da8,0x80008000,0x80008000,0x80008000,0x80008000,
0x2a1f8000,0x2f64ada8,0x2f64b000,0x2a1fada8,0x2da88000,0x2da8b000,0xada88000,0xada83000,0x2f648000,0xaa1fada8,0xaa1f3000,0x2f64ada8,
0x30008000,0xb0008000,0x30008000,0xb0008000,0x2f648000,0xaa1f2da8,0xaa1fb000,0x2f642da8,0x2da88000,0x2da83000,0xada88000,0xada8b000,
0x2a1f8000,0x2f642da8,0x2f643000,0x2a1f2da8,0x80008000,0x80008000,0x80008000,0x80008000,0xaa1f8000,0xaf642da8,0xaf643000,0xaa1f2da8,
0x2da88000,0x2da8b000,0xada88000,0xada83000,0xaf648000,0x2a1f2da8,0x2a1fb000,0xaf642da8,0x30008000,0xb0008000,0x30008000,0xb0008000,
0xaf648000,0x2a1fada8,0x2a1f3000,0xaf64ada8,0x2da88000,0x2da83000,0xada88000,0xada8b000,0xaa1f8000,0xaf64ada8,0xaf64b000,0xaa1fada8,
0x00000000,0x00000000,0x00000000,0x00000000,0x2a1f0000,0x2f642da8,0x2f643000,0x2a1f2da8,0x2da80000,0x2da83000,0xada80000,0xada8b000,
0x2f640000,0xaa1f2da8,0xaa1fb000,0x2f642da8,0x30000000,0xb0000000,0x30000000,0xb0000000,0x2f640000,0xaa1fada8,0xaa1f3000,0x2f64ada8,
0x2da80000,0x2da8b000,0xada80000,0xada83000,0x2a1f0000,0x2f64ada8,0x2f64b000,0x2a1fada8,0x00000000,0x00000000,0x00000000,0x00000000,
0xaa1f0000,0xaf64ada8,0xaf64b000,0xaa1fada8,0x2da80000,0x2da83000,0xada80000,0xada8b000,0xaf640000,0x2a1fada8,0x2a1f3000,0xaf64ada8,
0x30000000,0xb0000000,0x30000000,0xb0000000,0xaf640000,0x2a1f2da8,0x2a1fb000,0xaf642da8,0x2da80000,0x2da8b000,0xada80000,0xada83000,
0xaa1f0000,0xaf642da8,0xaf643000,0xaa1f2da8,0x30003000,0x30003000,0x30003000,0x30003000,0x2f643000,0x2a1f2da8,0xaa1f0000,0xaf64ada8,
0x2da83000,0xada80000,0xada8b000,0x2da88000,0x2a1f3000,0xaf64ada8,0x2f648000,0xaa1f2da8,0x00003000,0x8000b000,0x00003000,0x8000b000,
0xaa1f3000,0x2f64ada8,0xaf640000,0x2a1f2da8,0xada83000,0x2da88000,0x2da8b000,0xada80000,0xaf643000,0xaa1f2da8,0x2a1f8000,0x2f64ada8,
0x30003000,0x30003000,0x30003000,0x30003000,0xaf64b000,0xaa1fada8,0x2a1f8000,0x2f642da8,0x2da83000,0xada80000,0xada8b000,0x2da88000,
0xaa1fb000,0x2f642da8,0xaf640000,0x2a1fada8,0x00003000,0x8000b000,0x00003000,0x8000b000,0x2a1fb000,0xaf642da8,0x2f648000,0xaa1fada8,
0xada83000,0x2da88000,0x2da8b000,0xada80000,0x2f64b000,0x2a1fada8,0xaa1f0000,0xaf642da8,0x00000000,0x00000000,0x00000000,0x00000000,
0xaa1f0000,0xaf642da8,0xaf643000,0xaa1f2da8,0xada80000,0xada83000,0x2da80000,0x2da8b000,0xaf640000,0x2a1f2da8,0x2a1fb000,0xaf642da8,
0xb0000000,0x30000000,0xb0000000,0x30000000,0xaf640000,0x2a1fada8,0x2a1f3000,0xaf64ada8,0xada80000,0xada8b000,0x2da80000,0x2da83000,
0xaa1f0000,0xaf64ada8,0xaf64b000,0xaa1fada8,0x00000000,0x00000000,0x00000000,0x00000000,0x2a1f0000,0x2f64ada8,0x2f64b000,0x2a1fada8,
0xada80000,0xada83000,0x2da80000,0x2da8b000,0x2f640000,0xaa1fada8,0xaa1f3000,0x2f64ada8,0xb0000000,0x30000000,0xb0000000,0x30000000,
0x2f640000,0xaa1f2da8,0xaa1fb000,0x2f642da8,0xada80000,0xada8b000,0x2da80000,0x2da83000,0x2a1f0000,0x2f642da8,0x2f643000,0x2a1f2da8,
0xb0003000,0xb0003000,0xb0003000,0xb0003000,0xaf643000,0xaa1f2da8,0x2a1f0000,0x2f64ada8,0xada83000,0x2da80000,0x2da8b000,0xada88000,
0xaa1f3000,0x2f64ada8,0xaf648000,0x2a1f2da8,0x80003000,0x0000b000,0x80003000,0x0000b000,0x2a1f3000,0xaf64ada8,0x2f640000,0xaa1f2da8,
0x2da83000,0xada88000,0xada8b000,0x2da80000,0x2f643000,0x2a1f2da8,0xaa1f8000,0xaf64ada8,0xb0003000,0xb0003000,0xb0003000,0xb0003000,
0x2f64b000,0x2a1fada8,0xaa1f8000,0xaf642da8,0xada83000,0x2da80000,0x2da8b000,0xada88000,0x2a1fb000,0xaf642da8,0x2f640000,0xaa1fada8,
0x80003000,0x0000b000,0x80003000,0x0000b000,0xaa1fb000,0x2f642da8,0xaf648000,0x2a1fada8,0x2da83000,0xada88000,0xada8b000,0x2da80000,
0xaf64b000,0xaa1fada8,0x2a1f0000,0x2f642da8};

constexpr int kThreads = 384;
constexpr int kCtas = 128;

constexpr uint32_t SM_BASE = 1024;
constexpr uint32_t QKV_STAGE = 32768;
constexpr uint32_t SLOT = 16384;
constexpr uint32_t SM_KV = 2 * SLOT;
constexpr uint32_t SM_Q = 3 * SLOT;
constexpr uint32_t SM_SIG = 131072;
constexpr uint32_t SM_STG = 196608;
constexpr uint32_t SM_Y0 = SM_STG;
constexpr uint32_t SM_YT = SM_STG + 16384;
constexpr uint32_t SM_TW = SM_STG + 24576, SM_ONES = SM_TW + 2048, SM_F1 = SM_ONES + 2048, SM_F2 = SM_F1 + 4096;
constexpr uint32_t SM_BAR = SM_F2 + 2048;
constexpr uint32_t SM_SC = SM_BAR + 512;
constexpr uint32_t SM_TOTAL = 232448;
constexpr uint32_t A_SLOTS = 0xB2910, B_SLOTS = 0xA7654;

enum Bar { B_QKV_FULL = 0, B_QKV_EMPTY = 4, B_OUT_FULL = 8, B_OUT_EMPTY = 13, B_QKV_DONE = 18, B_CONV_DONE = 19, B_PREP_FULL = 20,
           B_PREP_EMPTY = 23, B_SIG_READY = 27, B_ZEROED = 28, B_KVP = 29, B_KV_READY = 30, B_O_WRITTEN = 31,
           B_OT_FREE = 33, B_SEG = 35, B_RDY0 = 39, B_RDY1 = 40, B_YIN = 42, B_Y_READY = 45, B_H_FULL = 46, B_FLAGS1 = 26, B_Q_FULL = 49, B_PAT_FREE = 41 };

constexpr int KV_SLICE = 640;
constexpr int XCH_BYTES = 11 * 4096;

struct Params {
  CUtensorMap x, w, wk, wo, outa, k, v, q;
  const __nv_bfloat16* shift_k;
  const __nv_bfloat16* ssm_k;
  const __nv_bfloat16* ssm_d;
  const __nv_bfloat16* q_ptr;
  __nv_bfloat16* out_ptr;
  const __nv_bfloat16* k_ptr;
  const __nv_bfloat16* v_ptr;
  const __nv_bfloat16* wo_ptr;
  int zero;
  uint8_t tile[64];
};

__device__ __align__(128) uint8_t g_xch[kCtas][XCH_BYTES];
__device__ __align__(128) unsigned g_oflag[128 * 32];
__device__ unsigned g_ready, g_epoch[kCtas];

#define TSTAMP(cond, i) do { } while (0)
#define GSTAMP(cond, i) do { } while (0)
#define LOOPSTAMP(id, cond, i) do { } while (0)

constexpr int kSpinLimit = 1 << 17;

DEVI void mbar_init(uint32_t a, uint32_t c) { asm volatile("mbarrier.init.shared::cta.b64 [%0], %1;" :: "r"(a), "r"(c) : "memory"); }
DEVI void mbar_expect(uint32_t a, uint32_t b) { asm volatile("mbarrier.arrive.expect_tx.shared::cta.b64 _, [%0], %1;" :: "r"(a), "r"(b) : "memory"); }
DEVI void mbar_arrive(uint32_t a) { asm volatile("mbarrier.arrive.shared::cta.b64 _, [%0];" :: "r"(a) : "memory"); }
DEVI void mbar_arrive_if(uint32_t a, bool pred) {
  asm volatile("{\n.reg .pred p;\nsetp.ne.b32 p, %1, 0;\n@p mbarrier.arrive.shared::cta.b64 _, [%0];\n}" :: "r"(a), "r"((int)pred) : "memory");
}
DEVI void mbar_wait(uint32_t a, uint32_t parity) {
  asm volatile("{\n.reg .pred p;\n.reg .u32 n;\nmov.u32 n, 0;\nW_LOOP:\n"
               "mbarrier.try_wait.parity.shared::cta.b64 p, [%0], %1;\n@p bra W_DONE;\n"
               "add.u32 n, n, 1;\nsetp.lt.u32 p, n, %2;\n@p bra W_LOOP;\nW_DONE:\n}"
               :: "r"(a), "r"(parity), "n"(kSpinLimit) : "memory");
}
DEVI void mbar_wait_long(uint32_t a, uint32_t parity) {
  asm volatile("{\n.reg .pred p;\n.reg .u32 n;\nmov.u32 n, 0;\nW_LOOP:\n"
               "mbarrier.try_wait.parity.shared::cta.b64 p, [%0], %1, %3;\n@p bra W_DONE;\n"
               "add.u32 n, n, 1;\nsetp.lt.u32 p, n, %2;\n@p bra W_LOOP;\nW_DONE:\n}"
               :: "r"(a), "r"(parity), "n"(kSpinLimit), "r"(4000) : "memory");
}
DEVI bool mbar_test(uint32_t a, uint32_t parity) {
  uint32_t ok;
  asm volatile("{\n.reg .pred p;\nmbarrier.test_wait.parity.shared::cta.b64 p, [%1], %2;\nselp.u32 %0, 1, 0, p;\n}" : "=r"(ok) : "r"(a), "r"(parity) : "memory");
  return ok;
}
DEVI bool elect() {
  uint32_t ok;
  asm volatile("{\n.reg .pred p;\nelect.sync _|p, 0xffffffff;\nselp.u32 %0, 1, 0, p;\n}" : "=r"(ok));
  return ok;
}
DEVI void flag_wait(const unsigned* p, unsigned target) {
  int n = 0; unsigned v;
  do {
    asm volatile("ld.acquire.gpu.global.u32 %0, [%1];" : "=r"(v) : "l"(p) : "memory");
  } while ((int)(v - target) < 0 && ++n < kSpinLimit);
}
DEVI void st_relaxed(void* p, uint32_t v) { asm volatile("st.relaxed.gpu.global.b32 [%0], %1;" :: "l"(p), "r"(v) : "memory"); }
DEVI uint32_t ld_relaxed(const void* p) { uint32_t v; asm volatile("ld.relaxed.gpu.global.b32 %0, [%1];" : "=r"(v) : "l"(p) : "memory"); return v; }
DEVI void ld_relaxed4(uint32_t* v, const void* p) {
  asm volatile("ld.relaxed.gpu.global.v4.b32 {%0,%1,%2,%3}, [%4];" : "=r"(v[0]), "=r"(v[1]), "=r"(v[2]), "=r"(v[3]) : "l"(p) : "memory");
}
template <int N> DEVI bool all_arrived(const uint32_t* v) {
  uint32_t m = v[0];
#pragma unroll
  for (int i = 1; i + 1 < N; i += 2) m = __vimax3_u32(m, v[i], v[i + 1]);
  if (N % 2 == 0) m = max(m, v[N - 1]);
  return __all_sync(0xffffffffu, m != 0xffffffffu);
}
DEVI void flag_add(unsigned* p) {
  asm volatile("fence.release.gpu;\nred.relaxed.gpu.global.add.u32 [%0], 1;" :: "l"(p) : "memory");
}
DEVI unsigned load_epoch(int cta) {
  unsigned v; asm volatile("ld.relaxed.gpu.global.u32 %0, [%1];" : "=r"(v) : "l"(&g_epoch[cta]) : "memory"); return v;
}
DEVI void fence_async_smem() { asm volatile("fence.proxy.async.shared::cta;" ::: "memory"); }
DEVI void bar_sync(int id, int n) { asm volatile("bar.sync %0, %1;" :: "r"(id), "r"(n) : "memory"); }
DEVI void cluster_sync() { asm volatile("barrier.cluster.arrive.relaxed.aligned;\nbarrier.cluster.wait.aligned;" ::: "memory"); }
DEVI void wg_fence() { asm volatile("wgmma.fence.sync.aligned;" ::: "memory"); }
DEVI void wg_commit() { asm volatile("wgmma.commit_group.sync.aligned;" ::: "memory"); }
template <int N> DEVI void wg_wait() { asm volatile("wgmma.wait_group.sync.aligned %0;" :: "n"(N) : "memory"); }
template <int N> DEVI void pin(uint32_t* r) {
#pragma unroll
  for (int i = 0; i < N; i++) asm volatile("" : "+r"(r[i]) :: "memory");
}
template <int N> DEVI void pin(float* r) {
#pragma unroll
  for (int i = 0; i < N; i++) asm volatile("" : "+f"(r[i]) :: "memory");
}

DEVI void sched_fence(int never) { asm volatile("{\n.reg .pred p;\nsetp.ne.b32 p, %0, 0;\nS_LOOP:\n@p st.volatile.shared.b32 [%0], %0;\n@p bra S_LOOP;\n}" :: "r"(never) : "memory"); }
DEVI void keep(uint32_t& x) { asm volatile("" : "+r"(x) :: "memory"); }
DEVI void keep(int& x) { asm volatile("" : "+r"(x) :: "memory"); }
template <class T> DEVI void keep(T*& x) { asm volatile("" : "+l"(x) :: "memory"); }

DEVI void tma2d(uint32_t dst, const CUtensorMap* m, int c0, int c1, uint32_t bar) {
  asm volatile("cp.async.bulk.tensor.2d.shared::cluster.global.mbarrier::complete_tx::bytes [%0], [%1, {%3, %4}], [%2];"
               :: "r"(dst), "l"(m), "r"(bar), "r"(c0), "r"(c1) : "memory");
}
DEVI void tma2d_mc(uint32_t dst, const CUtensorMap* m, int c0, int c1, uint32_t bar) {
  asm volatile("cp.async.bulk.tensor.2d.shared::cluster.global.mbarrier::complete_tx::bytes.multicast::cluster [%0], [%1, {%3, %4}], [%2], %5;"
               :: "r"(dst), "l"(m), "r"(bar), "r"(c0), "r"(c1), "h"((uint16_t)3) : "memory");
}
DEVI void tma3d(uint32_t dst, const CUtensorMap* m, int c0, int c1, int c2, uint32_t bar) {
  asm volatile("cp.async.bulk.tensor.3d.shared::cluster.global.mbarrier::complete_tx::bytes [%0], [%1, {%3, %4, %5}], [%2];"
               :: "r"(dst), "l"(m), "r"(bar), "r"(c0), "r"(c1), "r"(c2) : "memory");
}
DEVI void tma3d_mc(uint32_t dst, const CUtensorMap* m, int c0, int c1, int c2, uint32_t bar) {
  asm volatile("cp.async.bulk.tensor.3d.shared::cluster.global.mbarrier::complete_tx::bytes.multicast::cluster [%0], [%1, {%3, %4, %5}], [%2], %6;"
               :: "r"(dst), "l"(m), "r"(bar), "r"(c0), "r"(c1), "r"(c2), "h"((uint16_t)3) : "memory");
}
DEVI void tma2d_store(const CUtensorMap* m, uint32_t src, int c0, int c1) {
  asm volatile("cp.async.bulk.tensor.2d.global.shared::cta.bulk_group [%0, {%2, %3}], [%1];" :: "l"(m), "r"(src), "r"(c0), "r"(c1) : "memory");
}
DEVI void bulk_load(uint32_t dst, const void* src, uint32_t bytes, uint32_t bar) {
  asm volatile("cp.async.bulk.shared::cluster.global.mbarrier::complete_tx::bytes [%0], [%1], %2, [%3];" :: "r"(dst), "l"(src), "r"(bytes), "r"(bar) : "memory");
}
DEVI void bulk_store(void* dst, uint32_t src, uint32_t bytes) {
  asm volatile("cp.async.bulk.global.shared::cta.bulk_group [%0], [%1], %2;" :: "l"(dst), "r"(src), "r"(bytes) : "memory");
}
DEVI uint32_t peer_addr(uint32_t a, int rank) { uint32_t r; asm("mapa.shared::cluster.u32 %0, %1, %2;" : "=r"(r) : "r"(a), "r"(rank)); return r; }
DEVI void bulk_to_peer(uint32_t dst, uint32_t src, uint32_t bytes, uint32_t bar, int rank) {
  asm volatile("cp.async.bulk.shared::cluster.shared::cta.mbarrier::complete_tx::bytes [%0], [%1], %2, [%3];"
               :: "r"(peer_addr(dst, rank)), "r"(src), "r"(bytes), "r"(peer_addr(bar, rank)) : "memory");
}
DEVI void l2_prefetch(const void* p, uint32_t bytes) {
  asm volatile("cp.async.bulk.prefetch.L2.global [%0], %1;" :: "l"(p), "r"(bytes) : "memory");
}
DEVI void l2_prefetch2d(const CUtensorMap* m, int c0, int c1) {
  asm volatile("cp.async.bulk.prefetch.tensor.2d.L2.global [%0, {%1, %2}];" :: "l"(m), "r"(c0), "r"(c1) : "memory");
}
DEVI void l2_prefetch3d(const CUtensorMap* m, int c0, int c1, int c2) {
  asm volatile("cp.async.bulk.prefetch.tensor.3d.L2.global [%0, {%1, %2, %3}];" :: "l"(m), "r"(c0), "r"(c1), "r"(c2) : "memory");
}
DEVI void delay(int cycles) { const long long t = clock64(); while (clock64() - t < cycles) { } }
DEVI void bulk_commit() { asm volatile("cp.async.bulk.commit_group;" ::: "memory"); }
DEVI void bulk_wait_all() { asm volatile("cp.async.bulk.wait_group 0;" ::: "memory"); }
DEVI void bulk_wait_read() { asm volatile("cp.async.bulk.wait_group.read 0;" ::: "memory"); }
DEVI void prefetch_map(const CUtensorMap* m) { asm volatile("prefetch.tensormap [%0];" :: "l"(m) : "memory"); }
DEVI void arrive_both(uint32_t bar, int lane, bool pred = true) {
  asm volatile("{\n.reg .pred p;\n.reg .b32 r;\nsetp.ne.b32 p, %2, 0;\nmapa.shared::cluster.u32 r, %0, %1;\n@p mbarrier.arrive.shared::cluster.b64 _, [r];\n}"
               :: "r"(bar), "r"(lane & 1), "r"((int)(pred && lane < 2)) : "memory");
}

DEVI uint64_t make_desc(uint32_t off, uint32_t lbo, uint32_t sbo, uint32_t mode) {
  const uint32_t lo = (off >> 4) + (SM_BASE >> 4) + ((lbo >> 4) << 16), hi = (sbo >> 4) | (mode << 30);
  return ((uint64_t)hi << 32) | lo;
}
DEVI uint32_t pack_bf16(float lo, float hi) { uint32_t r; asm("cvt.rn.bf16x2.f32 %0, %1, %2;" : "=r"(r) : "f"(hi), "f"(lo)); return r; }
DEVI uint32_t pack_f16(float lo, float hi) { uint32_t r; asm("cvt.rn.f16x2.f32 %0, %1, %2;" : "=r"(r) : "f"(hi), "f"(lo)); return r; }
DEVI void stsm4(uint32_t addr, uint32_t r0, uint32_t r1, uint32_t r2, uint32_t r3) {
  asm volatile("stmatrix.sync.aligned.m8n8.x4.shared.b16 [%0], {%1,%2,%3,%4};" :: "r"(addr), "r"(r0), "r"(r1), "r"(r2), "r"(r3) : "memory");
}
DEVI void stsm2(uint32_t addr, uint32_t r0, uint32_t r1) {
  asm volatile("stmatrix.sync.aligned.m8n8.x2.shared.b16 [%0], {%1,%2};" :: "r"(addr), "r"(r0), "r"(r1) : "memory");
}
DEVI void stsm4_t(uint32_t addr, uint32_t r0, uint32_t r1, uint32_t r2, uint32_t r3) {
  asm volatile("stmatrix.sync.aligned.m8n8.x4.trans.shared.b16 [%0], {%1,%2,%3,%4};" :: "r"(addr), "r"(r0), "r"(r1), "r"(r2), "r"(r3) : "memory");
}
DEVI void ldsm4(uint32_t* r, uint32_t addr) {
  asm volatile("ldmatrix.sync.aligned.m8n8.x4.shared.b16 {%0,%1,%2,%3}, [%4];" : "=r"(r[0]), "=r"(r[1]), "=r"(r[2]), "=r"(r[3]) : "r"(addr) : "memory");
}
DEVI void ldsm4_t(uint32_t* r, uint32_t addr) {
  asm volatile("ldmatrix.sync.aligned.m8n8.x4.trans.shared.b16 {%0,%1,%2,%3}, [%4];" : "=r"(r[0]), "=r"(r[1]), "=r"(r[2]), "=r"(r[3]) : "r"(addr) : "memory");
}
DEVI uint32_t lds32(uint32_t a) { uint32_t v; asm volatile("ld.shared.b32 %0, [%1];" : "=r"(v) : "r"(a) : "memory"); return v; }
DEVI uint4 lds128(uint32_t a) {
  uint4 v; asm volatile("ld.shared.v4.b32 {%0,%1,%2,%3}, [%4];" : "=r"(v.x), "=r"(v.y), "=r"(v.z), "=r"(v.w) : "r"(a) : "memory"); return v;
}
DEVI uint32_t bmul2(uint32_t a, uint32_t b) { uint32_t r; asm("mul.rn.bf16x2 %0, %1, %2;" : "=r"(r) : "r"(a), "r"(b)); return r; }
DEVI uint32_t bfma2(uint32_t a, uint32_t b, uint32_t c) { uint32_t r; asm("fma.rn.bf16x2 %0, %1, %2, %3;" : "=r"(r) : "r"(a), "r"(b), "r"(c)); return r; }
DEVI float bf_lo(uint32_t w) { return __uint_as_float(w << 16); }
DEVI float bf_hi(uint32_t w) { return __uint_as_float(w & 0xffff0000u); }
DEVI uint32_t elu1(float t0, float t1) {
  float e0, e1;
  asm("ex2.approx.ftz.f32 %0, %1;" : "=f"(e0) : "f"(t0 * 1.4426950408889634f));
  asm("ex2.approx.ftz.f32 %0, %1;" : "=f"(e1) : "f"(t1 * 1.4426950408889634f));
  uint32_t r;
  asm("{\n.reg .b32 a, b;\nmin.bf16x2 a, %1, %4;\ncvt.rn.relu.bf16x2.f32 b, %3, %2;\nadd.rn.bf16x2 %0, a, b;\n}"
      : "=r"(r) : "r"(pack_bf16(e0, e1)), "f"(t0), "f"(t1), "r"(0x3f803f80u));
  return r;
}
DEVI uint32_t add_eps(uint32_t x) { uint32_t r; asm("add.rn.bf16x2 %0, %1, %2;" : "=r"(r) : "r"(x), "r"(0x35863586u)); return r; }

DEVI uint32_t hmul(uint32_t a, uint32_t b) { uint32_t r; asm("mul.rn.f16x2 %0, %1, %2;" : "=r"(r) : "r"(a), "r"(b)); return r; }
DEVI uint32_t hfma(uint32_t a, uint32_t b, uint32_t c) { uint32_t r; asm("fma.rn.f16x2 %0, %1, %2, %3;" : "=r"(r) : "r"(a), "r"(b), "r"(c)); return r; }
DEVI uint32_t hneg(uint32_t a) { uint32_t r; asm("neg.f16x2 %0, %1;" : "=r"(r) : "r"(a)); return r; }
DEVI uint32_t hadd(uint32_t a, uint32_t b) { uint32_t r; asm("add.rn.f16x2 %0, %1, %2;" : "=r"(r) : "r"(a), "r"(b)); return r; }
DEVI uint32_t hsub(uint32_t a, uint32_t b) { uint32_t r; asm("sub.rn.f16x2 %0, %1, %2;" : "=r"(r) : "r"(a), "r"(b)); return r; }
struct Cx { uint32_t re, im; };
DEVI Cx cmul(Cx a, Cx b) { return {hfma(a.re, b.re, hneg(hmul(a.im, b.im))), hfma(a.re, b.im, hmul(a.im, b.re))}; }
DEVI Cx cfma(Cx a, Cx b, Cx c) { return {hfma(a.re, b.re, hfma(hneg(a.im), b.im, c.re)), hfma(a.re, b.im, hfma(a.im, b.re, c.im))}; }
DEVI Cx rot(Cx a, Cx t) {
  const uint32_t x = hfma(hneg(t.re), a.im, a.re), y = hfma(t.im, x, a.im);
  return {hfma(hneg(t.re), y, x), y};
}
struct Fft {
  uint32_t fa[8];
  Cx tw[2];
  uint32_t vst;
  DEVI void stage1(uint32_t* d1, uint32_t slot) const {
    wg_fence();
    fft1_init(d1, fa[0], fa[1], fa[2], fa[3], make_desc(slot, 4096, 1024, 1));
    fft1_acc(d1, fa[4], fa[5], fa[6], fa[7], make_desc(slot + 2048, 4096, 1024, 1));
    wg_commit();
  }
  DEVI void stage2(uint32_t* d, const Cx* t) const {
    wg_fence();
    fft2_init(d, t[0].re, t[1].re, t[2].re, t[3].re, make_desc(SM_F2, 128, 512, 0));
    fft2_acc(d, t[0].im, t[1].im, t[2].im, t[3].im, make_desc(SM_F2 + 256, 128, 512, 0));
    wg_commit();
  }
  template <int PR> DEVI void fwd(const uint32_t* d1, uint32_t* d2) const {
    Cx t[4];
#pragma unroll
    for (int e = 0; e < 4; e++) {
      const int j = 8 * (PR & 1) + 4 * (e >> 1) + 2 * (PR >> 1) + (e & 1);
      t[e] = rot({d1[2 * j], d1[2 * j + 1]}, tw[e >> 1]);
    }
    stage2(d2 + 8 * PR, t);
  }
  static DEVI Cx U(const uint32_t* d2, int p, int hi) { return {d2[16 * (p >> 1) + 2 * hi + (p & 1)], d2[16 * (p >> 1) + 4 + 2 * hi + (p & 1)]}; }
  static DEVI Cx H(const uint32_t* d2, int p, int hi) { return U(d2 + 8, p, hi); }
  DEVI void prod01(const uint32_t* d2, Cx* p1, uint32_t* d3) const {
    Cx z[4];
#pragma unroll
    for (int hi = 0; hi < 2; hi++) {
      const Cx p0 = cmul(H(d2, 0, hi), U(d2, 0, hi));
      p1[hi] = cfma(H(d2, 1, hi), U(d2, 0, hi), cmul(H(d2, 0, hi), U(d2, 1, hi)));
      z[2 * hi] = {p0.im, p0.re};
      z[2 * hi + 1] = {hsub(p1[hi].im, p0.re), hadd(p1[hi].re, p0.im)};
    }
    stage2(d3, z);
  }
  DEVI void prod23(const uint32_t* d2, const Cx* p1, uint32_t* d3) const {
    Cx z[4];
#pragma unroll
    for (int hi = 0; hi < 2; hi++) {
      const Cx p2 = cfma(H(d2, 2, hi), U(d2, 0, hi), cfma(H(d2, 0, hi), U(d2, 2, hi), cmul(H(d2, 1, hi), U(d2, 1, hi))));
      const Cx z3 = cfma(H(d2, 3, hi), U(d2, 0, hi), cfma(H(d2, 2, hi), U(d2, 1, hi),
                    cfma(H(d2, 1, hi), U(d2, 2, hi), cfma(H(d2, 0, hi), U(d2, 3, hi), {p2.im, hneg(p2.re)}))));
      z[2 * hi] = {hsub(p2.im, p1[hi].re), hadd(p2.re, p1[hi].im)};
      z[2 * hi + 1] = {z3.im, z3.re};
    }
    stage2(d3 + 8, z);
  }
  template <int PB> DEVI void inv(const uint32_t* d3, uint32_t slot) const {
    Cx v[4];
#pragma unroll
    for (int e = 0; e < 4; e++) {
      const int r = 8 * PB + 2 * (e & 1) + (e >> 1);
      v[e] = rot({d3[r], d3[r + 4]}, tw[e & 1]);
    }
    stsm4(slot + (vst ^ (PB * 64)), v[0].im, v[1].im, v[2].im, v[3].im);
    stsm4(slot + 1024 + (vst ^ (PB * 64)), v[0].re, v[1].re, v[2].re, v[3].re);
  }
  DEVI void last(float* dy, uint32_t slot, int wg) const {
    fence_async_smem();
    bar_sync(2 + wg, 128);
    wg_fence();
    fft3_init(dy, make_desc(slot, 4096, 1024, 1), make_desc(SM_F1, 128, 1024, 0));
#pragma unroll
    for (int ks = 1; ks < 4; ks++) fft3_acc(dy, make_desc(slot + ks * 2048, 4096, 1024, 1), make_desc(SM_F1 + ks * 256, 128, 1024, 0));
    wg_commit();
  }
  static DEVI void store_y(const float* dy, uint32_t a) {
    stsm4_t(a, pack_bf16(dy[0], dy[1]), pack_bf16(dy[2], dy[3]), pack_bf16(dy[4], dy[5]), pack_bf16(dy[6], dy[7]));
    stsm4_t(a + 512, pack_bf16(dy[8], dy[9]), pack_bf16(dy[10], dy[11]), pack_bf16(dy[12], dy[13]), pack_bf16(dy[14], dy[15]));
  }
};
DEVI uint32_t normalize(uint32_t* x, uint32_t dst) {
  uint32_t m = x[0];
#pragma unroll
  for (int i = 1; i < 32; i++) asm("max.xorsign.abs.bf16x2 %0, %0, %1;" : "+r"(m) : "r"(x[i]));
  const uint32_t e = min(__reduce_max_sync(0xffffffffu, max(m & 0x7fffu, (m >> 16) & 0x7fffu)) >> 7, 252u);
  if (e > 140) {
#pragma unroll
    for (int i = 0; i < 32; i++) x[i] = bmul2(x[i], 15u * 0x00800080u);
  }
  const uint32_t sc = (e > 140 ? 253u - e : 141u - e) * 0x00800080u;
#pragma unroll
  for (int i = 0; i < 8; i++) {
    uint32_t y[4];
#pragma unroll
    for (int n = 0; n < 4; n++) {
      const uint32_t w = bmul2(x[4 * i + n], sc);
      y[n] = (w & 0x7fff7fffu) * 7u + w;
    }
    stsm4((dst ^ ((i >> 1) << 4)) + (i & 1) * 2048, y[0], y[1], y[2], y[3]);
  }
  return e;
}
#define CREGS 224
#define TAIL 3
#define DBG 0
#define XPF 3
#define XPFD 0
#define EARLY 1
#define KVPF 0
#define PSTART 5
#define PDELAY 1500
#define MAP 1
#define MC 7
#define HSTART 4
#define OPACE 0
#define POSTW 1
#define PPACE 300
#define QLATE 0
#define ONEF 1
#define GATE_STAGES 0x7bc
#define PH1 4
#define PH0 2
#define PH3 2
#define RPACE 300
#define C1DELAY 0
#define FDELAY 200
#define NE 1
#define NB0 3
#define EREL 1
#define HE 1
#define KBAL 1
#define KVFIRST 0
#define GB 2
#define CGMAP 1
#define PF0 24

__global__ void __cluster_dims__(2, 1, 1) __launch_bounds__(kThreads, 1)
fused_kernel(const __grid_constant__ Params P) {
  extern __shared__ __align__(1024) uint8_t smem[];
  if (threadIdx.x == 0) { prefetch_map(&P.x); prefetch_map(&P.w); if (KBAL) prefetch_map(&P.wk); prefetch_map(blockIdx.x & 1 ? &P.v : &P.k); }
  const uint32_t sb = __shfl_sync(0xffffffffu, (uint32_t)__cvta_generic_to_shared(smem), 0);
  if ((sb & 0xffffff) != SM_BASE) __trap();
  const int tid = threadIdx.x, lane = tid & 31;
  const int warp = __shfl_sync(0xffffffffu, tid >> 5, 0);
  const int rho = blockIdx.x & 1, tl = P.tile[blockIdx.x >> 1], cl = CGMAP ? tl : blockIdx.x >> 1, cta = 2 * cl + rho;
  const int j = tl & 7, rp = tl >> 3;
  const int r = rp * 2 + rho;
  auto bar = [&](int i) { return sb + SM_BAR + 8u * i; };
  TSTAMP(tid == 0, 0); GSTAMP(tid == 0, 30);

  if (warp == 8 && elect()) {
    for (int i = 0; i < 4; i++) mbar_init(bar(B_QKV_FULL + i), 1);
    asm volatile("fence.mbarrier_init.release.cluster;" ::: "memory");
#pragma unroll
    for (int it = 0; it < NE; it++) {
      const uint32_t st = sb + it * QKV_STAGE, fb = bar(B_QKV_FULL + it);
      mbar_expect(fb, QKV_STAGE);
      tma2d(st, &P.x, 32 * it, 128 * r, fb);
      tma3d(st + 24576, &P.w, 0, 32 * it, 16 + 2 * j, fb);
      tma3d(st + 8192, &P.w, 0, 32 * it, 2 * j, fb);
      tma3d(st + 16384, &P.w, 0, 32 * it, 32 + 2 * j, fb);
    }
  }
  if (tid == 0) {
    for (int i = 0; i < 4; i++) mbar_init(bar(B_QKV_EMPTY + i), 16);
    for (int i = 0; i < 5; i++) { mbar_init(bar(B_OUT_FULL + i), 1); mbar_init(bar(B_OUT_EMPTY + i), 16); }
    mbar_init(bar(B_QKV_DONE), 16); mbar_init(bar(B_CONV_DONE), 16);
    for (int i = 0; i < 3; i++) { mbar_init(bar(B_PREP_FULL + i), 1); mbar_init(bar(B_PREP_EMPTY + i), 2); mbar_init(bar(B_H_FULL + i), 1); }
    mbar_init(bar(B_SIG_READY), 4); mbar_init(bar(B_ZEROED), 1);
    mbar_init(bar(B_KVP), 8); mbar_init(bar(B_KV_READY), 4);
    for (int i = 0; i < 2; i++) {
      mbar_init(bar(B_O_WRITTEN + i), 8); mbar_init(bar(B_OT_FREE + i), 1);
      mbar_init(bar(B_YIN + i), 1); mbar_expect(bar(B_YIN + i), 8192);
    }
    for (int i = 0; i < 4; i++) { mbar_init(bar(B_SEG + i), 4); mbar_init(bar(B_Q_FULL + i), 1); }
    mbar_init(bar(B_Y_READY), 1); mbar_init(bar(B_FLAGS1), 1);
    mbar_init(bar(B_RDY0), 1); mbar_expect(bar(B_RDY0), 16);
    mbar_init(bar(B_RDY1), 1); mbar_init(bar(B_PAT_FREE), 1);
    asm volatile("fence.mbarrier_init.release.cluster;" ::: "memory");
  }
  LOOPSTAMP(3, tid == 256, 13); LOOPSTAMP(3, tid == 0, 14);
  __syncwarp();
  cluster_sync();
  LOOPSTAMP(3, tid == 256, 15);

  if (warp < 8) {
    asm volatile("setmaxnreg.inc.sync.aligned.u32 %0;" :: "n"(CREGS));
    const int wg = warp >> 2, wq = warp & 3;
    const int never = P.zero;
    const uint32_t orow = wq * 2048 + (lane & 15) * 128, ox = ((lane >> 4) ^ (lane & 7)) << 4;
    float aq[64];
    {
      float ak[64], avq[128];
      auto k_step = [&](uint32_t st, int kk, int acc) {
        mma_tn(ak, make_desc(st + 24576 + wg * 4096 + kk * 2048, 4096, 1024, 1), make_desc(st + kk * 32, 16, 512, 2), acc);
      };
      auto vq_step = [&](uint32_t st, int kk, int acc) {
        mma_nt256(avq, make_desc(st + wg * 4096 + kk * 32, 16, 512, 2), make_desc(st + 8192 + kk * 2048, 4096, 1024, 1), acc);
      };
#pragma unroll 1
      for (int it = 0; it < 29; ++it) {
        mbar_wait(bar(B_QKV_FULL + (it & 3)), (it >> 2) & 1);
        TSTAMP(tid == 0 && it == 0, 1); LOOPSTAMP(1, tid == 0 && it < 27, 1 + it); LOOPSTAMP(3, tid == 0 && it < 12, 1 + it);
        const uint32_t st = (it & 3) * QKV_STAGE;
        wg_fence();
        k_step(st, 0, it != 0);
        wg_commit();
        wg_wait<1>();
        arrive_both(bar(B_QKV_EMPTY + ((it - 1) & 3)), lane, it > 0);
        wg_fence();
        vq_step(st, 0, it != 0);
        k_step(st, 1, 1);
        vq_step(st, 1, 1);
        wg_commit();
      }
#pragma unroll
      for (int s = 1; s < 4; ++s) {
        mbar_wait(bar(B_QKV_FULL + s), 1);
        wg_fence();
#pragma unroll
        for (int kk = 0; kk < 2; kk++) k_step(s * QKV_STAGE, kk, 1);
      }
      wg_commit();
      uint32_t pk[32];
      auto phi_k = [&](int i0, int i1) {
#pragma unroll
        for (int i = i0; i < i1; i++) { pk[i] = elu1(ak[2 * i], ak[2 * i + 1]); asm volatile("" : "+r"(pk[i]) :: "memory"); }
        sched_fence(never);
      };
#pragma unroll
      for (int n = 0; n < 6; n++) {
        wg_fence();
        vq_step((1 + (n >> 1)) * QKV_STAGE, n & 1, 1);
        wg_commit();
        if (n == 0) {
          wg_wait<1>();
          pin<64>(ak);
          TSTAMP(tid == 0, 2);
          bar_sync(1, 256);
        }
        phi_k(n ? PH0 + PH1 * (n - 1) : 0, PH0 + PH1 * n);
      }
      wg_wait<0>();
      pin<128>(avq);
      arrive_both(bar(B_QKV_DONE), lane);
      TSTAMP(tid == 0, 3);
#pragma unroll
      for (int t = 0; t < 8; t++) {
        const float* b = avq + 64 + 8 * t;
        stsm4(sb + (t >> 2) * SLOT + wg * 8192 + orow + (ox ^ ((t & 3) << 5)), pack_bf16(b[0], b[1]), pack_bf16(b[2], b[3]), pack_bf16(b[4], b[5]), pack_bf16(b[6], b[7]));
      }
#pragma unroll
      for (int i = 0; i < 64; i++) aq[i] = avq[i];
      fence_async_smem();
      mbar_wait(bar(B_SIG_READY), 0);
      bar_sync(1, 256);
      float dkv[36];
      constexpr int PHD = PH0 + 5 * PH1;
#pragma unroll
      for (int ks = 0; ks < 8; ks++) {
        const uint32_t va = wg * SLOT + ks * 2048;
        const uint64_t db = make_desc(va, SM_ONES - va, 1024, 1);
        uint32_t a[4];
        pin<4>(pk + 4 * ks);
#pragma unroll
        for (int i = 0; i < 4; i++) a[i] = add_eps(pk[4 * ks + i]);
        wg_fence();
        if (ks == 0) mma_kv_init(dkv, a[0], a[1], a[2], a[3], db);
        else mma_kv_acc(dkv, a[0], a[1], a[2], a[3], db);
        wg_commit();
        if (PHD + PH3 * ks < 32) phi_k(PHD + PH3 * ks, PHD + PH3 * ks + PH3 < 32 ? PHD + PH3 * ks + PH3 : 32);
      }
      mbar_wait(bar(B_ZEROED), 0);
      wg_wait<0>();
      pin<36>(dkv);
      TSTAMP(tid == 0, 4);
      uint8_t* box = g_xch[warp * 16 + j] + 2 * SLOT + r * KV_SLICE;
      auto put = [&](const float* d) {
#pragma unroll
        for (int m = 0; m < 2; m++)
          asm volatile("st.relaxed.gpu.global.v4.b32 [%0], {%1,%2,%3,%4};" :: "l"(box + m * 8 * XCH_BYTES + lane * 16), "r"(pack_bf16(d[2 * m], d[2 * m + 1])),
                       "r"(pack_bf16(d[2 * m + 4], d[2 * m + 5])), "r"(pack_bf16(d[2 * m + 8], d[2 * m + 9])), "r"(pack_bf16(d[2 * m + 12], d[2 * m + 13])) : "memory");
      };
      if (wq < 2) put(dkv); else put(dkv + 16);
      if ((lane & 2) == 0) st_relaxed(box + (lane & 1) * 8 * XCH_BYTES + 512 + (lane & 28), __float_as_uint(lane & 1 ? dkv[34] : dkv[32]));
      __syncwarp();
      mbar_arrive_if(bar(B_KVP), lane == 0);
      TSTAMP(tid == 0, 5);
    }

    Fft F;
    ldsm4_t(F.fa, sb + SM_F1 + (lane >> 4) * 1024 + wq * 256 + (lane & 15) * 16);
    ldsm4_t(F.fa + 4, sb + SM_F1 + 2048 + (lane >> 4) * 1024 + wq * 256 + (lane & 15) * 16);
    {
      const uint4 t = lds128(sb + SM_TW + (tid & 127) * 16);
      F.tw[0] = {t.x, t.y}; F.tw[1] = {t.z, t.w};
    }
    F.vst = sb + (16 * wq + (lane & 7)) * 128 + (((lane >> 3) ^ (lane & 7)) << 4);
#pragma unroll 1
    for (int seg = 0; seg < 2; ++seg) {
      if (seg != wg) {
        pin<64>(aq);
#pragma unroll
        for (int i = 0; i < 32; i++) aq[i] = __uint_as_float(add_eps(elu1(aq[2 * i], aq[2 * i + 1])));
        TSTAMP((tid & 127) == 0, 6);
      }
      if (seg) {
        float dn[4][20];
        mbar_wait(bar(B_KV_READY), 0);
        TSTAMP(tid == 0, 8);
        wg_fence();
#pragma unroll
        for (int h = 0; h < 4; h++) {
          const uint64_t db = make_desc(SM_KV + h * 2560, 640, 128, 0);
          const float* a = aq + 8 * h;
          mma_o_init(dn[h], __float_as_uint(a[0]), __float_as_uint(a[1]), __float_as_uint(a[2]), __float_as_uint(a[3]), db);
          mma_o_acc(dn[h], __float_as_uint(a[4]), __float_as_uint(a[5]), __float_as_uint(a[6]), __float_as_uint(a[7]), db + (1280 >> 4));
          wg_commit();
        }
        auto head_store = [&](int h) {
          pin<20>(dn[h]);
          const float i0 = __fdividef(1.f, dn[h][16] + 1e-6f), i1 = __fdividef(1.f, dn[h][18] + 1e-6f);
#pragma unroll
          for (int hf = 0; hf < 2; hf++) {
            const float* a = dn[h] + 8 * hf;
            stsm4(sb + (h >> 1) * SLOT + wg * 8192 + orow + (ox ^ (((h & 1) * 2 + hf) << 5)),
                  pack_bf16(a[0] * i0, a[1] * i0), pack_bf16(a[2] * i1, a[3] * i1), pack_bf16(a[4] * i0, a[5] * i0), pack_bf16(a[6] * i1, a[7] * i1));
          }
          if (h & 1) { fence_async_smem(); __syncwarp(); mbar_arrive_if(bar(B_O_WRITTEN + (h >> 1)), lane == 0); }
        };
        wg_wait<3>(); head_store(0);
        wg_wait<2>(); head_store(1);
        wg_wait<1>(); head_store(2);
        wg_wait<0>(); head_store(3);
        TSTAMP(tid == 0, 9);
      }
      const int c = 4 * seg + wg;
      const uint32_t sa = SM_SIG + c * 8192, sc = sa + SLOT;
      const uint32_t ya = sb + ((wq >> 1) == rho ? (seg ? SM_SIG : SM_Y0) + wg * 8192 : SM_YT + wg * 4096) + (wq & 1) * 1024 + ((lane ^ c ^ (2 * rho)) << 4);
      uint32_t a1[32], b1[32], a2[32], b2[32], a3[16], b3[16];
      float ay[16], by[16];
      Cx pa[2], pb[2];
      F.stage1(a1, sa);
      wg_wait<0>(); pin<32>(a1);
      bar_sync(2 + wg, 128);
      F.fwd<0>(a1, a2); F.fwd<1>(a1, a2); F.fwd<2>(a1, a2); F.fwd<3>(a1, a2);
      F.stage1(b1, sc);
      wg_wait<3>(); pin<16>(a2);
      F.prod01(a2, pa, a3);
      wg_wait<2>(); pin<16>(a2 + 16);
      F.prod23(a2, pa, a3);
      wg_wait<1>(); pin<32>(b1); pin<8>(a3);
      F.inv<0>(a3, sa);
      F.fwd<0>(b1, b2);
      wg_wait<1>(); pin<8>(a3 + 8);
      F.inv<1>(a3, sa);
      F.fwd<1>(b1, b2); F.fwd<2>(b1, b2); F.fwd<3>(b1, b2);
      F.last(ay, sa, wg);
      wg_wait<3>(); pin<16>(b2);
      F.prod01(b2, pb, b3);
      wg_wait<2>(); pin<16>(b2 + 16);
      F.prod23(b2, pb, b3);
      wg_wait<1>(); pin<8>(b3); pin<16>(ay);
      F.inv<0>(b3, sc);
      wg_wait<0>(); pin<8>(b3 + 8);
      F.inv<1>(b3, sc);
      F.last(by, sc, wg);
      mbar_wait(bar(B_RDY1), seg ^ 1);
      Fft::store_y(ay, ya);
      wg_wait<0>(); pin<16>(by);
      Fft::store_y(by, (ya ^ 32) + 2048);
      fence_async_smem();
      __syncwarp();
      mbar_arrive_if(bar(B_SEG + 2 * seg + wg), lane == 0);
      TSTAMP(tid == 0 && seg == 0, 7); TSTAMP(tid == 128 && seg == 0, 10); TSTAMP(tid == 0 && seg == 1, 11); TSTAMP(tid == 128 && seg == 1, 12);
    }
    arrive_both(bar(B_CONV_DONE), lane);

    float acc[64];
    auto stage_mma = [&](int s, int kk, int accumulate) {
      mma_nt(acc, make_desc(((A_SLOTS >> (4 * s)) & 15) * SLOT + wg * 8192 + kk * 32, 16, 1024, 1),
             make_desc(((B_SLOTS >> (4 * s)) & 15) * SLOT + kk * 2048, 8192, 1024, 1), accumulate);
    };
    {
      int s = 0, sprev = 0;
      uint32_t ph = 0;
#pragma unroll 1
      for (int ks = 0; ks < 12; ++ks) {
        mbar_wait(bar(B_OUT_FULL + s), ph);
        LOOPSTAMP(2, tid == 0, 1 + ks);
        TSTAMP(tid == 0 && ks == 2, 13); TSTAMP(tid == 0 && ks == 9, 14);
        wg_fence();
        stage_mma(s, 0, ks != 0);
        wg_commit();
        wg_wait<1>();
        arrive_both(bar(B_OUT_EMPTY + sprev), lane, ks > 0);
        wg_fence();
#pragma unroll
        for (int kk = 1; kk < 4; kk++) stage_mma(s, kk, 1);
        wg_commit();
        sprev = s;
        if (++s == 5) { s = 0; ph ^= 1; }
      }
    }
#pragma unroll
    for (int ks = 12; ks < 16; ++ks) {
      if (ks == 16 - TAIL) asm volatile("{\n.reg .pred p;\nsetp.ne.b32 p, %0, 0;\n@p bar.sync 1, 256;\n}" :: "r"(wg) : "memory");
      mbar_wait(bar(B_OUT_FULL + ks % 5), (ks / 5) & 1);
      wg_fence();
#pragma unroll
      for (int kk = 0; kk < 4; kk++) stage_mma(ks % 5, kk, 1);
      wg_commit();
    }
    asm volatile("{\n.reg .pred p;\nsetp.eq.b32 p, %0, 0;\n@p bar.arrive 1, 256;\n}" :: "r"(wg) : "memory");
    wg_wait<0>(); pin<64>(acc);
    TSTAMP(tid == 0, 15); TSTAMP(tid == 128, 16);
    if (__any_sync(0xffffffffu, acc[0] != acc[0] || acc[2] != acc[2] || (DBG & 256))) {
#pragma unroll
      for (int i = 0; i < 64; i++) acc[i] = 0.f;
      const int row = warp * 16 + (lane >> 2);
#pragma unroll 1
      for (int k = 0; k < 1024; k += 2) {
        const uint8_t* src = g_xch[r * 8 + (k >> 7)] + ((k >> 6) & 1) * SLOT + row * 128 + ((((k >> 3) ^ row) & 7) << 4) + (k & 7) * 2;
        uint32_t a[2];
        int n = 0;
        do { a[0] = ld_relaxed(src); a[1] = ld_relaxed(src + 1024); } while (!all_arrived<2>(a) && ++n < kSpinLimit);
#pragma unroll 1
        for (int e = 0; e < 2; e++) {
          const float a0 = e ? bf_hi(a[0]) : bf_lo(a[0]), a1 = e ? bf_hi(a[1]) : bf_lo(a[1]);
          const uint32_t* wrow = reinterpret_cast<const uint32_t*>(P.wo_ptr + (k + e) * 1024 + 128 * j) + (lane & 3);
#pragma unroll
          for (int i = 0; i < 16; i++) {
            const uint32_t w = __ldg(wrow + 4 * i);
            acc[4 * i] += a0 * bf_lo(w); acc[4 * i + 1] += a0 * bf_hi(w);
            acc[4 * i + 2] += a1 * bf_lo(w); acc[4 * i + 3] += a1 * bf_hi(w);
          }
        }
      }
    }
#pragma unroll
    for (int hf = 0; hf < 2; hf++) {
      const uint32_t dst = sb + (1 + 8 * hf) * SLOT + wg * 8192;
#pragma unroll
      for (int t = 0; t < 4; t++) {
        const float* a = acc + 32 * hf + 8 * t;
        stsm4(dst + orow + (ox ^ (t << 5)), pack_bf16(a[0], a[1]), pack_bf16(a[2], a[3]), pack_bf16(a[4], a[5]), pack_bf16(a[6], a[7]));
      }
      fence_async_smem();
      __syncwarp();
      if (elect()) { tma2d_store(&P.outa, dst + wq * 2048, 128 * j + 64 * hf, 128 * r + 16 * warp); bulk_commit(); }
    }
    if (elect()) bulk_wait_read();
    TSTAMP(tid == 128, 17);
    __syncwarp();
    cluster_sync();
  } else {
    asm volatile("setmaxnreg.dec.sync.aligned.u32 %0;" :: "n"(504 - 2 * CREGS));
    auto chunk = [&](int ks) { const int c = ks >= 9, t = ks - 2 - 7 * c; return ks < 2 ? 2 * j + ks : 2 * (t + (t >= j)) + c; };
    auto load_q = [&](int n) {
      mbar_expect(bar(B_Q_FULL + (n & 3)), 4096);
      tma2d(sb + SM_Q + (n & 3) * 4096, &P.q, cl * 16, rho * 1024 + n * 128, bar(B_Q_FULL + (n & 3)));
    };
    auto load_wo = [&](uint32_t dst, int c, uint32_t bytes, uint32_t fb) {
      mbar_expect(fb, bytes);
      tma2d_mc(dst + rho * 8192, &P.wo, 128 * j + 64 * rho, c * 64, fb);
    };
    uint8_t* const xch = g_xch[r * 8 + j];
    if (warp == 8) {
      int ck = 0, cw = 0, cph = 1;
      const CUtensorMap* kvmap = rho ? &P.v : &P.k;
      auto load_kv = [&]() {
        if (elect()) {
          mbar_expect(bar(B_PREP_FULL + cw), 8704);
          tma3d_mc(sb + SM_STG + cw * 8704 + rho * 4608, kvmap, cl * 16, ck * 8 - 1 + rho, 0, bar(B_PREP_FULL + cw));
        }
        ++ck;
        if (++cw == 3) { cw = 0; cph ^= 1; }
      };
      auto load_stage = [&](int it) {
        const uint32_t st = sb + (it & 3) * QKV_STAGE, fb = bar(B_QKV_FULL + (it & 3));
        if (elect()) {
          mbar_expect(fb, QKV_STAGE);
          if (KBAL) tma2d_mc(st + 24576 + rho * 4096, &P.wk, 1024 + 128 * j + 64 * rho, 32 * it, fb);
          else if ((it & 1) == rho) tma3d_mc(st + 24576, &P.w, 0, 32 * it, 16 + 2 * j, fb);
          tma3d_mc(st + 8192 + rho * 8192, &P.w, 0, 32 * it, 32 * rho + 2 * j, fb);
          tma2d(st, &P.x, 32 * it, 128 * r, fb);
        }
      };
#pragma unroll 1
      for (int it = NE; it < 4; ++it) load_stage(it);
      LOOPSTAMP(3, lane == 0, 16);
      auto fetch_w = [&](int it) {
        if (elect()) {
          if (rho) l2_prefetch3d(&P.w, 0, 32 * it, 16 + 2 * j);
          l2_prefetch3d(&P.w, 0, 32 * it, 32 * rho + 2 * j);
        }
      };
      if (XPF) {
        if (XPFD) delay(XPFD);
        if (((rp - 4) & 7) < XPF) fetch_w(4 + ((rp - 4) & 7));
        if (((j - 4) & 7) < XPF && elect()) l2_prefetch2d(&P.x, 32 * (4 + ((j - 4) & 7)), 128 * r);
      }
#pragma unroll 1
      for (int i = 0; i < 8; i++) asm volatile("st.shared.v4.b32 [%0], {%1,%1,%1,%1};" :: "r"(sb + SM_F1 + i * 512 + lane * 16), "r"(0xffffffffu) : "memory");
      fence_async_smem();
      __syncwarp();
      if (!(DBG & 1) && elect()) { mbar_expect(bar(B_H_FULL), 12288); mbar_expect(bar(B_H_FULL + 1), 12288); mbar_expect(bar(B_H_FULL + 2), 8192); }
      auto load_h = [&](int c) {
        if (!(DBG & 1) && elect()) bulk_load(sb + SM_SIG + c * 8192 + 4096, P.ssm_k + (size_t)(cta * 8 + c) * 2048, 4096, bar(B_H_FULL + (c >= 3) + (c >= 6)));
      };
      LOOPSTAMP(3, lane == 0, 17);
      mbar_wait(bar(B_QKV_FULL), 0);
#pragma unroll 1
      for (int c = 0; c < HE; c++) load_h(c);
      if (PSTART < 4) load_kv();
      LOOPSTAMP(3, lane == 0, 18);
#pragma unroll 1
      for (int it = 4; it < 32; ++it) {
        mbar_wait(bar(B_QKV_EMPTY + (it & 3)), ((it >> 2) - 1) & 1);
        if (KVFIRST && ck < 16 && it >= PSTART && __all_sync(0xffffffffu, mbar_test(bar(B_PREP_EMPTY + cw), cph))) load_kv();
        load_stage(it);
        LOOPSTAMP(3, lane == 0 && it < 12, 15 + it);
        if (XPF && it < 32 - XPF) {
          if (((it + XPF) & 7) == rp) fetch_w(it + XPF);
          if (((it + XPF) & 7) == j && elect()) l2_prefetch2d(&P.x, 32 * (it + XPF), 128 * r);
        }
        if (it < 12 - HE) {
          load_h(it - 4 + HE);
        } else if (it < 23 - HE) {
          if (elect()) {
            if (!(DBG & 512)) bulk_store(xch + (it - 12 + HE) * 4096, sb + SM_F1, 4096);
            if (it == 22 - HE) bulk_commit();
          }
        } else if (it == 23 - HE) {
          if (elect()) { bulk_wait_read(); mbar_arrive(bar(B_PAT_FREE)); }
        } else if (it >= PF0 && it < PF0 + 6 && !(DBG & 8)) {
          if (elect()) l2_prefetch(it < PF0 + 2 ? P.wo_ptr + cta * 8192 + (it - PF0) * 4096 : P.q_ptr + cta * 16384 + (it - PF0 - 2) * 4096, 8192);
        }
        if (!KVFIRST && ck < 16 && it >= PSTART && !(DBG & 1) && __all_sync(0xffffffffu, mbar_test(bar(B_PREP_EMPTY + cw), cph))) load_kv();
      }
#pragma unroll 1
      while (ck < 16 && !(DBG & 1)) { mbar_wait(bar(B_PREP_EMPTY + cw), cph); load_kv(); }
      if (elect()) {
        flag_add(&g_ready);
        prefetch_map(&P.wo); prefetch_map(&P.outa); prefetch_map(&P.q);
        flag_wait(&g_ready, kCtas * (load_epoch(cta) + 1));
        mbar_arrive(bar(B_ZEROED));
        TSTAMP(true, 27);
      }
      __syncwarp();
      mbar_wait_long(bar(B_QKV_DONE), 0);
#pragma unroll 1
      for (int ks = 0; ks < NB0; ++ks) if (elect()) load_wo(sb + (4 + ks) * SLOT, chunk(ks), ks < 2 ? SLOT : 2 * SLOT, bar(B_OUT_FULL + ks));
    } else {
      const int at = tid - 288, aw = warp - 9, ch0 = cta * 8;
      {
        const uint32_t stg = sb + SM_STG + aw * 8704, pf = bar(B_PREP_FULL + aw), pe = bar(B_PREP_EMPTY + aw);
        const uint4 wv = __ldg(reinterpret_cast<const uint4*>(P.shift_k + (ch0 + 2 * (lane & 3)) * 4));
        const float skip = __bfloat162float(P.ssm_d[ch0 + (lane & 7)]);
        const uint32_t w0 = __byte_perm(wv.x, wv.z, 0x5410), w1 = __byte_perm(wv.x, wv.z, 0x7632);
        const uint32_t w2 = __byte_perm(wv.y, wv.w, 0x5410), w3 = __byte_perm(wv.y, wv.w, 0x7632);
        auto swz32 = [](uint32_t a) { return a ^ ((a >> 3) & 16); };
        const uint32_t kl = (lane >> 3) * 288 + (lane & 7) * 32 + rho * 16;
        const uint32_t ka = stg + swz32(kl + 32), kh = stg + swz32(kl + 12 * 288), va = stg + 4608 + swz32(lane * 32 + rho * 16);
        const uint32_t ua = sb + SM_SIG + (lane & 7) * 8192 + (((lane >> 3) ^ (lane & 7)) << 4);
        int ph = 0;
#pragma unroll 1
        for (int ck = aw; ck < 16; ck += 3, ph ^= 1) {
          if (DBG & 1) break;
          if (ck < 8 && !(DBG & 2)) {
            const uint32_t hs = sb + SM_SIG + ck * 8192 + 4096;
            uint32_t x[32];
            mbar_wait_long(bar(B_H_FULL + ck / 3), 0);
            LOOPSTAMP(4, at == 0, 23 + ck / 3);
#pragma unroll
            for (int i = 0; i < 8; i++) ldsm4(x + 4 * i, hs + i * 512 + lane * 16);
            const float d = __shfl_sync(0xffffffffu, skip, ck);
            if (lane == 0) x[0] = pack_bf16(bf_lo(x[0]) + d, bf_hi(x[0]));
            const uint32_t e = normalize(x, hs + (lane >> 1) * 128 + ((((lane & 1) * 4) ^ ((lane >> 1) & 7)) << 4));
            if (lane == 0) asm volatile("st.shared.b32 [%0], %1;" :: "r"(sb + SM_SC + 64 + 4 * ck), "r"(e) : "memory");
          }
          LOOPSTAMP(4, at == 0, 1 + ck);
          if (KVPF && ck + KVPF < 16 && elect()) {
            l2_prefetch(P.k_ptr + ((ck + KVPF) * 128 + cta) * 1024, 2048);
            l2_prefetch(P.v_ptr + ((ck + KVPF) * 128 + cta) * 1024, 2048);
          }
          mbar_wait_long(pf, ph);
          LOOPSTAMP(4, at == 0, 2 + ck);
          uint32_t k[20], v[16];
          ldsm4(k, kh);
#pragma unroll
          for (int m = 0; m < 4; m++) { ldsm4(k + 4 + 4 * m, (ka ^ ((m & 1) << 4)) + m * 1152); ldsm4(v + 4 * m, va + m * 1024); }
          if (EREL) arrive_both(pe + ((k[3] | k[4] | k[8] | k[12] | k[16] | v[0] | v[4] | v[8] | v[12]) & P.zero), lane, ck < 13);
#pragma unroll
          for (int m = 0; m < 4 && !(DBG & 16); m++) {
            uint32_t u[4];
#pragma unroll
            for (int n = 0; n < 4; n++) {
              const uint32_t* kk = k + 4 + 4 * m + n;
              u[n] = bmul2(bfma2(kk[0], w0, bfma2(kk[-1], w1, bfma2(kk[-2], w2, bmul2(kk[-3], w3)))), v[4 * m + n]);
            }
            stsm4_t((ua ^ (m << 6)) + ck * 256, u[0], u[1], u[2], u[3]);
          }
          if (!EREL) arrive_both(pe, lane, ck < 13);
          LOOPSTAMP(4, at == 0, 3 + ck);
        }
        bar_sync(4, 96);
        if (aw == 2 && elect()) {
          mbar_wait_long(bar(B_PAT_FREE), 0);
          fence_async_smem();
          mbar_expect(bar(B_SIG_READY), 10240);
          bulk_load(sb + SM_TW, g_tables, 10240, bar(B_SIG_READY));
        }
#pragma unroll 1
        for (int c = aw; c < 8 && !(DBG & 4); c += 3) {
          LOOPSTAMP(4, at == 0, 19 + c / 3);
          const uint32_t us = sb + SM_SIG + c * 8192;
          uint32_t x[32];
#pragma unroll
          for (int i = 0; i < 8; i++) ldsm4_t(x + 4 * i, us + i * 512 + ((lane ^ c) << 4));
          const uint32_t e = normalize(x, us + (lane >> 4) * 1024 + (lane & 7) * 128 + ((((lane >> 1) & 4) ^ (lane & 7)) << 4));
          const int f = min(max((int)(e + lds32(sb + SM_SC + 64 + 4 * c)) - 125, 0), 254);
          if (lane == 0) asm volatile("st.shared.b16 [%0], %1;" :: "r"(sb + SM_SC + rho * 16 + 2 * c), "h"((uint16_t)(f << 7)) : "memory");
        }
        fence_async_smem();
        __syncwarp();
        if (lane == 0) mbar_arrive(bar(B_SIG_READY));
        bar_sync(4, 96);
        if (at == 32) {
          const uint4 s = lds128(sb + SM_SC + rho * 16);
          asm volatile("st.async.weak.shared::cluster.mbarrier::complete_tx::bytes.v4.b32 [%0], {%1,%2,%3,%4}, [%5];"
                       :: "r"(peer_addr(sb + SM_SC + rho * 16, rho ^ 1)), "r"(s.x), "r"(s.y), "r"(s.z), "r"(s.w), "r"(peer_addr(bar(B_RDY0), rho ^ 1)) : "memory");
        }
        TSTAMP(at == 0, 20); LOOPSTAMP(4, at == 0, 22);
      }
    }
    __syncwarp();
    const unsigned epoch = load_epoch(cta);
    mbar_wait_long(bar(B_KVP), 0);
    {
      const int a4 = warp - 8;
      uint32_t v[20];
      int n = 0;
      do {
#pragma unroll
        for (int i = 0; i < 4; i++) ld_relaxed4(v + 4 * i, xch + 2 * SLOT + ((lane >> 3) * 4 + i) * KV_SLICE + (a4 * 8 + (lane & 7)) * 16);
        v[16] = ld_relaxed(xch + 2 * SLOT + (lane & 15) * KV_SLICE + 512 + (a4 * 2 + (lane >> 4)) * 4);
      } while (!all_arrived<17>(v) && ++n < kSpinLimit);
      TSTAMP(tid == 288, 21);
      float lo[4], hi[4], z = __uint_as_float(v[16]);
#pragma unroll
      for (int b = 0; b < 4; b++) {
        lo[b] = (bf_lo(v[b]) + bf_lo(v[4 + b])) + (bf_lo(v[8 + b]) + bf_lo(v[12 + b]));
        hi[b] = (bf_hi(v[b]) + bf_hi(v[4 + b])) + (bf_hi(v[8 + b]) + bf_hi(v[12 + b]));
      }
      const bool u16 = lane & 16, u8 = lane & 8;
#pragma unroll
      for (int b = 0; b < 2; b++) {
        lo[b] = (u16 ? lo[b + 2] : lo[b]) + __shfl_xor_sync(0xffffffffu, u16 ? lo[b] : lo[b + 2], 16);
        hi[b] = (u16 ? hi[b + 2] : hi[b]) + __shfl_xor_sync(0xffffffffu, u16 ? hi[b] : hi[b + 2], 16);
      }
      const float l = (u8 ? lo[1] : lo[0]) + __shfl_xor_sync(0xffffffffu, u8 ? lo[0] : lo[1], 8);
      const float h = (u8 ? hi[1] : hi[0]) + __shfl_xor_sync(0xffffffffu, u8 ? hi[0] : hi[1], 8);
      uint8_t* red = xch + 2 * SLOT + 16 * KV_SLICE;
      st_relaxed(red + (a4 * 8 + (lane & 7)) * 16 + (lane >> 3) * 4, pack_bf16(l, h));
#pragma unroll
      for (int o = 8; o; o >>= 1) z += __shfl_xor_sync(0xffffffffu, z, o);
      if ((lane & 15) == 0) st_relaxed(red + 512 + (a4 * 2 + (lane >> 4)) * 4, pack_bf16(z, z));
      TSTAMP(tid == 288, 22);
      n = 0;
      do {
#pragma unroll
        for (int i = 0; i < 4; i++) {
          const uint8_t* src = g_xch[(a4 * 4 + i) * 8 + j] + 2 * SLOT + 16 * KV_SLICE;
          ld_relaxed4(v + 4 * i, src + lane * 16);
          v[16 + i] = ld_relaxed(src + 512 + (lane & 28));
        }
      } while (!all_arrived<20>(v) && ++n < kSpinLimit);
#pragma unroll
      for (int i = 0; i < 4; i++) {
        const uint32_t dst = sb + SM_KV + (a4 * 4 + i) * 640;
        stsm4(dst + lane * 16, v[4 * i], v[4 * i + 1], v[4 * i + 2], v[4 * i + 3]);
        asm volatile("st.shared.b32 [%0], %1;" :: "r"(dst + 512 + lane * 4), "r"(v[16 + i]) : "memory");
      }
      fence_async_smem();
      __syncwarp();
      if (lane == 0) mbar_arrive(bar(B_KV_READY));
      TSTAMP(tid == 288, 23);
    }
    if (warp == 8) {
#pragma unroll 1
      for (int ks = NB0; ks < 4; ++ks) if (elect()) load_wo(sb + (4 + ks) * SLOT, chunk(ks), ks < 2 ? SLOT : 2 * SLOT, bar(B_OUT_FULL + ks));
#pragma unroll 1
      for (int n = 0; n < 4; ++n) if (elect()) load_q(n);
      int s = 4;
      uint32_t ph = 1;
#pragma unroll 1
      for (int ks = 4; ks < 16; ++ks) {
        uint32_t fb = bar(B_OUT_FULL + s), dst = sb + ((B_SLOTS >> (4 * s)) & 15) * SLOT;
        int c = chunk(ks);
        keep(fb); keep(dst); keep(c);
        mbar_wait_long(bar(ks == 4 ? B_CONV_DONE : B_OUT_EMPTY + s), ks == 4 ? 0 : ph);
        if (elect()) load_wo(dst, c, 2 * SLOT, fb);
        if (++s == 5) { s = 0; ph ^= 1; }
      }
    } else {
      auto wait_chunks = [&](unsigned mask) {
        unsigned ready;
        int n = 0;
        do {
          const unsigned f = ld_relaxed(&g_oflag[(r * 8 + ((lane >> 1) & 7)) * 32]);
          ready = __ballot_sync(0xffffffffu, (int)(f - (2 * epoch + 1 + (lane & 1))) >= 0);
        } while ((~ready & mask) && ++n < kSpinLimit);
        return ready;
      };
      if (warp == 9) {
        if (elect()) {
#pragma unroll 1
          for (int c = 0; c < 2; c++) {
            mbar_wait_long(bar(B_O_WRITTEN + c), 0);
            TSTAMP(c == 0, 19);
            if (c) delay(C1DELAY);
            bulk_store(xch + c * SLOT, sb + c * SLOT, SLOT);
            bulk_commit();
            bulk_wait_read();
            mbar_arrive(bar(B_OT_FREE + c));
            delay(FDELAY);
            st_relaxed(&g_oflag[(r * 8 + j) * 32], 2 * epoch + 1 + c);
            TSTAMP(c == 0, 29); TSTAMP(c == 1, 25);
          }
          g_epoch[cta] = epoch + 1;
        }
        __syncwarp();
        wait_chunks(0xaaaa);
        if (lane == 0) mbar_arrive(bar(B_FLAGS1));
      } else if (warp == 10) {
        mbar_wait_long(bar(B_RDY0), 0);
#pragma unroll 1
        for (int n = 0; n < 4; n++) {
          const int w = n & 1;
          mbar_wait_long(bar(B_SEG + n), 0);
          if (elect()) bulk_to_peer(sb + (n < 2 ? SM_Y0 : SM_SIG) + w * 8192 + 4096, sb + SM_YT + w * 4096, 4096, bar(B_YIN + (n >> 1)), rho ^ 1);
          if (w) {
            mbar_wait_long(bar(B_YIN + (n >> 1)), 0);
            if (lane == 0) asm volatile("mbarrier.arrive.shared::cluster.b64 _, [%0];" :: "r"(n < 2 ? peer_addr(bar(B_RDY1), rho ^ 1) : bar(B_Y_READY)) : "memory");
          }
        }
        TSTAMP(lane == 0, 26);
      } else {
        mbar_wait_long(bar(B_O_WRITTEN + 1), 0);
        unsigned ready = 0;
        int s = 2;
        uint32_t ph = 1;
#pragma unroll 1
        for (int ks = 2; ks < 16; ++ks) {
          const int c = chunk(ks);
          uint32_t fb = bar(B_OUT_FULL + s), dst = sb + ((A_SLOTS >> (4 * s)) & 15) * SLOT;
          uint8_t* src = g_xch[r * 8 + (c >> 1)] + (c & 1) * SLOT;
          keep(fb); keep(dst); keep(src);
          if (ks < 5 || ks == 9) {
            const unsigned need = ks < 4 ? 1u << c : 0x5555u;
            if (ks == 9) mbar_wait(bar(B_FLAGS1), 0);
            else if (~ready & need) ready = wait_chunks(need);
          }
          if (ks == 5 || ks == 6) mbar_wait(bar(B_OT_FREE + s), 0);
          if (ks >= 4) mbar_wait(bar(ks == 4 ? B_CONV_DONE : B_OUT_EMPTY + s), ks == 4 ? 0 : ph);
          if (elect()) bulk_load(dst, src, SLOT, fb);
          TSTAMP(ks == 2 && lane == 0, 18); LOOPSTAMP(2, lane == 0, 11 + ks);
          if (++s == 5) { s = 0; ph ^= 1; }
        }
      }
      if (warp < 11) {
        const int yc = (lane & 1) + ((lane >> 2) & 2) + (lane & 2) * 2, ysrc = (lane >> 2) & 1;
        const uint32_t ya = sb + (yc & 4 ? SM_SIG : SM_Y0) + (yc & 1) * 8192 + (yc & 2) * 1024 + (ysrc ^ rho) * 4096 +
                            (lane >> 4) * 128 + ((yc ^ (2 * ysrc)) << 4);
        uint32_t s0, s1;
        mbar_wait_long(bar(B_Y_READY), 0);
        asm volatile("ld.shared.v2.b32 {%0,%1}, [%2];" : "=r"(s0), "=r"(s1) : "r"(sb + SM_SC + (lane & 3) * 8) : "memory");
#pragma unroll 1
        for (int n = warp - 9; n < 8; n += 2) {
          __nv_bfloat16* op = P.out_ptr + (rho * 1024 + n * 128 + (lane >> 2)) * 2048 + 1024 + cl * 16 + (lane & 3) * 4;
          const uint32_t qa = sb + SM_Q + (n & 3) * 4096 + lane * 8;
          mbar_wait_long(bar(B_Q_FULL + (n & 3)), n >> 2);
#pragma unroll 1
          for (int u0 = 0; u0 < 8; u0 += GB) {
            const long long t0 = clock64();
            uint32_t y[GB][4], q[GB][4];
#pragma unroll
            for (int u = 0; u < GB; u++) {
              ldsm4_t(y[u], (ya ^ ((u0 + u) << 4)) + n * 256);
#pragma unroll
              for (int m = 0; m < 2; m++)
                asm volatile("ld.shared.v2.b32 {%0,%1}, [%2];" : "=r"(q[u][2 * m]), "=r"(q[u][2 * m + 1]) : "r"(qa + (u0 + u) * 512 + m * 256) : "memory");
            }
#pragma unroll
            for (int u = 0; u < GB; u++)
#pragma unroll
              for (int m = 0; m < 2; m++)
                if (!(DBG & 32) || q[u][0] == 0x12345678) asm volatile("st.global.v2.b32 [%0], {%1,%2};" :: "l"(op + (u0 * 16 + u * 16 + m * 8) * 2048),
                             "r"(bmul2(q[u][2 * m], bmul2(y[u][2 * m], s0))), "r"(bmul2(q[u][2 * m + 1], bmul2(y[u][2 * m + 1], s1))) : "memory");
            if (PPACE) while (clock64() - t0 < PPACE) { }
          }
          __syncwarp();
          if (n < 4 && elect()) load_q(n + 4);
        }
        TSTAMP(tid == 320, 24);
      }
    }
    __syncwarp();
    cluster_sync();
  }
  TSTAMP(tid == 0, 28); GSTAMP(tid == 0, 31);
}

typedef CUresult (*EncodeFn)(CUtensorMap*, CUtensorMapDataType, cuuint32_t, void*, const cuuint64_t*, const cuuint64_t*,
                             const cuuint32_t*, const cuuint32_t*, CUtensorMapInterleave, CUtensorMapSwizzle,
                             CUtensorMapL2promotion, CUtensorMapFloatOOBfill);

void encode(EncodeFn fn, CUtensorMap* m, const void* p, int rank, const cuuint64_t* dims, const cuuint64_t* strides,
            const cuuint32_t* box, CUtensorMapSwizzle sw) {
  const cuuint32_t es[3] = {1, 1, 1};
  fn(m, CU_TENSOR_MAP_DATA_TYPE_BFLOAT16, rank, const_cast<void*>(p), dims, strides, box, es, CU_TENSOR_MAP_INTERLEAVE_NONE, sw,
     CU_TENSOR_MAP_L2_PROMOTION_NONE, CU_TENSOR_MAP_FLOAT_OOB_FILL_NONE);
}
void encode2d(EncodeFn fn, CUtensorMap* m, const void* p, uint64_t cols, uint64_t rows, uint32_t bc, uint32_t br, CUtensorMapSwizzle sw) {
  const cuuint64_t dims[2] = {cols, rows}, strides[1] = {cols * 2};
  const cuuint32_t box[2] = {bc, br};
  encode(fn, m, p, 2, dims, strides, box, sw);
}
void encode3d(EncodeFn fn, CUtensorMap* m, const void* p, uint32_t nblk) {
  const cuuint64_t dims[3] = {1024, 128, 16}, strides[2] = {2048 * 16, 2048};
  const cuuint32_t box[3] = {16, nblk, 16};
  encode(fn, m, p, 3, dims, strides, box, CU_TENSOR_MAP_SWIZZLE_32B);
}

}

extern "C" void kernel_launch(void* const* d_in, const int* in_sizes, int n_in, void* d_out, int out_size) {
  static EncodeFn fn = nullptr;
  if (!fn) {
    cudaDriverEntryPointQueryResult qr;
    cudaGetDriverEntryPoint("cuTensorMapEncodeTiled", (void**)&fn, cudaEnableDefault, &qr);
    cudaFuncSetAttribute(fused_kernel, cudaFuncAttributeMaxDynamicSharedMemorySize, SM_TOTAL);
  }
  Params P;
  encode2d(fn, &P.x, d_in[0], 1024, 2048, 32, 128, CU_TENSOR_MAP_SWIZZLE_64B);
  {
    const cuuint64_t dims[3] = {64, 1024, 48}, strides[2] = {6144, 128};
    const cuuint32_t box[3] = {64, 32, 2};
    encode(fn, &P.w, d_in[1], 3, dims, strides, box, CU_TENSOR_MAP_SWIZZLE_128B);
  }
  encode2d(fn, &P.wk, d_in[1], 3072, 1024, 64, 32, CU_TENSOR_MAP_SWIZZLE_128B);
  encode2d(fn, &P.wo, d_in[2], 1024, 1024, 64, 64, CU_TENSOR_MAP_SWIZZLE_128B);
  encode2d(fn, &P.outa, d_out, 2048, 2048, 64, 16, CU_TENSOR_MAP_SWIZZLE_128B);
  encode3d(fn, &P.k, d_in[4], 9);
  encode3d(fn, &P.v, d_in[5], 8);
  encode2d(fn, &P.q, d_in[3], 1024, 2048, 16, 128, CU_TENSOR_MAP_SWIZZLE_NONE);
  P.shift_k = (const __nv_bfloat16*)d_in[6];
  P.ssm_k = (const __nv_bfloat16*)d_in[7];
  P.ssm_d = (const __nv_bfloat16*)d_in[8];
  P.zero = 0;
  for (int cl = 0; cl < 64; cl++) {
    const int gpc = cl < 4 ? 0 : cl < 36 ? (cl - 4) & 7 : 1 + (cl - 36) % 7, mem = cl < 4 ? 4 + cl : cl < 36 ? (cl - 4) >> 3 : 4 + (cl - 36) / 7;
    P.tile[cl] = (uint8_t)(8 * gpc + mem);
  }
  P.q_ptr = (const __nv_bfloat16*)d_in[3];
  P.out_ptr = (__nv_bfloat16*)d_out;
  P.k_ptr = (const __nv_bfloat16*)d_in[4];
  P.v_ptr = (const __nv_bfloat16*)d_in[5];
  P.wo_ptr = (const __nv_bfloat16*)d_in[2];
  fused_kernel<<<kCtas, kThreads, SM_TOTAL>>>(P);
}
```

```cpp
#include <cuda.h>
#include <cuda_runtime.h>
#include <cuda_bf16.h>
#include <stdint.h>

#define DEVI __device__ __forceinline__

namespace {

DEVI void mma_nt(float* d, uint64_t da, uint64_t db, int sd) {
  asm volatile("{\n.reg .pred p;\nsetp.ne.b32 p, %66, 0;\nwgmma.mma_async.sync.aligned.m64n128k16.f32.bf16.bf16 {%0, %1, %2, %3, %4, %5, %6, %7, %8, %9, %10, %11, %12, %13, %14, %15, %16, %17, %18, %19, %20, %21, %22, %23, %24, %25, %26, %27, %28, %29, %30, %31, %32, %33, %34, %35, %36, %37, %38, %39, %40, %41, %42, %43, %44, %45, %46, %47, %48, %49, %50, %51, %52, %53, %54, %55, %56, %57, %58, %59, %60, %61, %62, %63}, %64, %65, p, 1, 1, 0, 1;\n}\n"
    : "+f"(d[0]), "+f"(d[1]), "+f"(d[2]), "+f"(d[3]), "+f"(d[4]), "+f"(d[5]), "+f"(d[6]), "+f"(d[7]), "+f"(d[8]), "+f"(d[9]), "+f"(d[10]), "+f"(d[11]), "+f"(d[12]), "+f"(d[13]), "+f"(d[14]), "+f"(d[15]), "+f"(d[16]), "+f"(d[17]), "+f"(d[18]), "+f"(d[19]), "+f"(d[20]), "+f"(d[21]), "+f"(d[22]), "+f"(d[23]), "+f"(d[24]), "+f"(d[25]), "+f"(d[26]), "+f"(d[27]), "+f"(d[28]), "+f"(d[29]), "+f"(d[30]), "+f"(d[31]), "+f"(d[32]), "+f"(d[33]), "+f"(d[34]), "+f"(d[35]), "+f"(d[36]), "+f"(d[37]), "+f"(d[38]), "+f"(d[39]), "+f"(d[40]), "+f"(d[41]), "+f"(d[42]), "+f"(d[43]), "+f"(d[44]), "+f"(d[45]), "+f"(d[46]), "+f"(d[47]), "+f"(d[48]), "+f"(d[49]), "+f"(d[50]), "+f"(d[51]), "+f"(d[52]), "+f"(d[53]), "+f"(d[54]), "+f"(d[55]), "+f"(d[56]), "+f"(d[57]), "+f"(d[58]), "+f"(d[59]), "+f"(d[60]), "+f"(d[61]), "+f"(d[62]), "+f"(d[63])
    : "l"(da), "l"(db), "r"(sd));
}
DEVI void mma_tn(float* d, uint64_t da, uint64_t db, int sd) {
  asm volatile("{\n.reg .pred p;\nsetp.ne.b32 p, %66, 0;\nwgmma.mma_async.sync.aligned.m64n128k16.f32.bf16.bf16 {%0, %1, %2, %3, %4, %5, %6, %7, %8, %9, %10, %11, %12, %13, %14, %15, %16, %17, %18, %19, %20, %21, %22, %23, %24, %25, %26, %27, %28, %29, %30, %31, %32, %33, %34, %35, %36, %37, %38, %39, %40, %41, %42, %43, %44, %45, %46, %47, %48, %49, %50, %51, %52, %53, %54, %55, %56, %57, %58, %59, %60, %61, %62, %63}, %64, %65, p, 1, 1, 1, 0;\n}\n"
    : "+f"(d[0]), "+f"(d[1]), "+f"(d[2]), "+f"(d[3]), "+f"(d[4]), "+f"(d[5]), "+f"(d[6]), "+f"(d[7]), "+f"(d[8]), "+f"(d[9]), "+f"(d[10]), "+f"(d[11]), "+f"(d[12]), "+f"(d[13]), "+f"(d[14]), "+f"(d[15]), "+f"(d[16]), "+f"(d[17]), "+f"(d[18]), "+f"(d[19]), "+f"(d[20]), "+f"(d[21]), "+f"(d[22]), "+f"(d[23]), "+f"(d[24]), "+f"(d[25]), "+f"(d[26]), "+f"(d[27]), "+f"(d[28]), "+f"(d[29]), "+f"(d[30]), "+f"(d[31]), "+f"(d[32]), "+f"(d[33]), "+f"(d[34]), "+f"(d[35]), "+f"(d[36]), "+f"(d[37]), "+f"(d[38]), "+f"(d[39]), "+f"(d[40]), "+f"(d[41]), "+f"(d[42]), "+f"(d[43]), "+f"(d[44]), "+f"(d[45]), "+f"(d[46]), "+f"(d[47]), "+f"(d[48]), "+f"(d[49]), "+f"(d[50]), "+f"(d[51]), "+f"(d[52]), "+f"(d[53]), "+f"(d[54]), "+f"(d[55]), "+f"(d[56]), "+f"(d[57]), "+f"(d[58]), "+f"(d[59]), "+f"(d[60]), "+f"(d[61]), "+f"(d[62]), "+f"(d[63])
    : "l"(da), "l"(db), "r"(sd));
}
DEVI void mma_nt256(float* d, uint64_t da, uint64_t db, int sd) {
  asm volatile("{\n.reg .pred p;\nsetp.ne.b32 p, %130, 0;\nwgmma.mma_async.sync.aligned.m64n256k16.f32.bf16.bf16 {%0, %1, %2, %3, %4, %5, %6, %7, %8, %9, %10, %11, %12, %13, %14, %15, %16, %17, %18, %19, %20, %21, %22, %23, %24, %25, %26, %27, %28, %29, %30, %31, %32, %33, %34, %35, %36, %37, %38, %39, %40, %41, %42, %43, %44, %45, %46, %47, %48, %49, %50, %51, %52, %53, %54, %55, %56, %57, %58, %59, %60, %61, %62, %63, %64, %65, %66, %67, %68, %69, %70, %71, %72, %73, %74, %75, %76, %77, %78, %79, %80, %81, %82, %83, %84, %85, %86, %87, %88, %89, %90, %91, %92, %93, %94, %95, %96, %97, %98, %99, %100, %101, %102, %103, %104, %105, %106, %107, %108, %109, %110, %111, %112, %113, %114, %115, %116, %117, %118, %119, %120, %121, %122, %123, %124, %125, %126, %127}, %128, %129, p, 1, 1, 0, 1;\n}\n"
    : "+f"(d[0]), "+f"(d[1]), "+f"(d[2]), "+f"(d[3]), "+f"(d[4]), "+f"(d[5]), "+f"(d[6]), "+f"(d[7]), "+f"(d[8]), "+f"(d[9]), "+f"(d[10]), "+f"(d[11]), "+f"(d[12]), "+f"(d[13]), "+f"(d[14]), "+f"(d[15]), "+f"(d[16]), "+f"(d[17]), "+f"(d[18]), "+f"(d[19]), "+f"(d[20]), "+f"(d[21]), "+f"(d[22]), "+f"(d[23]), "+f"(d[24]), "+f"(d[25]), "+f"(d[26]), "+f"(d[27]), "+f"(d[28]), "+f"(d[29]), "+f"(d[30]), "+f"(d[31]), "+f"(d[32]), "+f"(d[33]), "+f"(d[34]), "+f"(d[35]), "+f"(d[36]), "+f"(d[37]), "+f"(d[38]), "+f"(d[39]), "+f"(d[40]), "+f"(d[41]), "+f"(d[42]), "+f"(d[43]), "+f"(d[44]), "+f"(d[45]), "+f"(d[46]), "+f"(d[47]), "+f"(d[48]), "+f"(d[49]), "+f"(d[50]), "+f"(d[51]), "+f"(d[52]), "+f"(d[53]), "+f"(d[54]), "+f"(d[55]), "+f"(d[56]), "+f"(d[57]), "+f"(d[58]), "+f"(d[59]), "+f"(d[60]), "+f"(d[61]), "+f"(d[62]), "+f"(d[63]), "+f"(d[64]), "+f"(d[65]), "+f"(d[66]), "+f"(d[67]), "+f"(d[68]), "+f"(d[69]), "+f"(d[70]), "+f"(d[71]), "+f"(d[72]), "+f"(d[73]), "+f"(d[74]), "+f"(d[75]), "+f"(d[76]), "+f"(d[77]), "+f"(d[78]), "+f"(d[79]), "+f"(d[80]), "+f"(d[81]), "+f"(d[82]), "+f"(d[83]), "+f"(d[84]), "+f"(d[85]), "+f"(d[86]), "+f"(d[87]), "+f"(d[88]), "+f"(d[89]), "+f"(d[90]), "+f"(d[91]), "+f"(d[92]), "+f"(d[93]), "+f"(d[94]), "+f"(d[95]), "+f"(d[96]), "+f"(d[97]), "+f"(d[98]), "+f"(d[99]), "+f"(d[100]), "+f"(d[101]), "+f"(d[102]), "+f"(d[103]), "+f"(d[104]), "+f"(d[105]), "+f"(d[106]), "+f"(d[107]), "+f"(d[108]), "+f"(d[109]), "+f"(d[110]), "+f"(d[111]), "+f"(d[112]), "+f"(d[113]), "+f"(d[114]), "+f"(d[115]), "+f"(d[116]), "+f"(d[117]), "+f"(d[118]), "+f"(d[119]), "+f"(d[120]), "+f"(d[121]), "+f"(d[122]), "+f"(d[123]), "+f"(d[124]), "+f"(d[125]), "+f"(d[126]), "+f"(d[127])
    : "l"(da), "l"(db), "r"(sd));
}
DEVI void mma_kv_init(float* d, uint32_t a0, uint32_t a1, uint32_t a2, uint32_t a3, uint64_t db) {
  asm volatile("wgmma.mma_async.sync.aligned.m64n72k16.f32.bf16.bf16 {%0, %1, %2, %3, %4, %5, %6, %7, %8, %9, %10, %11, %12, %13, %14, %15, %16, %17, %18, %19, %20, %21, %22, %23, %24, %25, %26, %27, %28, %29, %30, %31, %32, %33, %34, %35}, {%36,%37,%38,%39}, %40, 0, 1, 1, 1;\n"
    : "=f"(d[0]), "=f"(d[1]), "=f"(d[2]), "=f"(d[3]), "=f"(d[4]), "=f"(d[5]), "=f"(d[6]), "=f"(d[7]), "=f"(d[8]), "=f"(d[9]), "=f"(d[10]), "=f"(d[11]), "=f"(d[12]), "=f"(d[13]), "=f"(d[14]), "=f"(d[15]), "=f"(d[16]), "=f"(d[17]), "=f"(d[18]), "=f"(d[19]), "=f"(d[20]), "=f"(d[21]), "=f"(d[22]), "=f"(d[23]), "=f"(d[24]), "=f"(d[25]), "=f"(d[26]), "=f"(d[27]), "=f"(d[28]), "=f"(d[29]), "=f"(d[30]), "=f"(d[31]), "=f"(d[32]), "=f"(d[33]), "=f"(d[34]), "=f"(d[35])
    : "r"(a0), "r"(a1), "r"(a2), "r"(a3), "l"(db));
}
DEVI void mma_kv_acc(float* d, uint32_t a0, uint32_t a1, uint32_t a2, uint32_t a3, uint64_t db) {
  asm volatile("wgmma.mma_async.sync.aligned.m64n72k16.f32.bf16.bf16 {%0, %1, %2, %3, %4, %5, %6, %7, %8, %9, %10, %11, %12, %13, %14, %15, %16, %17, %18, %19, %20, %21, %22, %23, %24, %25, %26, %27, %28, %29, %30, %31, %32, %33, %34, %35}, {%36,%37,%38,%39}, %40, 1, 1, 1, 1;\n"
    : "+f"(d[0]), "+f"(d[1]), "+f"(d[2]), "+f"(d[3]), "+f"(d[4]), "+f"(d[5]), "+f"(d[6]), "+f"(d[7]), "+f"(d[8]), "+f"(d[9]), "+f"(d[10]), "+f"(d[11]), "+f"(d[12]), "+f"(d[13]), "+f"(d[14]), "+f"(d[15]), "+f"(d[16]), "+f"(d[17]), "+f"(d[18]), "+f"(d[19]), "+f"(d[20]), "+f"(d[21]), "+f"(d[22]), "+f"(d[23]), "+f"(d[24]), "+f"(d[25]), "+f"(d[26]), "+f"(d[27]), "+f"(d[28]), "+f"(d[29]), "+f"(d[30]), "+f"(d[31]), "+f"(d[32]), "+f"(d[33]), "+f"(d[34]), "+f"(d[35])
    : "r"(a0), "r"(a1), "r"(a2), "r"(a3), "l"(db));
}
DEVI void mma_o_init(float* d, uint32_t a0, uint32_t a1, uint32_t a2, uint32_t a3, uint64_t db) {
  asm volatile("wgmma.mma_async.sync.aligned.m64n40k16.f32.bf16.bf16 {%0, %1, %2, %3, %4, %5, %6, %7, %8, %9, %10, %11, %12, %13, %14, %15, %16, %17, %18, %19}, {%20,%21,%22,%23}, %24, 0, 1, 1, 1;\n"
    : "=f"(d[0]), "=f"(d[1]), "=f"(d[2]), "=f"(d[3]), "=f"(d[4]), "=f"(d[5]), "=f"(d[6]), "=f"(d[7]), "=f"(d[8]), "=f"(d[9]), "=f"(d[10]), "=f"(d[11]), "=f"(d[12]), "=f"(d[13]), "=f"(d[14]), "=f"(d[15]), "=f"(d[16]), "=f"(d[17]), "=f"(d[18]), "=f"(d[19])
    : "r"(a0), "r"(a1), "r"(a2), "r"(a3), "l"(db));
}
DEVI void mma_o_acc(float* d, uint32_t a0, uint32_t a1, uint32_t a2, uint32_t a3, uint64_t db) {
  asm volatile("wgmma.mma_async.sync.aligned.m64n40k16.f32.bf16.bf16 {%0, %1, %2, %3, %4, %5, %6, %7, %8, %9, %10, %11, %12, %13, %14, %15, %16, %17, %18, %19}, {%20,%21,%22,%23}, %24, 1, 1, 1, 1;\n"
    : "+f"(d[0]), "+f"(d[1]), "+f"(d[2]), "+f"(d[3]), "+f"(d[4]), "+f"(d[5]), "+f"(d[6]), "+f"(d[7]), "+f"(d[8]), "+f"(d[9]), "+f"(d[10]), "+f"(d[11]), "+f"(d[12]), "+f"(d[13]), "+f"(d[14]), "+f"(d[15]), "+f"(d[16]), "+f"(d[17]), "+f"(d[18]), "+f"(d[19])
    : "r"(a0), "r"(a1), "r"(a2), "r"(a3), "l"(db));
}
DEVI void fft1_init(uint32_t* d, uint32_t a0, uint32_t a1, uint32_t a2, uint32_t a3, uint64_t db) {
  asm volatile("wgmma.mma_async.sync.aligned.m64n128k16.f16.f16.f16 {%0, %1, %2, %3, %4, %5, %6, %7, %8, %9, %10, %11, %12, %13, %14, %15, %16, %17, %18, %19, %20, %21, %22, %23, %24, %25, %26, %27, %28, %29, %30, %31}, {%32,%33,%34,%35}, %36, 0, 1, 1, 1;\n"
    : "=r"(d[0]), "=r"(d[1]), "=r"(d[2]), "=r"(d[3]), "=r"(d[4]), "=r"(d[5]), "=r"(d[6]), "=r"(d[7]), "=r"(d[8]), "=r"(d[9]), "=r"(d[10]), "=r"(d[11]), "=r"(d[12]), "=r"(d[13]), "=r"(d[14]), "=r"(d[15]), "=r"(d[16]), "=r"(d[17]), "=r"(d[18]), "=r"(d[19]), "=r"(d[20]), "=r"(d[21]), "=r"(d[22]), "=r"(d[23]), "=r"(d[24]), "=r"(d[25]), "=r"(d[26]), "=r"(d[27]), "=r"(d[28]), "=r"(d[29]), "=r"(d[30]), "=r"(d[31])
    : "r"(a0), "r"(a1), "r"(a2), "r"(a3), "l"(db));
}
DEVI void fft1_acc(uint32_t* d, uint32_t a0, uint32_t a1, uint32_t a2, uint32_t a3, uint64_t db) {
  asm volatile("wgmma.mma_async.sync.aligned.m64n128k16.f16.f16.f16 {%0, %1, %2, %3, %4, %5, %6, %7, %8, %9, %10, %11, %12, %13, %14, %15, %16, %17, %18, %19, %20, %21, %22, %23, %24, %25, %26, %27, %28, %29, %30, %31}, {%32,%33,%34,%35}, %36, 1, 1, 1, 1;\n"
    : "+r"(d[0]), "+r"(d[1]), "+r"(d[2]), "+r"(d[3]), "+r"(d[4]), "+r"(d[5]), "+r"(d[6]), "+r"(d[7]), "+r"(d[8]), "+r"(d[9]), "+r"(d[10]), "+r"(d[11]), "+r"(d[12]), "+r"(d[13]), "+r"(d[14]), "+r"(d[15]), "+r"(d[16]), "+r"(d[17]), "+r"(d[18]), "+r"(d[19]), "+r"(d[20]), "+r"(d[21]), "+r"(d[22]), "+r"(d[23]), "+r"(d[24]), "+r"(d[25]), "+r"(d[26]), "+r"(d[27]), "+r"(d[28]), "+r"(d[29]), "+r"(d[30]), "+r"(d[31])
    : "r"(a0), "r"(a1), "r"(a2), "r"(a3), "l"(db));
}
DEVI void fft2_init(uint32_t* d, uint32_t a0, uint32_t a1, uint32_t a2, uint32_t a3, uint64_t db) {
  asm volatile("wgmma.mma_async.sync.aligned.m64n32k16.f16.f16.f16 {%0, %1, %2, %3, %4, %5, %6, %7}, {%8,%9,%10,%11}, %12, 0, 1, 1, 0;\n"
    : "=r"(d[0]), "=r"(d[1]), "=r"(d[2]), "=r"(d[3]), "=r"(d[4]), "=r"(d[5]), "=r"(d[6]), "=r"(d[7])
    : "r"(a0), "r"(a1), "r"(a2), "r"(a3), "l"(db));
}
DEVI void fft2_acc(uint32_t* d, uint32_t a0, uint32_t a1, uint32_t a2, uint32_t a3, uint64_t db) {
  asm volatile("wgmma.mma_async.sync.aligned.m64n32k16.f16.f16.f16 {%0, %1, %2, %3, %4, %5, %6, %7}, {%8,%9,%10,%11}, %12, 1, 1, 1, 0;\n"
    : "+r"(d[0]), "+r"(d[1]), "+r"(d[2]), "+r"(d[3]), "+r"(d[4]), "+r"(d[5]), "+r"(d[6]), "+r"(d[7])
    : "r"(a0), "r"(a1), "r"(a2), "r"(a3), "l"(db));
}
DEVI void fft3_init(float* d, uint64_t da, uint64_t db) {
  asm volatile("wgmma.mma_async.sync.aligned.m64n32k16.f32.f16.f16 {%0, %1, %2, %3, %4, %5, %6, %7, %8, %9, %10, %11, %12, %13, %14, %15}, %16, %17, 0, 1, 1, 1, 0;\n"
    : "=f"(d[0]), "=f"(d[1]), "=f"(d[2]), "=f"(d[3]), "=f"(d[4]), "=f"(d[5]), "=f"(d[6]), "=f"(d[7]), "=f"(d[8]), "=f"(d[9]), "=f"(d[10]), "=f"(d[11]), "=f"(d[12]), "=f"(d[13]), "=f"(d[14]), "=f"(d[15])
    : "l"(da), "l"(db));
}
DEVI void fft3_acc(float* d, uint64_t da, uint64_t db) {
  asm volatile("wgmma.mma_async.sync.aligned.m64n32k16.f32.f16.f16 {%0, %1, %2, %3, %4, %5, %6, %7, %8, %9, %10, %11, %12, %13, %14, %15}, %16, %17, 1, 1, 1, 1, 0;\n"
    : "+f"(d[0]), "+f"(d[1]), "+f"(d[2]), "+f"(d[3]), "+f"(d[4]), "+f"(d[5]), "+f"(d[6]), "+f"(d[7]), "+f"(d[8]), "+f"(d[9]), "+f"(d[10]), "+f"(d[11]), "+f"(d[12]), "+f"(d[13]), "+f"(d[14]), "+f"(d[15])
    : "l"(da), "l"(db));
}

__device__ __align__(128) const uint32_t g_tables[2560] = {
0xa11ba1e4,0xa51ba5e4,0x18b61248,0x1cb61648,0x9f12a052,0xa311a452,0x1d7f1bdb,0x217f1fdb,0x9bdb9d7f,0x9fdba17f,0x20521f12,0x24522311,
0x924898b6,0x96489cb6,0x21e4211b,0x25e4251b,0xaa63ab5f,0xae5faf59,0x21e41bdb,0x25e41fdb,0xa86ba967,0xac6aad65,0x26e024e9,0x2ade28e8,
0xa4e9a6e0,0xa8e8aade,0x2967286b,0x2d652c6a,0x9bdba1e4,0x9fdba5e4,0x2b5f2a63,0x2f592e5f,0xadc2aea7,0xb1b6b294,0x254d1f12,0x294d2311,
0xabf6acde,0xafefb0d7,0x2a31286b,0x2e2d2c6a,0xa86baa31,0xac6aae2d,0x2cde2bf6,0x30d72fef,0x9f12a54d,0xa311a94d,0x2ea72dc2,0x329431b6,
0xb02cb0d2,0xb41ab4b7,0x27a9211b,0x2ba7251b,0xadc2af0c,0xb1b6b2f7,0x2c792a63,0x30742e5f,0xaa63ac79,0xae5fb074,0x2f0c2dc2,0x32f731b6,
0xa11ba7a9,0xa51baba7,0x30d2302c,0x34b7341a,0xb17ab257,0xb552b61a,0x290222ad,0x2d0026ad,0xaf8cb09f,0xb371b487,0x2ddc2c2e,0x31cf3029,
0xac2eaddc,0xb029b1cf,0x309f2f8c,0x34873371,0xa2ada902,0xa6adad00,0x3257317a,0x361a3552,0xb2cdb3e3,0xb682b76f,0x2a312420,0x2e2d281f,
0xb0acb1bb,0xb493b58d,0x2f3f2d2a,0x33283122,0xad2aaf3f,0xb122b328,0x31bb30ac,0x358d3493,0xa420aa31,0xa81fae2d,0x33e332cd,0x376f3682,
0xb413b4bc,0xb7a6b85a,0x2b5f24e9,0x2f5928e8,0xb194b2da,0xb56ab68d,0x30522e28,0x343e3219,0xae28b052,0xb219b43e,0x32da3194,0x368d356a,
0xa4e9ab5f,0xa8e8af59,0x34bc3413,0x385a37a6,0xb4c3b58c,0xb85fb8f3,0x2c4725b2,0x304229b1,0xb27eb3fd,0xb63cb785,0x31062f26,0x34e7330f,
0xaf26b106,0xb30fb4e7,0x33fd327e,0x3785363c,0xa5b2ac47,0xa9b1b042,0x358c34c3,0x38f3385f,0xb577b662,0xb8e5b982,0x2cde267b,0x30d72a7a,
0xb36bb493,0xb70ab83a,0x31bb3012,0x358d3402,0xb012b1bb,0xb402b58d,0x3493336b,0x383a370a,0xa67bacde,0xaa7ab0d7,0x36623577,0x398238e5,
0xb630b741,0xb962ba04,0x2d762744,0x316c2b43,0xb42eb52a,0xb7d2b8ad,0x32713092,0x3631347b,0xb092b271,0xb47bb631,0x352a342e,0x38ad37d2,
0xa744ad76,0xab43b16c,0x37413630,0x3a043962,0xb6eeb815,0xb9d6ba7a,0x2e0e2807,0x32012c06,0xb4a7b5c4,0xb84ab91b,0x33293113,0x36d234f3,
0xb113b329,0xb4f3b6d2,0x35c434a7,0x391b384a,0xa807ae0e,0xac06b201,0x381536ee,0x3a7a39d6,0xb7b4b88e,0xba41bae1,0x2ea7286b,0x32942c6a,
0xb523b662,0xb8a8b982,0x33e33194,0x376f356a,0xb194b3e3,0xb56ab76f,0x36623523,0x398238a8,0xa86baea7,0xac6ab294,0x388e37b4,0x3ae13a41,
0xb841b90f,0xbaa2bb3a,0x2f3f28d0,0x33282cce,0xb5a1b705,0xb902b9e3,0x344f3216,0x380535df,0xb216b44f,0xb5dfb805,0x370535a1,0x39e33902,
0xa8d0af3f,0xacceb328,0x390f3841,0x3b3a3aa2,0xb8acb997,0xbaf7bb83,0x2fd82935,0x33ba2d33,0xb621b7ac,0xb958ba3d,0x34ae3298,0x38503654,
0xb298b4ae,0xb654b850,0x37ac3621,0x3a3d3958,0xa935afd8,0xad33b3ba,0x399738ac,0x3b833af7,0xb91cba28,0xbb42bbbc,0x30392999,0x34262d97,
0xb6a4b82d,0xb9aaba90,0x350e331c,0x389936c6,0xb31cb50e,0xb6c6b899,0x382d36a4,0x3a9039aa,0xa999b039,0xad97b426,0x3a28391c,0x3bbc3b42,
0xb992bac3,0xbb81bbe3,0x308529fe,0x346f2dfb,0xb72ab886,0xb9f8badb,0x357033a0,0x38e03737,0xb3a0b570,0xb737b8e0,0x3886372a,0x3adb39f8,
0xa9feb085,0xadfbb46f,0x3ac33992,0x3be33b81,0x39cf3b16,0x3b9c3bf1,0xb0acaa31,0xb493ae2d,0x376f38b4,0x3a1d3afe,0xb5a1b3e3,0xb902b76f,
0x33e335a1,0x376f3902,0xb8b4b76f,0xbafeba1d,0x2a3130ac,0x2e2d3493,0xbb16b9cf,0xbbf1bb9c,0x39563a74,0x3b633bd2,0xb05fa9cc,0xb44badc9,
0x36e73859,0x39d23ab6,0xb53fb35e,0xb8bcb6ff,0x335e353f,0x36ff38bc,0xb859b6e7,0xbab6b9d2,0x29cc305f,0x2dc9344b,0xba74b956,0xbbd2bb63,
0x38e339de,0x3b1e3ba1,0xb012a967,0xb402ad65,0x36623801,0x39823a67,0xb4deb2da,0xb874b68d,0x32da34de,0x368d3874,0xb801b662,0xba67b982,
0x29673012,0x2d653402,0xb9deb8e3,0xbba1bb1e,0x38763952,0x3ace3b60,0xaf8ca902,0xb371ad00,0x35e13758,0x392e3a11,0xb47eb257,0xb82ab61a,
0x3257347e,0x361a382a,0xb758b5e1,0xba11b92e,0x29022f8c,0x2d003371,0xb952b876,0xbb60bace,0x380d38ce,0x3a733b10,0xaef3a89e,0xb2deac9c,
0x356236b3,0x38d639b3,0xb420b1d5,0xb7bdb5a5,0x31d53420,0x35a537bd,0xb6b3b562,0xb9b3b8d6,0x289e2ef3,0x2c9c32de,0xb8ceb80d,0xbb10ba73,
0x37503851,0x3a0d3ab0,0xae5aa839,0xb24bac38,0x34e53613,0x387a394f,0xb386b153,0xb721b52f,0x31533386,0x352f3721,0xb613b4e5,0xb94fb87a,
0x28392e5a,0x2c38324b,0xb851b750,0xbab0ba0d,0x368e37b4,0x399d3a41,0xadc2a7a9,0xb1b6aba7,0x346a3577,0x381a38e5,0xb2cdb0d2,0xb682b4b7,
0x30d232cd,0x34b73682,0xb577b46a,0xb8e5b81a,0x27a92dc2,0x2ba731b6,0xb7b4b68e,0xba41b99d,0x35d236d1,0x392439c5,0xad2aa6e0,0xb122aade,
0x33e334de,0x376f3874,0xb216b052,0xb5dfb43e,0x30523216,0x343e35df,0xb4deb3e3,0xb874b76f,0x26e02d2a,0x2ade3122,0xb6d1b5d2,0xb9c5b924,
0x351c35f6,0x38a3393c,0xac93a617,0xb08daa16,0x32f43448,0x36a437fe,0xb160afa5,0xb53ab389,0x2fa53160,0x3389353a,0xb448b2f4,0xb7feb6a4,
0x26172c93,0x2a16308d,0xb5f6b51c,0xb93cb8a3,0x346a3523,0x381a38a8,0xabf6a54d,0xafefa94d,0x3209336b,0x35d4370a,0xb0acaea7,0xb493b294,
0x2ea730ac,0x32943493,0xb36bb209,0xb70ab5d4,0x254d2bf6,0x294d2fef,0xb523b46a,0xb8a8b81a,0x33783456,0x3715380a,0xaac8a484,0xaec3a884,
0x3120324a,0x34ff360e,0xaff2ada9,0xb3d3b19e,0x2da92ff2,0x319e33d3,0xb24ab120,0xb60eb4ff,0x24842ac8,0x28842ec3,0xb456b378,0xb80ab715,
0x3223331c,0x35eb36c6,0xa999a376,0xad97a776,0x3039312d,0x3426350b,0xae8dacac,0xb27cb0a6,0x2cac2e8d,0x30a6327c,0xb12db039,0xb50bb426,
0x23762999,0x27762d97,0xb31cb223,0xb6c6b5eb,0x30d23194,0x34b7356a,0xa86ba1e4,0xac6aa5e4,0x2ea73012,0x32943402,0xad2aab5f,0xb122af59,
0x2b5f2d2a,0x2f593122,0xb012aea7,0xb402b294,0x21e4286b,0x25e42c6a,0xb194b0d2,0xb56ab4b7,0x2f0c3012,0x32f73402,0xa67ba052,0xaa7aa452,
0x2cde2df5,0x30d731e8,0xab91a967,0xaf8bad65,0x29672b91,0x2d652f8b,0xadf5acde,0xb1e8b0d7,0x2052267b,0x24522a7a,0xb012af0c,0xb402b2f7,
0x2c792d2a,0x30743122,0xa4209d7f,0xa81fa17f,0x2a312b91,0x2e2d2f8b,0xa8d0a6e0,0xacceaade,0x26e028d0,0x2ade2cce,0xab91aa31,0xaf8bae2d,
0x1d7f2420,0x217f281f,0xad2aac79,0xb122b074,0x27a9286b,0x2ba72c6a,0x9f1298b6,0xa3119cb6,0x254d267b,0x294d2a7a,0xa420a1e4,0xa81fa5e4,
0x21e42420,0x25e4281f,0xa67ba54d,0xaa7aa94d,0x18b61f12,0x1cb62311,0xa86ba7a9,0xac6aaba7,0x3f803f80,0x3f803f80,0x3f803f80,0x3f803f80,
0x3f803f80,0x3f803f80,0x3f803f80,0x3f803f80,0x3f803f80,0x3f803f80,0x3f803f80,0x3f803f80,0x3f803f80,0x3f803f80,0x3f803f80,0x3f803f80,
0x3f803f80,0x3f803f80,0x3f803f80,0x3f803f80,0x3f803f80,0x3f803f80,0x3f803f80,0x3f803f80,0x3f803f80,0x3f803f80,0x3f803f80,0x3f803f80,
0x3f803f80,0x3f803f80,0x3f803f80,0x3f803f80,0x3f803f80,0x3f803f80,0x3f803f80,0x3f803f80,0x3f803f80,0x3f803f80,0x3f803f80,0x3f803f80,
0x3f803f80,0x3f803f80,0x3f803f80,0x3f803f80,0x3f803f80,0x3f803f80,0x3f803f80,0x3f803f80,0x3f803f80,0x3f803f80,0x3f803f80,0x3f803f80,
0x3f803f80,0x3f803f80,0x3f803f80,0x3f803f80,0x3f803f80,0x3f803f80,0x3f803f80,0x3f803f80,0x3f803f80,0x3f803f80,0x3f803f80,0x3f803f80,
0x3f803f80,0x3f803f80,0x3f803f80,0x3f803f80,0x3f803f80,0x3f803f80,0x3f803f80,0x3f803f80,0x3f803f80,0x3f803f80,0x3f803f80,0x3f803f80,
0x3f803f80,0x3f803f80,0x3f803f80,0x3f803f80,0x3f803f80,0x3f803f80,0x3f803f80,0x3f803f80,0x3f803f80,0x3f803f80,0x3f803f80,0x3f803f80,
0x3f803f80,0x3f803f80,0x3f803f80,0x3f803f80,0x3f803f80,0x3f803f80,0x3f803f80,0x3f803f80,0x3f803f80,0x3f803f80,0x3f803f80,0x3f803f80,
0x3f803f80,0x3f803f80,0x3f803f80,0x3f803f80,0x3f803f80,0x3f803f80,0x3f803f80,0x3f803f80,0x3f803f80,0x3f803f80,0x3f803f80,0x3f803f80,
0x3f803f80,0x3f803f80,0x3f803f80,0x3f803f80,0x3f803f80,0x3f803f80,0x3f803f80,0x3f803f80,0x3f803f80,0x3f803f80,0x3f803f80,0x3f803f80,
0x3f803f80,0x3f803f80,0x3f803f80,0x3f803f80,0x3f803f80,0x3f803f80,0x3f803f80,0x3f803f80,0x3f803f80,0x3f803f80,0x3f803f80,0x3f803f80,
0x3f803f80,0x3f803f80,0x3f803f80,0x3f803f80,0x3f803f80,0x3f803f80,0x3f803f80,0x3f803f80,0x3f803f80,0x3f803f80,0x3f803f80,0x3f803f80,
0x3f803f80,0x3f803f80,0x3f803f80,0x3f803f80,0x3f803f80,0x3f803f80,0x3f803f80,0x3f803f80,0x3f803f80,0x3f803f80,0x3f803f80,0x3f803f80,
0x3f803f80,0x3f803f80,0x3f803f80,0x3f803f80,0x3f803f80,0x3f803f80,0x3f803f80,0x3f803f80,0x3f803f80,0x3f803f80,0x3f803f80,0x3f803f80,
0x3f803f80,0x3f803f80,0x3f803f80,0x3f803f80,0x3f803f80,0x3f803f80,0x3f803f80,0x3f803f80,0x3f803f80,0x3f803f80,0x3f803f80,0x3f803f80,
0x3f803f80,0x3f803f80,0x3f803f80,0x3f803f80,0x3f803f80,0x3f803f80,0x3f803f80,0x3f803f80,0x3f803f80,0x3f803f80,0x3f803f80,0x3f803f80,
0x3f803f80,0x3f803f80,0x3f803f80,0x3f803f80,0x3f803f80,0x3f803f80,0x3f803f80,0x3f803f80,0x3f803f80,0x3f803f80,0x3f803f80,0x3f803f80,
0x3f803f80,0x3f803f80,0x3f803f80,0x3f803f80,0x3f803f80,0x3f803f80,0x3f803f80,0x3f803f80,0x3f803f80,0x3f803f80,0x3f803f80,0x3f803f80,
0x3f803f80,0x3f803f80,0x3f803f80,0x3f803f80,0x3f803f80,0x3f803f80,0x3f803f80,0x3f803f80,0x3f803f80,0x3f803f80,0x3f803f80,0x3f803f80,
0x3f803f80,0x3f803f80,0x3f803f80,0x3f803f80,0x3f803f80,0x3f803f80,0x3f803f80,0x3f803f80,0x3f803f80,0x3f803f80,0x3f803f80,0x3f803f80,
0x3f803f80,0x3f803f80,0x3f803f80,0x3f803f80,0x3f803f80,0x3f803f80,0x3f803f80,0x3f803f80,0x3f803f80,0x3f803f80,0x3f803f80,0x3f803f80,
0x3f803f80,0x3f803f80,0x3f803f80,0x3f803f80,0x3f803f80,0x3f803f80,0x3f803f80,0x3f803f80,0x3f803f80,0x3f803f80,0x3f803f80,0x3f803f80,
0x3f803f80,0x3f803f80,0x3f803f80,0x3f803f80,0x3f803f80,0x3f803f80,0x3f803f80,0x3f803f80,0x3f803f80,0x3f803f80,0x3f803f80,0x3f803f80,
0x3f803f80,0x3f803f80,0x3f803f80,0x3f803f80,0x3f803f80,0x3f803f80,0x3f803f80,0x3f803f80,0x3f803f80,0x3f803f80,0x3f803f80,0x3f803f80,
0x3f803f80,0x3f803f80,0x3f803f80,0x3f803f80,0x3f803f80,0x3f803f80,0x3f803f80,0x3f803f80,0x3f803f80,0x3f803f80,0x3f803f80,0x3f803f80,
0x3f803f80,0x3f803f80,0x3f803f80,0x3f803f80,0x3f803f80,0x3f803f80,0x3f803f80,0x3f803f80,0x3f803f80,0x3f803f80,0x3f803f80,0x3f803f80,
0x3f803f80,0x3f803f80,0x3f803f80,0x3f803f80,0x3f803f80,0x3f803f80,0x3f803f80,0x3f803f80,0x3f803f80,0x3f803f80,0x3f803f80,0x3f803f80,
0x3f803f80,0x3f803f80,0x3f803f80,0x3f803f80,0x3f803f80,0x3f803f80,0x3f803f80,0x3f803f80,0x3f803f80,0x3f803f80,0x3f803f80,0x3f803f80,
0x3f803f80,0x3f803f80,0x3f803f80,0x3f803f80,0x3f803f80,0x3f803f80,0x3f803f80,0x3f803f80,0x3f803f80,0x3f803f80,0x3f803f80,0x3f803f80,
0x3f803f80,0x3f803f80,0x3f803f80,0x3f803f80,0x3f803f80,0x3f803f80,0x3f803f80,0x3f803f80,0x3f803f80,0x3f803f80,0x3f803f80,0x3f803f80,
0x3f803f80,0x3f803f80,0x3f803f80,0x3f803f80,0x3f803f80,0x3f803f80,0x3f803f80,0x3f803f80,0x3f803f80,0x3f803f80,0x3f803f80,0x3f803f80,
0x3f803f80,0x3f803f80,0x3f803f80,0x3f803f80,0x3f803f80,0x3f803f80,0x3f803f80,0x3f803f80,0x3f803f80,0x3f803f80,0x3f803f80,0x3f803f80,
0x3f803f80,0x3f803f80,0x3f803f80,0x3f803f80,0x3f803f80,0x3f803f80,0x3f803f80,0x3f803f80,0x3f803f80,0x3f803f80,0x3f803f80,0x3f803f80,
0x3f803f80,0x3f803f80,0x3f803f80,0x3f803f80,0x3f803f80,0x3f803f80,0x3f803f80,0x3f803f80,0x3f803f80,0x3f803f80,0x3f803f80,0x3f803f80,
0x3f803f80,0x3f803f80,0x3f803f80,0x3f803f80,0x3f803f80,0x3f803f80,0x3f803f80,0x3f803f80,0x3f803f80,0x3f803f80,0x3f803f80,0x3f803f80,
0x3f803f80,0x3f803f80,0x3f803f80,0x3f803f80,0x3f803f80,0x3f803f80,0x3f803f80,0x3f803f80,0x3f803f80,0x3f803f80,0x3f803f80,0x3f803f80,
0x3f803f80,0x3f803f80,0x3f803f80,0x3f803f80,0x3f803f80,0x3f803f80,0x3f803f80,0x3f803f80,0x3f803f80,0x3f803f80,0x3f803f80,0x3f803f80,
0x3f803f80,0x3f803f80,0x3f803f80,0x3f803f80,0x3f803f80,0x3f803f80,0x3f803f80,0x3f803f80,0x3f803f80,0x3f803f80,0x3f803f80,0x3f803f80,
0x3f803f80,0x3f803f80,0x3f803f80,0x3f803f80,0x3f803f80,0x3f803f80,0x3f803f80,0x3f803f80,0x3f803f80,0x3f803f80,0x3f803f80,0x3f803f80,
0x3f803f80,0x3f803f80,0x3f803f80,0x3f803f80,0x3f803f80,0x3f803f80,0x3f803f80,0x3f803f80,0x3f803f80,0x3f803f80,0x3f803f80,0x3f803f80,
0x3f803f80,0x3f803f80,0x3f803f80,0x3f803f80,0x3f803f80,0x3f803f80,0x3f803f80,0x3f803f80,0x3f803f80,0x3f803f80,0x3f803f80,0x3f803f80,
0x3f803f80,0x3f803f80,0x3f803f80,0x3f803f80,0x3f803f80,0x3f803f80,0x3f803f80,0x3f803f80,0x3f803f80,0x3f803f80,0x3f803f80,0x3f803f80,
0x3f803f80,0x3f803f80,0x3f803f80,0x3f803f80,0x3bf23bff,0x3ba53bd4,0x3b163b65,0x3a493ab6,0x3b7c3bfb,0x38bc3a60,0x2b43356a,0xb7f3b359,
0x3a933bf1,0x9cb63764,0xba9eb785,0xbb73bbf3,0x39463be2,0xb8cc28e8,0xbb42bbc2,0x3328b70a,0x374e3bcf,0xbbabb648,0xaec3baa9,0x3bfa3994,
0x33403bb7,0xbb85b9fc,0x3a64b0be,0x2c6a3b47,0xa4523b9a,0xb86abbae,0x3b6a3911,0xbbd0ad65,0xb4263b78,0x2adebbe6,0x30f03bfd,0xb5b1bbbc,
0x2f5925e4,0x34b73294,0x376f361a,0x38f3385a,0x35a52c9c,0x3a7338d6,0x3bfd3b87,0x3af13bc9,0x388e2fbd,0x3c003b18,0x387f3b10,0xb5d42f27,
0x3a04316c,0x3a673bfe,0xb6bb33d3,0xbbccbb2f,0x3b1e32f7,0x34933b5c,0xbbf5b86f,0x2d00b9bc,0x3bcb343e,0xb576394f,0xb8d1bbe9,0x3bfb36a4,
0x3c0034ff,0xbaac347b,0x3602ba31,0x32de3bf9,0x3bba35bc,0xbbfdb109,0x3be7aa7a,0xbb7a341a,0x394639cd,0x381538b2,0x358136dd,0x3153341a,
0xbb1eb9c9,0xbbf5bbdd,0xba39bb65,0xb4f3b889,0xb340b93c,0x3966340e,0x3bec3b87,0x37213a7e,0x3c003a4d,0x32193a21,0xbb5eb785,0xb894bbb0,
0xb426389e,0xbb37bb45,0x38b7b3d3,0x397d3bfc,0xbafebac1,0x3b13217f,0xadc93aa9,0xba49bb59,0x3979b7e8,0xb0d73b32,0xb6f4bbe9,0x3af139da,
0x38553b24,0xb9a1ba3d,0x3ab03911,0xbb73b759,0x3a043982,0x3ae13a7a,0x3b833b3a,0x3be33bbc,0x374e3986,0xae9131e8,0xb907b61a,0xbb9cba97,
0xbbcbba0d,0xb9e7bbbd,0x3074b56a,0x3b2a38ad,0x2452b8ee,0x3bda3924,0x363c3b10,0xba90b46f,0x3bba3a89,0xb6e836af,0xba76bbc2,0x39d2ac06,
0xb7c8384a,0xb77abc00,0x3bf8386f,0xb8f33654,0xb9d6baf4,0x3be836ff,0xbb3530be,0x37f3b974,0x3abab737,0xb9af3902,0x3865ba31,0xb5d43b1b,
0x32c62fbd,0x363134cf,0x38653785,0x398b38fd,0xb715b16c,0xbae1b970,0xbbfebbc2,0xba85bb92,0x392e32f7,0x3bf53b6c,0x37a63aa9,0xb7422311,
0xba81b43e,0xb9e7bbfc,0x380fb0be,0x3b963b7f,0x3b7134ff,0x32193b04,0xbc00b911,0x319eb929,0xbbefb5bc,0x36e8b8b2,0x382a3bfd,0xbbffb805,
0x3bf23676,0xbb1331e8,0x376fb9aa,0x2f8b3bde,0xbb7cb72c,0x3be8340e,0xbbfdaa16,0x3bb8b122,0xbbd2bbf1,0xbb60bba1,0xbab0bb10,0xb9c5ba41,
0x3b2c3be2,0x381539df,0xa94d33d3,0xb8a3b52f,0xba19bbcf,0x2e91b5f7,0x3b07386f,0x3b213c00,0x38a83bb7,0xb966aba7,0xbae5bbe9,0x3517b599,
0xb5dfbb9a,0x3bda37b2,0x1fdb3a31,0xbbe0ba1d,0x30293b78,0xbb37ba7a,0x3ad5aa7a,0xa7763aeb,0x2f59bb52,0x377a3bdd,0xbb16b9a6,0x3bf231cf,
0xb5a53b27,0x30d7bbbd,0x2b433bfe,0xb432bbe5,0x3a813a0d,0x3b3f3ae8,0x3bbf3b87,0x3bfb3be5,0xb5dfb8ee,0x3263ad97,0x399d3785,0x3bd03b01,
0xbbefba89,0xb958bb81,0x3389b3d3,0x3b7a394a,0xaf59384a,0xbbf7b9b8,0xb4c3baa9,0x3afb35eb,0x3b7c3af4,0xb825353a,0xb9f8bbe9,0x3a542884,
0x388eb737,0x360e3bf4,0xbbdcb911,0x398bb4db,0xb946bb4f,0x3bc03830,0xbb832a7a,0x38a3b8db,0xbb1e35c8,0x3a35b85f,0xb90739aa,0x3742bab6,
0xb8a8b93c,0xb6c6b80a,0xb402b56a,0xac6ab122,0xbb71ba4d,0xbbd7bbf8,0xb9b3bb10,0xb2deb7bd,0x3029389e,0xb9f4b58d,0xbbc6bbc2,0xb5b1ba00,
0x3bf23ac1,0x2dfb3999,0xbba3b86f,0xb7d2bb6f,0x35a5b7e8,0x3ad83b90,0xb95430be,0xb8e5bbff,0xba93bb24,0x3b682ef5,0xb2013a31,0xb9c5bb9f,
0xba043682,0x33ebbad1,0x35813bfd,0xba85ba5c,0x374e3b76,0xb90cbab3,0x3a3939a6,0xbb21b85a,0xb7c83b52,0x391bba9b,0xba2539aa,0x3afbb889,
0xb9793b27,0x3bc5b80a,0xbb8eaa16,0x38e538ad,0xbaba3af7,0x3b60ad97,0xb27cba2d,0xb98b3bb0,0xbb943ac4,0x3815358d,0x39e3bbea,0xba852c06,
0xbbf93a8c,0xae9139b8,0x3bacb874,0x3742bb59,0xbbe43a50,0xb9663b90,0x340233ba,0x3b96b974,0xbb573a11,0xbbda3bf4,0xb99d3b0d,0xb19e3759,
0xba5839cd,0xbb373ad1,0xbbc63b89,0xbbff3bee,0x3afe3676,0xba29b884,0x391f39a6,0xb7d2ba97,0x39d6372c,0xb3a2bae8,0xb5463bfe,0x3a54ba7e,
0x385537dd,0x3631bbf8,0xbbd63916,0x39c5346f,0x35233845,0x3ae1bb81,0xb96bb0a6,0xb8a33bfc,0x2d333899,0x3bf5b999,0x3487baa5,0xbb213654,
0xb13b38ea,0x39e7b53a,0x3bbfbbc3,0x3517b9da,0xb65f3937,0x32192ef5,0x39b3b790,0x3be0bb1b,0xb8e03982,0xb6e83830,0xb389355e,0xa7763042,
0xbb943682,0x3bebb371,0xbbfe2a7a,0x3bcc3042,0xad33bb76,0xb79b3bd4,0x3b07b9aa,0xbbfa32ad,0x3be4b50b,0xb6c6b8d6,0xb80f3bfe,0x3bfbb835,
0xb65f3bb5,0x3bd7b764,0x9fdbba2d,0xbbd03a41,0xba58330f,0xb9f43bfe,0x382a30a6,0x3b7abb92,0x3a45bbe1,0xadfbb648,0xbb163874,0xbafb3c00,
0x3699afef,0x3ad8b94f,0x3bfdbbc3,0x3a54bb7f,0xbbdf3bfa,0xbb683bae,0xba9e3b0d,0xb98b3a1d,0x35233b4f,0xb08dbbc8,0xa94d3bfd,0x3328bbee,
0xbbf935c8,0x3b0a3294,0xb7a6b9a6,0xad003bd3,0x313bbb98,0xbb3f3a60,0x3ae52a16,0xac6abace,0x3b57b44b,0x3263bb18,0xbc003916,0x32de38fd,
0xb8e03bce,0x3958a8e8,0x3ad5bbea,0xb5b1b52f,0xb8f83185,0xbbf73b5c,0xb76f3aa5,0x37d2a311,0x3b4abbf0,0x3825b9fc,0xab43b3ba,0xb8e53599,
0x31b6acce,0x360eb47b,0x387fb790,0x39c5b929,0x3a9337dd,0xb9a1b924,0x387f3a2d,0xb66bbb01,0xb946b845,0x308d3b45,0x36bbbbea,0xbac73a00,
0x374e3899,0x379bbc00,0xbbf53874,0x393335eb,0xb340b8ea,0xbb3f3b32,0x38d133ba,0x3941bbff,0xa4523937,0x3bd7b902,0x3602bb0d,0xbabd34db,
0x3426b982,0xb9583371,0xbbe73b89,0xb68d3a5c,0xb7c839c9,0x2dfb3294,0x391fb625,0x3bb3bab6,0x3979ba0d,0x3825b8d6,0x3546b6d2,0x3010b359,
0x388ebaf7,0xb9af3a21,0x3a9eb916,0xbb5437bd,0xba043ac4,0x3bebb6af,0xbb42b0a6,0x3840394a,0x3b1eba8c,0xbb0aa17f,0x2ec33aa5,0x3a15bb6f,
0xbbcb3a50,0x36c636ff,0x3a64bbc3,0xba09a884,0x3c00ba11,0x3263ba3d,0xbb6a3790,0xb8503b9f,0xbbba39cd,0xb9f43bc8,0x30f0355e,0x3b4cb8db,
0x3afeb986,0x3bf7bbd4,0x3a25bb63,0x3457b85a,0xb9d6393c,0xbad83a60,0xbb8e3b3d,0xbbef3bc9,0x33403b98,0xa9b1bbed,0xb0743bfe,0x3517bbc9,
0x3c00b44b,0xbaa2b4cf,0x363c3a2d,0x319ebbf3,0x3426bbce,0xbb8b39df,0x3a7630a6,0x2776bb2f,0xbafe3185,0xb4b73b6c,0x3bf8b874,0xaf8bb994,
0xb9793bf0,0x38bc2ba7,0x3b35bbc3,0xb432b6a4,0x3855acce,0x3c00bb04,0x3865bb0d,0xb66bad65,0x3b94bbff,0x38ccba7a,0x294db55e,0xb840341a,
0xad33a5e4,0xb49331e8,0xb7a63625,0xb9333889,0x3bcbb50b,0xbbfe305b,0x3bec2a16,0xbb96b359,0x2452bbb5,0xb87a3ba1,0x3b5eb916,0xbbe02f27,
0xbbba330f,0x35523970,0x38b7bbea,0xbbff370a,0xb7c83be1,0x3ba5b5f7,0x2dc9baa5,0xbbf239bc,0x39d6afef,0x3a73bbfc,0xb6f4b3ba,0xbbb83b47,
0x3ababbfa,0x1cb6b7b2,0xbab03790,0xbb543bf9,0xb52326ad,0xba6738b2,0xbbfe3b89,0xbac73bbc,0xbbf93bff,0xbbab3bdd,0xbb073b63,0xba153a97,
0xb8f83986,0xb77a385f,0xb4c33625,0xaf8b32ad,0xb699393c,0x30d7305b,0x3954b6d2,0x3bb8bace,0xb1b638ee,0x39afb4cf,0x3bdcbba7,0x366bba41,
0x2c38389e,0x3bebb970,0x3581bade,0xbac7352f,0x34e7384a,0x3b0abb6c,0xb907b24b,0xb9333c00,0x383a37e8,0x36c6bbfc,0xbbec38c1,0x39413599,
0x39c03737,0xb263bb04,0xb63c3bf6,0x3abdba1d,0x3aee3682,0xb9f4b8b2,0x38b739f0,0xb68dbaeb,0xba4539c9,0xbb133ab3,0xbba33b63,0xbbf23bd3,
0xbb4a3a0d,0xbbe83bed,0xb9f83b3d,0xb4323835,0xbbdf3a4d,0xb9a13ba1,0x320134ab,0x3b54b8fd,0xbbfc3a89,0xb08d39df,0x3b83b81a,0x3840bb92,
0xbb9e3ac1,0x379b35f7,0x3a39bbd8,0xba15a311,0xbacb3af4,0x3b3faba7,0xb074ba6f,0xba093b7f,0xb9903b24,0x3bd7b7b2,0xbb5eae5f,0x38503929,
0xb7fe3b4f,0x3958ba7a,0xba76395d,0x3b4cb805,0x2c3826ad,0x33ebb109,0x36bbb55e,0x38a3b805,0x3b9ebbff,0x390cba9b,0x2ec3b625,0xb74231cf,
0xb83a2c9c,0xbbfe3ae8,0xb8d13b3d,0x35173122,0xb9903bf1,0x387a2d97,0x3b6abba7,0xb19eb7bd,0x3aeeb16c,0x3552bb81,0xbbe7381a,0x27763a00,
0x3463bbcf,0xbba539b8,0x3a25324b,0x2f8bbb6f,0xbbff343e,0x3a73353a,0xb546ba6f,0xb4323bff,0x32c63b9a,0x9cb6bbf4,0xb27c3bf6,0x366bbb9f,
0xbbfc3bff,0xbbc03be6,0xbb423b89,0xba853aeb,0x34e7a5e4,0x3a35b884,0x3bf5bb63,0x3b21bbde,0x3acbbbfb,0x29b1b80a,0xba6436d2,0xbb963be5,
0xb9c02fbd,0xbaa23bf8,0x360234ab,0x3be0bb01,0xb7fe3be2,0x3b8bb58d,0x30f0bade,0xbbff394a,0x3bb2b2f7,0xb4b7b999,0xb91f3bd8,0x3bf2b5eb,
0x281fbbb7,0xb8bc3b90,0x3b8eb8c1,0xbbb82884,0xbbd234ff,0x3c00aef5,0xbbd6ae5f,0x3b5434db,0xbaba3a4d,0xbb683b18,0xbbd63ba7,0xbc003bf3,
0x3b94ba89,0x3bc0bbfe,0x396bbade,0x3153b70a,0xbbf93ac1,0xb90c3b5c,0x3487324b,0x3b9cb994,0x3be4baf4,0x29b1b94f,0xbbbf38c1,0xb7213b47,
0xbb573b24,0x387a347b,0x39b3bbf6,0xba902d65,0x3a58bb4f,0xbb8b3109,0x338939f0,0x397dbbbc,0xb8f83b76,0x3ba5b884,0xbba39648,0x38f33889,
0x3699bb98,0xb8bc3ae8,0x39f8b9eb,0xbaf138ad,0x3855b8ee,0x360eb764,0x327cb4ab,0x251baf27,0xb523389e,0x33eb28e8,0x39e3b81a,0x3be3bb2f,
0x2d33b84a,0xba353648,0xbbac3bd8,0xb4f339bc,0x313b37e8,0x3bfeb9fc,0x3402ba6f,0xbb2a36a4,0xb65fb737,0xbaa23bae,0x399d2e5f,0x3894bbf9,
0x38e03682,0x3552bbe6,0xbbc6395d,0x39d2341a,0xba45b5c8,0x34b73a9b,0x34c3bc00,0xba493a97,0x3b4a350b,0xba73b80a,0x39543962,0xb7f3ba7e,
0xbbe43bfb,0xbb853bbd,0xbae53b3d,0xba093a7e,0xb65f2fbd,0xbaac3924,0xbc003ba7,0xbabd3bb0,0x3a58bbe2,0xaadeb6af,0xbad5381a,0xbb4c3bfc,
0x3a45b2f7,0x3a29bc00,0xb76fb24b,0xbbb33b59,0xb6993bb7,0x3bc5b6ff,0x2b43ba6f,0xbbef39da,0xbbdf34ff,0x36313902,0x387fbbf6,0xbc003759,
0xac38bb78,0xb8153bc8,0x3b42b95d,0xbbe33042,0x3b9eb676,0xbbf53294,0x3bf51648,0xbb9cb2ad,0xb13b2c9c,0xb576340e,0xb80f36d2,0xb94138ad,
0x3b57bbf1,0x386aba21,0x1fdbb4ab,0xb850346f,0x38e0b16c,0x3bfdbb45,0x382abade,0xb68dac06,0xb8f83bcf,0x391ba17f,0x3b16bbd8,0xb457b654,
0xbb4a343e,0xb3a23b32,0x3bfdb8c1,0xb010b974,0x31b6bb9a,0xbb603a3d,0x3a9e2e5f,0x251bbb1b,0x3bfcb5bc,0xbae1b371,0x36bb39f0,0x3153bbee,
0x34e73b52,0xae91bbd4,0xaec33c00,0x34f3bbd3,0x3bb235c8,0xbbf7b1e8,0x3bf81648,0xbbb331cf,0x3bff350b,0xbad8340e,0x36f4b9eb,0x30103be5,
0x3bd2344b,0xb60e3924,0xb865bbf6,0x3c0037bd,0x3b2c330f,0x33eb3b45,0xbbfeb8c7,0x3153b94a,0x3a193185,0x3a353c00,0xb7a63232,0xbb9cbb6f,
0x38a82fef,0x3bfe3b32,0x380f3adb,0xb7212884,0x35df2cce,0x3aa23902,0x3c003ba9,0x3a903b9f,0x302926ad,0x35523371,0x382a36dd,0x397d38db,
0xb4633b76,0x2dfbbbdd,0x2dc93c00,0xb457bbde,0xa81f3b98,0xb825bbbd,0x3b353962,0xbbefb122,0x32c63bb5,0xbb68ba21,0x3ab0ae2d,0xa51b3b01,
0x37153bce,0xbbc0b6af,0xa94dba6b,0x3be33a00,0x392e3be1,0xb90c217f,0xbb07bbd9,0x34f3b5eb,0x3a813bf0,0xa9b136ff,0xbae5b820,0xbb2abbff,
0x3b713bfa,0x387a3a3d,0x9fdb349f,0xb894b4db,0x3bef3bff,0x3b8b3bc8,0x3ad53b3a,0x39d23a5c,0x3b2cb5bc,0xba673830,0x396bb95d,0xb8403a5c,
0xb92ebb52,0x3bab385f,0xbbac9648,0x3933b85a,0xb8a8372c,0xb576bbed,0x3bbf3962,0xba093359,0x3b713af7,0xb86a34cf,0xb99dbbf6,0x3abd2f27,
0x3029b845,0x3bfd39df,0x33893a6b,0xbb4cb70a,0xbbf2ba8c,0xb91bbb6c,0x34c3b232,0x3bb339bc,0x35a538ea,0xb3a22ba7,0xb9f8b820,0xbbefbb47,
0x3a933a11,0x3b603b04,0x3bdc3ba9,0x3c003bf9,0x37153b78,0xb8ccbad1,0x39e339f0,0xbac7b8db,0x3a19b676,0xb4933ab3,0xb487bc00,0x3a153ab6,
0xba81bb27,0x3b85305b,0xb40239eb,0xb941bbc9,0xb5df37dd,0xbaacbba1,0x39b3ae2d,0x38503bf3,0x3bef3ac4,0x2ade3970,0xbbc6b8c7,0xb68dbb2f,
0xaf59b899,0x3a2935f7,0x3ba33bd9,0x34573994,0xbb7cba50,0xbbc5bbfc,0xb954badb,0xb010b6a4,0x388e3937,0x363137b2,0x3201349f,0xa51b2d65,
0xb1b63bb5,0x9cb6bbf8,0x32013bf6,0xb5d4bbb0,0xac38bbce,0x38cc3b81,0xbb83b8c7,0x3bcc2c06,0x34e73be1,0xbbabb999,0x3a39b232,0x2d003b59,
0xb83abbf0,0x3b85353a,0x30743adb,0xbbfbb974,0x39c03bfa,0xb86a2ef5,0xbb5ebba9,0x32deb759,0xbaeebbff,0xaadeb830,0x3a7636dd,0x3b7a3bee,
0x3bb23bff,0x391b3ab3,0x2dc9361a,0xb7d2b2ad,0xbbffbbfb,0xbbc5bbed,0xbb35bb87,0xba54bace,0xbbdfb44b,0x3c002d97,0xbbdc2e2d,0x3b73b46f,
0x3bfc330f,0xba67358d,0x3581ba6b,0x33283bfc,0xbb9eb185,0x3493b9b8,0x39073bd9,0xbbfab654,0x3acb2fef,0x35763b90,0xbbecb820,0x2c6ab9da,
0xb990acce,0xbaacbbf4,0x363cb49f,0x3bd03b1b,0x37fe26ad,0x3bfd3ad1,0x38b73b3a,0xb5b13042,0xb46325e4,0xba29b85f,0xbbf8bb65,0xbafbbbd3,
0x281fac9c,0x33a2305b,0x36f4356a,0x38e53835,0x383a3b27,0xb966ba60,0x3a643962,0xbb2ab835,0xb99037dd,0x3219bb18,0x36023bf6,0xba90ba41,
0xbaeebac4,0x3b3728e8,0xb0f03a6b,0xb9d2bb92,0x3463b899,0x3b133b5c,0xb91f3232,0xb8f3bc00,0x3bff3a50,0x30d739fc,0xbb8eb820,0xb7f3bb7f,
0x32c63937,0xb9a1b47b,0xbbd6bba9,0xb5d4ba1d,0xbb2cb9cd,0xbbebbbe6,0xb9e3bb3a,0xb328b805,0xb92eb9c9,0xb79bb884,0xb487b61a,0xad00b1cf,
0xbacb372c,0x39e7b8d6,0xb8d139eb,0x3721bace,0xb9c0baf7,0x3bda3764,0xbb6a2e2d,0x3894b8fd,0x37feb845,0x36e83bfe,0xbbe7b8c7,0x397db52f,
0x3bb23a8c,0xb77a3648,0xba25bbd9,0x3a492311,0xa81f38ea,0xbbe8b94f,0xb546badb,0x3af13599,0xbbd2ba11,0xb9afbbae,0x327cb49f,0x3b733929,
0xb715b982,0x308db109,0x396b36dd,0x3bcc3aeb,0x3a193986,0x3b0a3a9b,0x3bac3b65,0x3bfa3bde,0x30003000,0x30003000,0x30003000,0x30003000,
0x2f643000,0x2a1f2da8,0xaa1f0000,0xaf64ada8,0x2da83000,0xada80000,0xada8b000,0x2da88000,0x2a1f3000,0xaf64ada8,0x2f648000,0xaa1f2da8,
0x00003000,0x8000b000,0x00003000,0x8000b000,0xaa1f3000,0x2f64ada8,0xaf640000,0x2a1f2da8,0xada83000,0x2da88000,0x2da8b000,0xada80000,
0xaf643000,0xaa1f2da8,0x2a1f8000,0x2f64ada8,0x30003000,0x30003000,0x30003000,0x30003000,0xaf64b000,0xaa1fada8,0x2a1f8000,0x2f642da8,
0x2da83000,0xada80000,0xada8b000,0x2da88000,0xaa1fb000,0x2f642da8,0xaf640000,0x2a1fada8,0x00003000,0x8000b000,0x00003000,0x8000b000,
0x2a1fb000,0xaf642da8,0x2f648000,0xaa1fada8,0xada83000,0x2da88000,0x2da8b000,0xada80000,0x2f64b000,0x2a1fada8,0xaa1f0000,0xaf642da8,
0x80008000,0x80008000,0x80008000,0x80008000,0xaa1f8000,0xaf64ada8,0xaf64b000,0xaa1fada8,0xada88000,0xada8b000,0x2da88000,0x2da83000,
0xaf648000,0x2a1fada8,0x2a1f3000,0xaf64ada8,0xb0008000,0x30008000,0xb0008000,0x30008000,0xaf648000,0x2a1f2da8,0x2a1fb000,0xaf642da8,
0xada88000,0xada83000,0x2da88000,0x2da8b000,0xaa1f8000,0xaf642da8,0xaf643000,0xaa1f2da8,0x80008000,0x80008000,0x80008000,0x80008000,
0x2a1f8000,0x2f642da8,0x2f643000,0x2a1f2da8,0xada88000,0xada8b000,0x2da88000,0x2da83000,0x2f648000,0xaa1f2da8,0xaa1fb000,0x2f642da8,
0xb0008000,0x30008000,0xb0008000,0x30008000,0x2f648000,0xaa1fada8,0xaa1f3000,0x2f64ada8,0xada88000,0xada83000,0x2da88000,0x2da8b000,
0x2a1f8000,0x2f64ada8,0x2f64b000,0x2a1fada8,0xb0003000,0xb0003000,0xb0003000,0xb0003000,0xaf643000,0xaa1f2da8,0x2a1f0000,0x2f64ada8,
0xada83000,0x2da80000,0x2da8b000,0xada88000,0xaa1f3000,0x2f64ada8,0xaf648000,0x2a1f2da8,0x80003000,0x0000b000,0x80003000,0x0000b000,
0x2a1f3000,0xaf64ada8,0x2f640000,0xaa1f2da8,0x2da83000,0xada88000,0xada8b000,0x2da80000,0x2f643000,0x2a1f2da8,0xaa1f8000,0xaf64ada8,
0xb0003000,0xb0003000,0xb0003000,0xb0003000,0x2f64b000,0x2a1fada8,0xaa1f8000,0xaf642da8,0xada83000,0x2da80000,0x2da8b000,0xada88000,
0x2a1fb000,0xaf642da8,0x2f640000,0xaa1fada8,0x80003000,0x0000b000,0x80003000,0x0000b000,0xaa1fb000,0x2f642da8,0xaf648000,0x2a1fada8,
0x2da83000,0xada88000,0xada8b000,0x2da80000,0xaf64b000,0xaa1fada8,0x2a1f0000,0x2f642da8,0x80008000,0x80008000,0x80008000,0x80008000,
0x2a1f8000,0x2f64ada8,0x2f64b000,0x2a1fada8,0x2da88000,0x2da8b000,0xada88000,0xada83000,0x2f648000,0xaa1fada8,0xaa1f3000,0x2f64ada8,
0x30008000,0xb0008000,0x30008000,0xb0008000,0x2f648000,0xaa1f2da8,0xaa1fb000,0x2f642da8,0x2da88000,0x2da83000,0xada88000,0xada8b000,
0x2a1f8000,0x2f642da8,0x2f643000,0x2a1f2da8,0x80008000,0x80008000,0x80008000,0x80008000,0xaa1f8000,0xaf642da8,0xaf643000,0xaa1f2da8,
0x2da88000,0x2da8b000,0xada88000,0xada83000,0xaf648000,0x2a1f2da8,0x2a1fb000,0xaf642da8,0x30008000,0xb0008000,0x30008000,0xb0008000,
0xaf648000,0x2a1fada8,0x2a1f3000,0xaf64ada8,0x2da88000,0x2da83000,0xada88000,0xada8b000,0xaa1f8000,0xaf64ada8,0xaf64b000,0xaa1fada8,
0x00000000,0x00000000,0x00000000,0x00000000,0x2a1f0000,0x2f642da8,0x2f643000,0x2a1f2da8,0x2da80000,0x2da83000,0xada80000,0xada8b000,
0x2f640000,0xaa1f2da8,0xaa1fb000,0x2f642da8,0x30000000,0xb0000000,0x30000000,0xb0000000,0x2f640000,0xaa1fada8,0xaa1f3000,0x2f64ada8,
0x2da80000,0x2da8b000,0xada80000,0xada83000,0x2a1f0000,0x2f64ada8,0x2f64b000,0x2a1fada8,0x00000000,0x00000000,0x00000000,0x00000000,
0xaa1f0000,0xaf64ada8,0xaf64b000,0xaa1fada8,0x2da80000,0x2da83000,0xada80000,0xada8b000,0xaf640000,0x2a1fada8,0x2a1f3000,0xaf64ada8,
0x30000000,0xb0000000,0x30000000,0xb0000000,0xaf640000,0x2a1f2da8,0x2a1fb000,0xaf642da8,0x2da80000,0x2da8b000,0xada80000,0xada83000,
0xaa1f0000,0xaf642da8,0xaf643000,0xaa1f2da8,0x30003000,0x30003000,0x30003000,0x30003000,0x2f643000,0x2a1f2da8,0xaa1f0000,0xaf64ada8,
0x2da83000,0xada80000,0xada8b000,0x2da88000,0x2a1f3000,0xaf64ada8,0x2f648000,0xaa1f2da8,0x00003000,0x8000b000,0x00003000,0x8000b000,
0xaa1f3000,0x2f64ada8,0xaf640000,0x2a1f2da8,0xada83000,0x2da88000,0x2da8b000,0xada80000,0xaf643000,0xaa1f2da8,0x2a1f8000,0x2f64ada8,
0x30003000,0x30003000,0x30003000,0x30003000,0xaf64b000,0xaa1fada8,0x2a1f8000,0x2f642da8,0x2da83000,0xada80000,0xada8b000,0x2da88000,
0xaa1fb000,0x2f642da8,0xaf640000,0x2a1fada8,0x00003000,0x8000b000,0x00003000,0x8000b000,0x2a1fb000,0xaf642da8,0x2f648000,0xaa1fada8,
0xada83000,0x2da88000,0x2da8b000,0xada80000,0x2f64b000,0x2a1fada8,0xaa1f0000,0xaf642da8,0x00000000,0x00000000,0x00000000,0x00000000,
0xaa1f0000,0xaf642da8,0xaf643000,0xaa1f2da8,0xada80000,0xada83000,0x2da80000,0x2da8b000,0xaf640000,0x2a1f2da8,0x2a1fb000,0xaf642da8,
0xb0000000,0x30000000,0xb0000000,0x30000000,0xaf640000,0x2a1fada8,0x2a1f3000,0xaf64ada8,0xada80000,0xada8b000,0x2da80000,0x2da83000,
0xaa1f0000,0xaf64ada8,0xaf64b000,0xaa1fada8,0x00000000,0x00000000,0x00000000,0x00000000,0x2a1f0000,0x2f64ada8,0x2f64b000,0x2a1fada8,
0xada80000,0xada83000,0x2da80000,0x2da8b000,0x2f640000,0xaa1fada8,0xaa1f3000,0x2f64ada8,0xb0000000,0x30000000,0xb0000000,0x30000000,
0x2f640000,0xaa1f2da8,0xaa1fb000,0x2f642da8,0xada80000,0xada8b000,0x2da80000,0x2da83000,0x2a1f0000,0x2f642da8,0x2f643000,0x2a1f2da8,
0xb0003000,0xb0003000,0xb0003000,0xb0003000,0xaf643000,0xaa1f2da8,0x2a1f0000,0x2f64ada8,0xada83000,0x2da80000,0x2da8b000,0xada88000,
0xaa1f3000,0x2f64ada8,0xaf648000,0x2a1f2da8,0x80003000,0x0000b000,0x80003000,0x0000b000,0x2a1f3000,0xaf64ada8,0x2f640000,0xaa1f2da8,
0x2da83000,0xada88000,0xada8b000,0x2da80000,0x2f643000,0x2a1f2da8,0xaa1f8000,0xaf64ada8,0xb0003000,0xb0003000,0xb0003000,0xb0003000,
0x2f64b000,0x2a1fada8,0xaa1f8000,0xaf642da8,0xada83000,0x2da80000,0x2da8b000,0xada88000,0x2a1fb000,0xaf642da8,0x2f640000,0xaa1fada8,
0x80003000,0x0000b000,0x80003000,0x0000b000,0xaa1fb000,0x2f642da8,0xaf648000,0x2a1fada8,0x2da83000,0xada88000,0xada8b000,0x2da80000,
0xaf64b000,0xaa1fada8,0x2a1f0000,0x2f642da8};

constexpr int kThreads = 384;
constexpr int kCtas = 128;

constexpr uint32_t SM_BASE = 1024;
constexpr uint32_t QKV_STAGE = 32768;
constexpr uint32_t SLOT = 16384;
constexpr uint32_t SM_KV = 2 * SLOT;
constexpr uint32_t SM_Q = 3 * SLOT;
constexpr uint32_t SM_SIG = 131072;
constexpr uint32_t SM_STG = 196608;
constexpr uint32_t SM_Y0 = SM_STG;
constexpr uint32_t SM_YT = SM_STG + 16384;
constexpr uint32_t SM_TW = SM_STG + 24576, SM_ONES = SM_TW + 2048, SM_F1 = SM_ONES + 2048, SM_F2 = SM_F1 + 4096;
constexpr uint32_t SM_BAR = SM_F2 + 2048;
constexpr uint32_t SM_SC = SM_BAR + 512;
constexpr uint32_t SM_TOTAL = 232448;
constexpr uint32_t A_SLOTS = 0xB2910, B_SLOTS = 0xA7654;

enum Bar { B_QKV_FULL = 0, B_QKV_EMPTY = 4, B_OUT_FULL = 8, B_OUT_EMPTY = 13, B_QKV_DONE = 18, B_CONV_DONE = 19, B_PREP_FULL = 20,
           B_PREP_EMPTY = 23, B_SIG_READY = 27, B_ZEROED = 28, B_KVP = 29, B_KV_READY = 30, B_O_WRITTEN = 31,
           B_OT_FREE = 33, B_SEG = 35, B_RDY0 = 39, B_RDY1 = 40, B_YIN = 42, B_Y_READY = 45, B_H_FULL = 46, B_FLAGS1 = 26, B_Q_FULL = 49, B_STG_FREE = 41 };

constexpr int KV_SLICE = 640;
constexpr int XCH_BYTES = 11 * 4096;

struct Params {
  CUtensorMap x, w, wk, wo, outa, k, v, q;
  const __nv_bfloat16* shift_k;
  const __nv_bfloat16* ssm_k;
  const __nv_bfloat16* ssm_d;
  const __nv_bfloat16* q_ptr;
  __nv_bfloat16* out_ptr;
  const __nv_bfloat16* wo_ptr;
  int zero;
  uint8_t tile[64];
};

__device__ __align__(128) uint8_t g_xch[kCtas][XCH_BYTES];
__device__ __align__(128) unsigned g_oflag[128 * 32];
__device__ unsigned g_ready, g_epoch[kCtas];

#define TSTAMP(cond, i) do { } while (0)
#define GSTAMP(cond, i) do { } while (0)
#define LOOPSTAMP(id, cond, i) do { } while (0)

constexpr int kSpinLimit = 1 << 17;

DEVI void mbar_init(uint32_t a, uint32_t c) { asm volatile("mbarrier.init.shared::cta.b64 [%0], %1;" :: "r"(a), "r"(c) : "memory"); }
DEVI void mbar_expect(uint32_t a, uint32_t b) { asm volatile("mbarrier.arrive.expect_tx.shared::cta.b64 _, [%0], %1;" :: "r"(a), "r"(b) : "memory"); }
DEVI void mbar_arrive(uint32_t a) { asm volatile("mbarrier.arrive.shared::cta.b64 _, [%0];" :: "r"(a) : "memory"); }
DEVI void mbar_arrive_if(uint32_t a, bool pred) {
  asm volatile("{\n.reg .pred p;\nsetp.ne.b32 p, %1, 0;\n@p mbarrier.arrive.shared::cta.b64 _, [%0];\n}" :: "r"(a), "r"((int)pred) : "memory");
}
DEVI void mbar_wait(uint32_t a, uint32_t parity) {
  asm volatile("{\n.reg .pred p;\n.reg .u32 n;\nmov.u32 n, 0;\nW_LOOP:\n"
               "mbarrier.try_wait.parity.shared::cta.b64 p, [%0], %1;\nadd.u32 n, n, 1;\n"
               "setp.lt.and.u32 p, n, %2, !p;\n@p bra W_LOOP;\n}"
               :: "r"(a), "r"(parity), "n"(kSpinLimit) : "memory");
}
DEVI bool mbar_test(uint32_t a, uint32_t parity) {
  uint32_t ok;
  asm volatile("{\n.reg .pred p;\nmbarrier.test_wait.parity.shared::cta.b64 p, [%1], %2;\nselp.u32 %0, 1, 0, p;\n}" : "=r"(ok) : "r"(a), "r"(parity) : "memory");
  return ok;
}
DEVI bool elect() {
  uint32_t ok;
  asm volatile("{\n.reg .pred p;\nelect.sync _|p, 0xffffffff;\nselp.u32 %0, 1, 0, p;\n}" : "=r"(ok));
  return ok;
}
DEVI void flag_wait(const unsigned* p, unsigned target) {
  int n = 0; unsigned v;
  do {
    asm volatile("ld.acquire.gpu.global.u32 %0, [%1];" : "=r"(v) : "l"(p) : "memory");
  } while ((int)(v - target) < 0 && ++n < kSpinLimit);
}
DEVI void st_relaxed(void* p, uint32_t v) { asm volatile("st.relaxed.gpu.global.b32 [%0], %1;" :: "l"(p), "r"(v) : "memory"); }
DEVI uint32_t ld_relaxed(const void* p) { uint32_t v; asm volatile("ld.relaxed.gpu.global.b32 %0, [%1];" : "=r"(v) : "l"(p) : "memory"); return v; }
DEVI void ld_relaxed4(uint32_t* v, const void* p) {
  asm volatile("ld.relaxed.gpu.global.v4.b32 {%0,%1,%2,%3}, [%4];" : "=r"(v[0]), "=r"(v[1]), "=r"(v[2]), "=r"(v[3]) : "l"(p) : "memory");
}
template <int N> DEVI bool all_arrived(const uint32_t* v) {
  uint32_t m = v[0];
#pragma unroll
  for (int i = 1; i + 1 < N; i += 2) m = __vimax3_u32(m, v[i], v[i + 1]);
  if (N % 2 == 0) m = max(m, v[N - 1]);
  return __all_sync(0xffffffffu, m != 0xffffffffu);
}
DEVI void flag_add(unsigned* p) {
  asm volatile("fence.release.gpu;\nred.relaxed.gpu.global.add.u32 [%0], 1;" :: "l"(p) : "memory");
}
DEVI unsigned load_epoch(int cta) {
  unsigned v; asm volatile("ld.relaxed.gpu.global.u32 %0, [%1];" : "=r"(v) : "l"(&g_epoch[cta]) : "memory"); return v;
}
DEVI void fence_async_smem() { asm volatile("fence.proxy.async.shared::cta;" ::: "memory"); }
DEVI void bar_sync(int id, int n) { asm volatile("bar.sync %0, %1;" :: "r"(id), "r"(n) : "memory"); }
DEVI void cluster_arrive() { asm volatile("barrier.cluster.arrive.relaxed.aligned;" ::: "memory"); }
DEVI void cluster_wait() { asm volatile("barrier.cluster.wait.aligned;" ::: "memory"); }
DEVI void wg_fence() { asm volatile("wgmma.fence.sync.aligned;" ::: "memory"); }
DEVI void wg_commit() { asm volatile("wgmma.commit_group.sync.aligned;" ::: "memory"); }
template <int N> DEVI void wg_wait() { asm volatile("wgmma.wait_group.sync.aligned %0;" :: "n"(N) : "memory"); }
template <int N> DEVI void pin(uint32_t* r) {
#pragma unroll
  for (int i = 0; i < N; i++) asm volatile("" : "+r"(r[i]) :: "memory");
}
template <int N> DEVI void pin(float* r) {
#pragma unroll
  for (int i = 0; i < N; i++) asm volatile("" : "+f"(r[i]) :: "memory");
}

DEVI void sched_fence(int zero, int id) { asm volatile("{\n.reg .pred p;\nsetp.eq.b32 p, %0, %1;\nS_LOOP:\n@p st.volatile.shared.b32 [%0], %0;\n@p bra S_LOOP;\n}" :: "r"(zero), "r"(id + 1) : "memory"); }
DEVI void pin_range(float* r, int i0, int i1) {
#pragma unroll
  for (int i = i0; i < i1; i++) asm volatile("" : "+f"(r[i]) :: "memory");
}
DEVI void keep(uint32_t& x) { asm volatile("" : "+r"(x) :: "memory"); }
DEVI void keep(int& x) { asm volatile("" : "+r"(x) :: "memory"); }
template <class T> DEVI void keep(T*& x) { asm volatile("" : "+l"(x) :: "memory"); }

DEVI void tma2d(uint32_t dst, const CUtensorMap* m, int c0, int c1, uint32_t bar) {
  asm volatile("cp.async.bulk.tensor.2d.shared::cluster.global.mbarrier::complete_tx::bytes [%0], [%1, {%3, %4}], [%2];"
               :: "r"(dst), "l"(m), "r"(bar), "r"(c0), "r"(c1) : "memory");
}
DEVI void tma2d_mc(uint32_t dst, const CUtensorMap* m, int c0, int c1, uint32_t bar) {
  asm volatile("cp.async.bulk.tensor.2d.shared::cluster.global.mbarrier::complete_tx::bytes.multicast::cluster [%0], [%1, {%3, %4}], [%2], %5;"
               :: "r"(dst), "l"(m), "r"(bar), "r"(c0), "r"(c1), "h"((uint16_t)3) : "memory");
}
DEVI void tma3d(uint32_t dst, const CUtensorMap* m, int c0, int c1, int c2, uint32_t bar) {
  asm volatile("cp.async.bulk.tensor.3d.shared::cluster.global.mbarrier::complete_tx::bytes [%0], [%1, {%3, %4, %5}], [%2];"
               :: "r"(dst), "l"(m), "r"(bar), "r"(c0), "r"(c1), "r"(c2) : "memory");
}
DEVI void tma3d_mc(uint32_t dst, const CUtensorMap* m, int c0, int c1, int c2, uint32_t bar) {
  asm volatile("cp.async.bulk.tensor.3d.shared::cluster.global.mbarrier::complete_tx::bytes.multicast::cluster [%0], [%1, {%3, %4, %5}], [%2], %6;"
               :: "r"(dst), "l"(m), "r"(bar), "r"(c0), "r"(c1), "r"(c2), "h"((uint16_t)3) : "memory");
}
DEVI void tma2d_store(const CUtensorMap* m, uint32_t src, int c0, int c1) {
  asm volatile("cp.async.bulk.tensor.2d.global.shared::cta.bulk_group [%0, {%2, %3}], [%1];" :: "l"(m), "r"(src), "r"(c0), "r"(c1) : "memory");
}
DEVI void bulk_load(uint32_t dst, const void* src, uint32_t bytes, uint32_t bar) {
  asm volatile("cp.async.bulk.shared::cluster.global.mbarrier::complete_tx::bytes [%0], [%1], %2, [%3];" :: "r"(dst), "l"(src), "r"(bytes), "r"(bar) : "memory");
}
DEVI void bulk_store(void* dst, uint32_t src, uint32_t bytes) {
  asm volatile("cp.async.bulk.global.shared::cta.bulk_group [%0], [%1], %2;" :: "l"(dst), "r"(src), "r"(bytes) : "memory");
}
DEVI uint32_t peer_addr(uint32_t a, int rank) { uint32_t r; asm("mapa.shared::cluster.u32 %0, %1, %2;" : "=r"(r) : "r"(a), "r"(rank)); return r; }
DEVI void bulk_to_peer(uint32_t dst, uint32_t src, uint32_t bytes, uint32_t bar, int rank) {
  asm volatile("cp.async.bulk.shared::cluster.shared::cta.mbarrier::complete_tx::bytes [%0], [%1], %2, [%3];"
               :: "r"(peer_addr(dst, rank)), "r"(src), "r"(bytes), "r"(peer_addr(bar, rank)) : "memory");
}
DEVI void l2_prefetch(const void* p, uint32_t bytes) {
  asm volatile("cp.async.bulk.prefetch.L2.global [%0], %1;" :: "l"(p), "r"(bytes) : "memory");
}
DEVI void l2_prefetch2d(const CUtensorMap* m, int c0, int c1) {
  asm volatile("cp.async.bulk.prefetch.tensor.2d.L2.global [%0, {%1, %2}];" :: "l"(m), "r"(c0), "r"(c1) : "memory");
}
DEVI void l2_prefetch3d(const CUtensorMap* m, int c0, int c1, int c2) {
  asm volatile("cp.async.bulk.prefetch.tensor.3d.L2.global [%0, {%1, %2, %3}];" :: "l"(m), "r"(c0), "r"(c1), "r"(c2) : "memory");
}
DEVI uint32_t clock32() { uint32_t t; asm volatile("mov.u32 %0, %%clock;" : "=r"(t) :: "memory"); return t; }
DEVI void delay(uint32_t cycles) { const uint32_t t = clock32(); while (clock32() - t < cycles) { } }
DEVI void bulk_commit() { asm volatile("cp.async.bulk.commit_group;" ::: "memory"); }
DEVI void bulk_wait_all() { asm volatile("cp.async.bulk.wait_group 0;" ::: "memory"); }
DEVI void bulk_wait_read() { asm volatile("cp.async.bulk.wait_group.read 0;" ::: "memory"); }
DEVI void prefetch_map(const CUtensorMap* m) { asm volatile("prefetch.tensormap [%0];" :: "l"(m) : "memory"); }
DEVI void arrive_both(uint32_t bar, int lane, bool pred = true) {
  asm volatile("{\n.reg .pred p;\n.reg .b32 r;\nsetp.ne.b32 p, %2, 0;\nmapa.shared::cluster.u32 r, %0, %1;\n@p mbarrier.arrive.shared::cluster.b64 _, [r];\n}"
               :: "r"(bar), "r"(lane & 1), "r"((int)(pred && lane < 2)) : "memory");
}

DEVI uint64_t make_desc(uint32_t off, uint32_t lbo, uint32_t sbo, uint32_t mode) {
  const uint32_t lo = (off >> 4) + (SM_BASE >> 4) + ((lbo >> 4) << 16), hi = (sbo >> 4) | (mode << 30);
  return ((uint64_t)hi << 32) | lo;
}
DEVI uint32_t pack_bf16(float lo, float hi) { uint32_t r; asm("cvt.rn.bf16x2.f32 %0, %1, %2;" : "=r"(r) : "f"(hi), "f"(lo)); return r; }
DEVI uint32_t pack_f16(float lo, float hi) { uint32_t r; asm("cvt.rn.f16x2.f32 %0, %1, %2;" : "=r"(r) : "f"(hi), "f"(lo)); return r; }
DEVI void stsm4(uint32_t addr, uint32_t r0, uint32_t r1, uint32_t r2, uint32_t r3) {
  asm volatile("stmatrix.sync.aligned.m8n8.x4.shared.b16 [%0], {%1,%2,%3,%4};" :: "r"(addr), "r"(r0), "r"(r1), "r"(r2), "r"(r3) : "memory");
}
DEVI void stsm2(uint32_t addr, uint32_t r0, uint32_t r1) {
  asm volatile("stmatrix.sync.aligned.m8n8.x2.shared.b16 [%0], {%1,%2};" :: "r"(addr), "r"(r0), "r"(r1) : "memory");
}
DEVI void stsm4_t(uint32_t addr, uint32_t r0, uint32_t r1, uint32_t r2, uint32_t r3) {
  asm volatile("stmatrix.sync.aligned.m8n8.x4.trans.shared.b16 [%0], {%1,%2,%3,%4};" :: "r"(addr), "r"(r0), "r"(r1), "r"(r2), "r"(r3) : "memory");
}
DEVI void ldsm4(uint32_t* r, uint32_t addr) {
  asm volatile("ldmatrix.sync.aligned.m8n8.x4.shared.b16 {%0,%1,%2,%3}, [%4];" : "=r"(r[0]), "=r"(r[1]), "=r"(r[2]), "=r"(r[3]) : "r"(addr) : "memory");
}
DEVI void ldsm4_t(uint32_t* r, uint32_t addr) {
  asm volatile("ldmatrix.sync.aligned.m8n8.x4.trans.shared.b16 {%0,%1,%2,%3}, [%4];" : "=r"(r[0]), "=r"(r[1]), "=r"(r[2]), "=r"(r[3]) : "r"(addr) : "memory");
}
DEVI uint32_t lds32(uint32_t a) { uint32_t v; asm volatile("ld.shared.b32 %0, [%1];" : "=r"(v) : "r"(a) : "memory"); return v; }
DEVI uint4 lds128(uint32_t a) {
  uint4 v; asm volatile("ld.shared.v4.b32 {%0,%1,%2,%3}, [%4];" : "=r"(v.x), "=r"(v.y), "=r"(v.z), "=r"(v.w) : "r"(a) : "memory"); return v;
}
DEVI uint32_t bmul2(uint32_t a, uint32_t b) { uint32_t r; asm("mul.rn.bf16x2 %0, %1, %2;" : "=r"(r) : "r"(a), "r"(b)); return r; }
DEVI uint32_t bfma2(uint32_t a, uint32_t b, uint32_t c) { uint32_t r; asm("fma.rn.bf16x2 %0, %1, %2, %3;" : "=r"(r) : "r"(a), "r"(b), "r"(c)); return r; }
DEVI float bf_lo(uint32_t w) { return __uint_as_float(w << 16); }
DEVI float bf_hi(uint32_t w) { return __uint_as_float(w & 0xffff0000u); }
DEVI uint32_t elu1(float a0, float a1) {
  constexpr float L = 1.4426950408889634f;
  float e0, e1;
  asm("ex2.approx.ftz.f32 %0, %1;" : "=f"(e0) : "f"(-fabsf(fmaf(a0, L, -L))));
  asm("ex2.approx.ftz.f32 %0, %1;" : "=f"(e1) : "f"(-fabsf(fmaf(a1, L, -L))));
  return pack_bf16(fmaxf(e0, a0), fmaxf(e1, a1));
}
DEVI uint32_t add_eps(uint32_t x) { uint32_t r; asm("add.rn.bf16x2 %0, %1, %2;" : "=r"(r) : "r"(x), "r"(0x35863586u)); return r; }

DEVI uint32_t hmul(uint32_t a, uint32_t b) { uint32_t r; asm("mul.rn.f16x2 %0, %1, %2;" : "=r"(r) : "r"(a), "r"(b)); return r; }
DEVI uint32_t hfma(uint32_t a, uint32_t b, uint32_t c) { uint32_t r; asm("fma.rn.f16x2 %0, %1, %2, %3;" : "=r"(r) : "r"(a), "r"(b), "r"(c)); return r; }
DEVI uint32_t hneg(uint32_t a) { uint32_t r; asm("neg.f16x2 %0, %1;" : "=r"(r) : "r"(a)); return r; }
DEVI uint32_t hadd(uint32_t a, uint32_t b) { uint32_t r; asm("add.rn.f16x2 %0, %1, %2;" : "=r"(r) : "r"(a), "r"(b)); return r; }
DEVI uint32_t hsub(uint32_t a, uint32_t b) { uint32_t r; asm("sub.rn.f16x2 %0, %1, %2;" : "=r"(r) : "r"(a), "r"(b)); return r; }
struct Cx { uint32_t re, im; };
DEVI Cx cmul(Cx a, Cx b) { return {hfma(a.re, b.re, hneg(hmul(a.im, b.im))), hfma(a.re, b.im, hmul(a.im, b.re))}; }
DEVI Cx cfma(Cx a, Cx b, Cx c) { return {hfma(a.re, b.re, hfma(hneg(a.im), b.im, c.re)), hfma(a.re, b.im, hfma(a.im, b.re, c.im))}; }
DEVI Cx rot(Cx a, Cx t) {
  const uint32_t x = hfma(hneg(t.re), a.im, a.re), y = hfma(t.im, x, a.im);
  return {hfma(hneg(t.re), y, x), y};
}
struct Fft {
  uint32_t fa[8];
  Cx tw[2];
  uint32_t vst;
  DEVI void stage1(uint32_t* d1, uint32_t slot) const {
    wg_fence();
    fft1_init(d1, fa[0], fa[1], fa[2], fa[3], make_desc(slot, 4096, 1024, 1));
    fft1_acc(d1, fa[4], fa[5], fa[6], fa[7], make_desc(slot + 2048, 4096, 1024, 1));
    wg_commit();
  }
  DEVI void stage2(uint32_t* d, const Cx* t) const {
    wg_fence();
    fft2_init(d, t[0].re, t[1].re, t[2].re, t[3].re, make_desc(SM_F2, 128, 512, 0));
    fft2_acc(d, t[0].im, t[1].im, t[2].im, t[3].im, make_desc(SM_F2 + 256, 128, 512, 0));
    wg_commit();
  }
  template <int PR> DEVI void fwd(const uint32_t* d1, uint32_t* d2) const {
    Cx t[4];
#pragma unroll
    for (int e = 0; e < 4; e++) {
      const int j = 8 * (PR & 1) + 4 * (e >> 1) + 2 * (PR >> 1) + (e & 1);
      t[e] = rot({d1[2 * j], d1[2 * j + 1]}, tw[e >> 1]);
    }
    stage2(d2 + 8 * PR, t);
  }
  static DEVI Cx U(const uint32_t* d2, int p, int hi) { return {d2[16 * (p >> 1) + 2 * hi + (p & 1)], d2[16 * (p >> 1) + 4 + 2 * hi + (p & 1)]}; }
  static DEVI Cx H(const uint32_t* d2, int p, int hi) { return U(d2 + 8, p, hi); }
  DEVI void prod01(const uint32_t* d2, Cx* p1, uint32_t* d3) const {
    Cx z[4];
#pragma unroll
    for (int hi = 0; hi < 2; hi++) {
      const Cx p0 = cmul(H(d2, 0, hi), U(d2, 0, hi));
      p1[hi] = cfma(H(d2, 1, hi), U(d2, 0, hi), cmul(H(d2, 0, hi), U(d2, 1, hi)));
      z[2 * hi] = {p0.im, p0.re};
      z[2 * hi + 1] = {hsub(p1[hi].im, p0.re), hadd(p1[hi].re, p0.im)};
    }
    stage2(d3, z);
  }
  DEVI void prod23(const uint32_t* d2, const Cx* p1, uint32_t* d3) const {
    Cx z[4];
#pragma unroll
    for (int hi = 0; hi < 2; hi++) {
      const Cx p2 = cfma(H(d2, 2, hi), U(d2, 0, hi), cfma(H(d2, 0, hi), U(d2, 2, hi), cmul(H(d2, 1, hi), U(d2, 1, hi))));
      const Cx z3 = cfma(H(d2, 3, hi), U(d2, 0, hi), cfma(H(d2, 2, hi), U(d2, 1, hi),
                    cfma(H(d2, 1, hi), U(d2, 2, hi), cfma(H(d2, 0, hi), U(d2, 3, hi), {p2.im, hneg(p2.re)}))));
      z[2 * hi] = {hsub(p2.im, p1[hi].re), hadd(p2.re, p1[hi].im)};
      z[2 * hi + 1] = {z3.im, z3.re};
    }
    stage2(d3 + 8, z);
  }
  template <int PB> DEVI void inv(const uint32_t* d3, uint32_t slot) const {
    Cx v[4];
#pragma unroll
    for (int e = 0; e < 4; e++) {
      const int r = 8 * PB + 2 * (e & 1) + (e >> 1);
      v[e] = rot({d3[r], d3[r + 4]}, tw[e & 1]);
    }
    stsm4(slot + (vst ^ (PB * 64)), v[0].im, v[1].im, v[2].im, v[3].im);
    stsm4(slot + 1024 + (vst ^ (PB * 64)), v[0].re, v[1].re, v[2].re, v[3].re);
  }
  DEVI void last(float* dy, uint32_t slot, int wg) const {
    fence_async_smem();
    bar_sync(2 + wg, 128);
    wg_fence();
    fft3_init(dy, make_desc(slot, 4096, 1024, 1), make_desc(SM_F1, 128, 1024, 0));
#pragma unroll
    for (int ks = 1; ks < 4; ks++) fft3_acc(dy, make_desc(slot + ks * 2048, 4096, 1024, 1), make_desc(SM_F1 + ks * 256, 128, 1024, 0));
    wg_commit();
  }
  static DEVI void store_y(const float* dy, uint32_t a) {
    stsm4_t(a, pack_bf16(dy[0], dy[1]), pack_bf16(dy[2], dy[3]), pack_bf16(dy[4], dy[5]), pack_bf16(dy[6], dy[7]));
    stsm4_t(a + 512, pack_bf16(dy[8], dy[9]), pack_bf16(dy[10], dy[11]), pack_bf16(dy[12], dy[13]), pack_bf16(dy[14], dy[15]));
  }
};
DEVI uint32_t normalize(uint32_t* x, uint32_t dst) {
  uint32_t m = x[0];
#pragma unroll
  for (int i = 1; i < 32; i++) asm("max.xorsign.abs.bf16x2 %0, %0, %1;" : "+r"(m) : "r"(x[i]));
  const uint32_t e = min(__reduce_max_sync(0xffffffffu, max(m & 0x7fffu, (m >> 16) & 0x7fffu)) >> 7, 252u);
  if (e > 140) {
#pragma unroll
    for (int i = 0; i < 32; i++) x[i] = bmul2(x[i], 15u * 0x00800080u);
  }
  const uint32_t sc = (e > 140 ? 253u - e : 141u - e) * 0x00800080u;
#pragma unroll
  for (int i = 0; i < 8; i++) {
    uint32_t y[4];
#pragma unroll
    for (int n = 0; n < 4; n++) {
      const uint32_t w = bmul2(x[4 * i + n], sc);
      y[n] = (w & 0x7fff7fffu) * 7u + w;
    }
    stsm4((dst ^ ((i >> 1) << 4)) + (i & 1) * 2048, y[0], y[1], y[2], y[3]);
  }
  return e;
}
#define TAIL 3
#define DBG 0
#define XPF 3
#define PSTART 5
#define HSTART 4
#define PF0 24
#define PPACE 300
#define FDELAY 200
#define PH0 2
#define QA 4
#define QB 2
#define QC 4
#define S1POS 1
#define NB0 3

__global__ void __cluster_dims__(2, 1, 1) __launch_bounds__(kThreads, 1)
fused_kernel(const __grid_constant__ Params P) {
  extern __shared__ __align__(1024) uint8_t smem[];
  if (threadIdx.x == 0) { prefetch_map(&P.x); prefetch_map(&P.w); prefetch_map(&P.wk); prefetch_map(blockIdx.x & 1 ? &P.v : &P.k); }
  const uint32_t sb = __shfl_sync(0xffffffffu, (uint32_t)__cvta_generic_to_shared(smem), 0);
  if ((sb & 0xffffff) != SM_BASE) __trap();
  const int tid = threadIdx.x, lane = tid & 31;
  const int warp = __shfl_sync(0xffffffffu, tid >> 5, 0);
  const int rho = blockIdx.x & 1, cl = P.tile[blockIdx.x >> 1], cta = 2 * cl + rho;
  const int j = cl & 7, rp = cl >> 3, r = rp * 2 + rho;
  auto bar = [&](int i) { return sb + SM_BAR + 8u * i; };
  TSTAMP(tid == 0, 0); GSTAMP(tid == 0, 30);

  if (warp == 8 && elect()) {
    for (int i = 0; i < 4; i++) mbar_init(bar(B_QKV_FULL + i), 1);
    asm volatile("fence.mbarrier_init.release.cluster;" ::: "memory");
    mbar_expect(bar(B_QKV_FULL), QKV_STAGE);
    tma2d(sb, &P.x, 0, 128 * r, bar(B_QKV_FULL));
    tma3d(sb + 24576, &P.w, 0, 0, 16 + 2 * j, bar(B_QKV_FULL));
    tma3d(sb + 8192, &P.w, 0, 0, 2 * j, bar(B_QKV_FULL));
    tma3d(sb + 16384, &P.w, 0, 0, 32 + 2 * j, bar(B_QKV_FULL));
  }
  if (tid == 0) {
    for (int i = 0; i < 4; i++) mbar_init(bar(B_QKV_EMPTY + i), 16);
    for (int i = 0; i < 5; i++) { mbar_init(bar(B_OUT_FULL + i), 1); mbar_init(bar(B_OUT_EMPTY + i), 16); }
    mbar_init(bar(B_QKV_DONE), 16); mbar_init(bar(B_CONV_DONE), 16);
    for (int i = 0; i < 3; i++) { mbar_init(bar(B_PREP_FULL + i), 1); mbar_init(bar(B_PREP_EMPTY + i), 2); mbar_init(bar(B_H_FULL + i), 1); mbar_expect(bar(B_H_FULL + i), i < 2 ? 12288 : 8192); }
    mbar_init(bar(B_SIG_READY), 4); mbar_init(bar(B_ZEROED), 1);
    mbar_init(bar(B_KVP), 8); mbar_init(bar(B_KV_READY), 4);
    for (int i = 0; i < 2; i++) {
      mbar_init(bar(B_O_WRITTEN + i), 8); mbar_init(bar(B_OT_FREE + i), 1);
      mbar_init(bar(B_YIN + i), 1); mbar_expect(bar(B_YIN + i), 8192);
    }
    for (int i = 0; i < 4; i++) { mbar_init(bar(B_SEG + i), 4); mbar_init(bar(B_Q_FULL + i), 1); }
    mbar_init(bar(B_Y_READY), 1); mbar_init(bar(B_FLAGS1), 1);
    mbar_init(bar(B_RDY0), 1); mbar_expect(bar(B_RDY0), 16);
    mbar_init(bar(B_RDY1), 1); mbar_init(bar(B_STG_FREE), 3);
    asm volatile("fence.mbarrier_init.release.cluster;" ::: "memory");
  }
  if (warp == 9 || warp == 10) {
#pragma unroll
    for (int i = 0; i < 4; i++) asm volatile("st.shared.v4.b32 [%0], {%1,%1,%1,%1};" :: "r"(sb + SM_F1 + i * 1024 + (tid - 288) * 16), "r"(0xffffffffu) : "memory");
    fence_async_smem();
  }
  LOOPSTAMP(3, tid == 256, 13); LOOPSTAMP(3, tid == 0, 14);
  __syncwarp();
  cluster_arrive();
  cluster_wait();
  LOOPSTAMP(3, tid == 256, 15);

  if (warp < 8) {
    asm volatile("setmaxnreg.inc.sync.aligned.u32 224;");
    const int wg = warp >> 2, wq = warp & 3;
    const int never = __shfl_sync(0xffffffffu, P.zero, 0);
    const uint32_t orow = wq * 2048 + (lane & 15) * 128, ox = ((lane >> 4) ^ (lane & 7)) << 4;
    float aq[64];
    Fft F;
    uint32_t a1[32];
    {
      float ak[64], avq[128];
      auto k_step = [&](uint32_t st, int kk, int acc) {
        mma_tn(ak, make_desc(st + 24576 + wg * 4096 + kk * 2048, 4096, 1024, 1), make_desc(st + kk * 32, 16, 512, 2), acc);
      };
      auto vq_step = [&](uint32_t st, int kk, int acc) {
        mma_nt256(avq, make_desc(st + wg * 4096 + kk * 32, 16, 512, 2), make_desc(st + 8192 + kk * 2048, 4096, 1024, 1), acc);
      };
#pragma unroll
      for (int i = 0; i < 64; i++) { ak[i] = 1.f; avq[i] = 1.f; avq[64 + i] = 0.f; }
#pragma unroll 1
      for (int it = 0; it < 29; ++it) {
        mbar_wait(bar(B_QKV_FULL + (it & 3)), (it >> 2) & 1);
        TSTAMP(tid == 0 && it == 0, 1); LOOPSTAMP(1, tid == 0 && it < 27, 1 + it); LOOPSTAMP(3, tid == 0 && it < 12, 1 + it);
        const uint32_t st = (it & 3) * QKV_STAGE;
        wg_fence();
        k_step(st, 0, 1);
        wg_commit();
        wg_wait<1>();
        arrive_both(bar(B_QKV_EMPTY + ((it - 1) & 3)), lane, it > 0);
        wg_fence();
        vq_step(st, 0, 1);
        k_step(st, 1, 1);
        vq_step(st, 1, 1);
        wg_commit();
      }
#pragma unroll 1
      for (int s = 1; s < 4; ++s) {
        mbar_wait(bar(B_QKV_FULL + s), 1);
        wg_fence();
        k_step(s * QKV_STAGE, 0, 1);
        k_step(s * QKV_STAGE, 1, 1);
        wg_commit();
      }
      uint32_t pk[32];
      auto phi_k = [&](int i0, int i1) {
#pragma unroll
        for (int i = i0; i < i1; i++) { pk[i] = elu1(ak[2 * i], ak[2 * i + 1]); asm volatile("" : "+r"(pk[i]) :: "memory"); }
        sched_fence(never, i0);
      };
#pragma unroll
      for (int n = 0; n < 6; n++) {
        wg_fence();
        vq_step((1 + (n >> 1)) * QKV_STAGE, n & 1, 1);
        wg_commit();
        if (n == 0) {
          wg_wait<1>();
          pin<64>(ak);
          TSTAMP(tid == 0, 2);
          bar_sync(1, 256);
        }
        phi_k(n ? PH0 + (32 - PH0) * (n - 1) / 5 : 0, PH0 + (32 - PH0) * n / 5);
      }
      mbar_wait(bar(B_SIG_READY), 0);
      ldsm4_t(F.fa, sb + SM_F1 + (lane >> 4) * 1024 + wq * 256 + (lane & 15) * 16);
      ldsm4_t(F.fa + 4, sb + SM_F1 + 2048 + (lane >> 4) * 1024 + wq * 256 + (lane & 15) * 16);
      const uint4 tw = lds128(sb + SM_TW + (tid & 127) * 16);
      F.tw[0] = {tw.x, tw.y}; F.tw[1] = {tw.z, tw.w};
      F.vst = sb + (16 * wq + (lane & 7)) * 128 + (((lane >> 3) ^ (lane & 7)) << 4);
      wg_wait<0>();
      pin<128>(avq);
      if (S1POS == 0) F.stage1(a1, SM_SIG + wg * 8192);
      arrive_both(bar(B_QKV_DONE), lane);
      TSTAMP(tid == 0, 3);
#pragma unroll
      for (int t = 0; t < 8; t++) {
        const float* b = avq + 64 + 8 * t;
        stsm4(sb + (t >> 2) * SLOT + wg * 8192 + orow + (ox ^ ((t & 3) << 5)), pack_bf16(b[0], b[1]), pack_bf16(b[2], b[3]), pack_bf16(b[4], b[5]), pack_bf16(b[6], b[7]));
      }
#pragma unroll
      for (int i = 0; i < 64; i++) aq[i] = avq[i];
      fence_async_smem();
      bar_sync(1, 256);
      float dkv[36];
#pragma unroll
      for (int ks = 0; ks < 8; ks++) {
        const uint32_t va = wg * SLOT + ks * 2048;
        const uint64_t db = make_desc(va, SM_ONES - va, 1024, 1);
        uint32_t a[4];
        pin<4>(pk + 4 * ks);
#pragma unroll
        for (int i = 0; i < 4; i++) a[i] = add_eps(pk[4 * ks + i]);
        wg_fence();
        if (ks == 0) mma_kv_init(dkv, a[0], a[1], a[2], a[3], db);
        else mma_kv_acc(dkv, a[0], a[1], a[2], a[3], db);
      }
      wg_commit();
      uint8_t* box = g_xch[warp * 16 + j] + 2 * SLOT + r * KV_SLICE + lane * 16;
      uint8_t* zbox = box + (lane & 1) * 8 * XCH_BYTES + 512 + (lane & 28) - lane * 16;
      keep(box); keep(zbox);
      if (S1POS == 1) F.stage1(a1, SM_SIG + wg * 8192);
      mbar_wait(bar(B_ZEROED), 0);
      wg_wait<S1POS == 1>();
      pin<36>(dkv);
      if (S1POS == 2) F.stage1(a1, SM_SIG + wg * 8192);
      TSTAMP(tid == 0, 4);
      auto put = [&](const float* d) {
#pragma unroll
        for (int m = 0; m < 2; m++)
          asm volatile("st.relaxed.gpu.global.v4.b32 [%0], {%1,%2,%3,%4};" :: "l"(box + m * 8 * XCH_BYTES), "r"(pack_bf16(d[2 * m], d[2 * m + 1])),
                       "r"(pack_bf16(d[2 * m + 4], d[2 * m + 5])), "r"(pack_bf16(d[2 * m + 8], d[2 * m + 9])), "r"(pack_bf16(d[2 * m + 12], d[2 * m + 13])) : "memory");
      };
      if (wq < 2) put(dkv); else put(dkv + 16);
      asm volatile("{\n.reg .pred p;\nsetp.eq.b32 p, %2, 0;\n@p st.relaxed.gpu.global.b32 [%0], %1;\n}" :: "l"(zbox), "f"(lane & 1 ? dkv[34] : dkv[32]), "r"(lane & 2) : "memory");
      __syncwarp();
      mbar_arrive_if(bar(B_KVP), lane == 0);
      TSTAMP(tid == 0, 5);
    }

    uint32_t pq[32];
    auto phi_q = [&](int i0, int i1) {
      pin_range(aq, 2 * i0, 2 * i1);
#pragma unroll
      for (int i = i0; i < i1; i++) { pq[i] = add_eps(elu1(aq[2 * i], aq[2 * i + 1])); keep(pq[i]); }
      sched_fence(never, 40 + i0);
    };
    uint32_t a2[32];
    float by[16];
    auto conv_pair = [&](uint32_t sa, uint32_t ya, uint32_t first) {
      const uint32_t sc = sa + SLOT;
      uint32_t b1[32], b2[32], a3[16], b3[16];
      float ay[16];
      Cx pa[2], pb[2];
      sched_fence(never, 80);
      F.stage1(b1, sc);
      F.prod01(a2, pa, a3);
      F.prod23(a2, pa, a3);
      wg_wait<1>(); pin<32>(b1); pin<8>(a3);
      F.inv<0>(a3, sa);
      F.fwd<0>(b1, b2);
      wg_wait<1>(); pin<8>(a3 + 8);
      F.inv<1>(a3, sa);
      F.fwd<1>(b1, b2); F.fwd<2>(b1, b2); F.fwd<3>(b1, b2);
      F.last(ay, sa, wg);
      wg_wait<3>(); pin<16>(b2);
      F.prod01(b2, pb, b3);
      wg_wait<2>(); pin<16>(b2 + 16);
      F.prod23(b2, pb, b3);
      mbar_wait(bar(B_RDY1), first);
      wg_wait<1>(); pin<8>(b3); pin<16>(ay);
      F.inv<0>(b3, sc);
      Fft::store_y(ay, ya);
      wg_wait<0>(); pin<8>(b3 + 8);
      F.inv<1>(b3, sc);
    };
    const bool ylocal = (wq >> 1) == rho;
    const uint32_t yoff = sb + (wq & 1) * 1024 + ((lane ^ wg ^ (2 * rho)) << 4);
    const uint32_t ya0 = yoff + (ylocal ? SM_Y0 + wg * 8192 : SM_YT + wg * 4096), ya1 = (yoff ^ 64) + (ylocal ? SM_SIG + wg * 8192 : SM_YT + wg * 4096);
    auto pair_done = [&](uint32_t ya, int seg) {
      pin<16>(by);
      Fft::store_y(by, (ya ^ 32) + 2048);
      fence_async_smem();
      __syncwarp();
      mbar_arrive_if(bar(B_SEG + 2 * seg + wg), lane == 0);
    };
    const uint32_t s0 = SM_SIG + wg * 8192, s1 = s0 + 2 * SLOT;
    phi_q(0, QA);
    wg_wait<0>(); pin<32>(a1);
    bar_sync(2 + wg, 128);
    F.fwd<0>(a1, a2); phi_q(QA, QA + QB);
    F.fwd<1>(a1, a2); phi_q(QA + QB, QA + 2 * QB);
    F.fwd<2>(a1, a2); phi_q(QA + 2 * QB, QA + 3 * QB);
    F.fwd<3>(a1, a2);
    phi_q(QA + 3 * QB, QA + 3 * QB + QC);
    wg_wait<0>(); pin<32>(a2);
#pragma unroll 1
    for (uint32_t sa = s0;; sa += 2 * SLOT + P.zero) {
    conv_pair(sa, sa == s1 ? ya1 : ya0, sa != s1);
    if (sa == s1) break;
    F.last(by, s0 + SLOT, wg);
    F.stage1(a1, s1);
    phi_q(QA + 3 * QB + QC, 32);
    wg_wait<1>();
    pair_done(ya0, 0);
    TSTAMP(tid == 0, 7); TSTAMP(tid == 128, 10);
    {
      float dn[4][20];
      mbar_wait(bar(B_KV_READY), 0);
      TSTAMP(tid == 0, 8);
      wg_fence();
#pragma unroll
      for (int h = 0; h < 4; h++) {
        const uint64_t db = make_desc(SM_KV + h * 2560, 640, 128, 0);
        const uint32_t* a = pq + 8 * h;
        mma_o_init(dn[h], a[0], a[1], a[2], a[3], db);
        mma_o_acc(dn[h], a[4], a[5], a[6], a[7], db + (1280 >> 4));
        wg_commit();
      }
      auto head_store = [&](int h) {
        pin<20>(dn[h]);
        const float i0 = __fdividef(1.f, dn[h][16] + 1e-6f), i1 = __fdividef(1.f, dn[h][18] + 1e-6f);
        const uint32_t p0 = pack_bf16(i0, i0), p1 = pack_bf16(i1, i1);
#pragma unroll
        for (int hf = 0; hf < 2; hf++) {
          const float* a = dn[h] + 8 * hf;
          const uint32_t dst = sb + (h >> 1) * SLOT + wg * 8192 + orow + (ox ^ (((h & 1) * 2 + hf) << 5));
          stsm4(dst, bmul2(pack_bf16(a[0], a[1]), p0), bmul2(pack_bf16(a[2], a[3]), p1), bmul2(pack_bf16(a[4], a[5]), p0), bmul2(pack_bf16(a[6], a[7]), p1));
        }
        if (h & 1) { fence_async_smem(); __syncwarp(); mbar_arrive_if(bar(B_O_WRITTEN + (h >> 1)), lane == 0); }
      };
      wg_wait<4>(); pin<32>(a1);
      bar_sync(2 + wg, 128);
      F.fwd<0>(a1, a2);
      wg_wait<4>(); head_store(0);
      F.fwd<1>(a1, a2);
      wg_wait<4>(); head_store(1);
      F.fwd<2>(a1, a2);
      wg_wait<4>(); head_store(2);
      F.fwd<3>(a1, a2);
      wg_wait<4>(); head_store(3);
      TSTAMP(tid == 0, 9);
#pragma unroll
      for (int i = 0; i < 32; i++) { aq[i] = aq[32 + i] = 0.f; pq[i] = 0; }
      wg_wait<0>(); pin<32>(a2);
    }
    }
    F.last(by, s1 + SLOT, wg);

    float acc[64];
    auto stage_mma = [&](int s, int kk, int accumulate) {
      mma_nt(acc, make_desc(((A_SLOTS >> (4 * s)) & 15) * SLOT + wg * 8192 + kk * 32, 16, 1024, 1),
             make_desc(((B_SLOTS >> (4 * s)) & 15) * SLOT + kk * 2048, 8192, 1024, 1), accumulate);
    };
    {
      mbar_wait(bar(B_OUT_FULL), 0);
      wg_fence();
#pragma unroll
      for (int kk = 0; kk < 2; kk++) stage_mma(0, kk, kk);
      wg_commit();
      wg_wait<1>();
      arrive_both(bar(B_CONV_DONE), lane);
      cluster_arrive();
      wg_fence();
#pragma unroll
      for (int kk = 2; kk < 4; kk++) stage_mma(0, kk, 1);
      wg_commit();
      pair_done(ya1, 1);
      TSTAMP(tid == 0, 11); TSTAMP(tid == 128, 12);
      int s = 1, sprev = 0;
      uint32_t ph = 0;
#pragma unroll 1
      for (int ks = 1; ks < 12; ++ks) {
        mbar_wait(bar(B_OUT_FULL + s), ph);
        LOOPSTAMP(2, tid == 0, 1 + ks);
        TSTAMP(tid == 0 && ks == 2, 13); TSTAMP(tid == 0 && ks == 9, 14);
        wg_fence();
        stage_mma(s, 0, 1);
        wg_commit();
        wg_wait<1>();
        arrive_both(bar(B_OUT_EMPTY + sprev), lane);
        wg_fence();
#pragma unroll
        for (int kk = 1; kk < 4; kk++) stage_mma(s, kk, 1);
        wg_commit();
        sprev = s;
        if (++s == 5) { s = 0; ph ^= 1; }
      }
#pragma unroll 1
      for (int ks = 12; ks < 16; ++ks) {
        asm volatile("{\n.reg .pred p;\nsetp.ne.b32 p, %0, 0;\n@p bar.sync 1, 256;\n}" :: "r"((int)(ks == 16 - TAIL && wg)) : "memory");
        mbar_wait(bar(B_OUT_FULL + s), ks == 15);
        wg_fence();
#pragma unroll
        for (int kk = 0; kk < 4; kk++) stage_mma(s, kk, 1);
        wg_commit();
        if (++s == 5) s = 0;
      }
    }
    asm volatile("{\n.reg .pred p;\nsetp.eq.b32 p, %0, 0;\n@p bar.arrive 1, 256;\n}" :: "r"(wg) : "memory");
    wg_wait<0>(); pin<64>(acc);
    TSTAMP(tid == 0, 15); TSTAMP(tid == 128, 16);
#pragma unroll
    for (int hf = 0; hf < 2; hf++) {
      const uint32_t dst = sb + (1 + 8 * hf) * SLOT + wg * 8192;
#pragma unroll
      for (int t = 0; t < 4; t++) {
        const float* a = acc + 32 * hf + 8 * t;
        stsm4(dst + orow + (ox ^ (t << 5)), pack_bf16(a[0], a[1]), pack_bf16(a[2], a[3]), pack_bf16(a[4], a[5]), pack_bf16(a[6], a[7]));
      }
      fence_async_smem();
      __syncwarp();
      if (elect()) { tma2d_store(&P.outa, dst + wq * 2048, 128 * j + 64 * hf, 128 * r + 16 * warp); bulk_commit(); }
    }
    const bool stale = __any_sync(0xffffffffu, acc[0] != acc[0] || acc[2] != acc[2] || (DBG & 256));
    if (elect()) bulk_wait_read();
    TSTAMP(tid == 128, 17);
    __syncwarp();
    cluster_wait();
    TSTAMP(tid == 128, 28); GSTAMP(tid == 128, 31);
    if (stale) {
      __threadfence();
#pragma unroll
      for (int i = 0; i < 64; i++) acc[i] = 0.f;
      const int row = warp * 16 + (lane >> 2);
#pragma unroll 1
      for (int k = 0; k < 1024; k += 2) {
        const uint8_t* src = g_xch[r * 8 + (k >> 7)] + ((k >> 6) & 1) * SLOT + row * 128 + ((((k >> 3) ^ row) & 7) << 4) + (k & 7) * 2;
        uint32_t a[2];
        int n = 0;
        do { a[0] = ld_relaxed(src); a[1] = ld_relaxed(src + 1024); } while (!all_arrived<2>(a) && ++n < kSpinLimit);
#pragma unroll 1
        for (int e = 0; e < 2; e++) {
          const float a0 = e ? bf_hi(a[0]) : bf_lo(a[0]), a1 = e ? bf_hi(a[1]) : bf_lo(a[1]);
          const uint32_t* wrow = reinterpret_cast<const uint32_t*>(P.wo_ptr + (k + e) * 1024 + 128 * j) + (lane & 3);
#pragma unroll
          for (int i = 0; i < 16; i++) {
            const uint32_t w = __ldg(wrow + 4 * i);
            acc[4 * i] += a0 * bf_lo(w); acc[4 * i + 1] += a0 * bf_hi(w);
            acc[4 * i + 2] += a1 * bf_lo(w); acc[4 * i + 3] += a1 * bf_hi(w);
          }
        }
      }
      uint32_t* op = reinterpret_cast<uint32_t*>(P.out_ptr + (128 * r + row) * 2048 + 128 * j) + (lane & 3);
#pragma unroll
      for (int i = 0; i < 32; i++) op[(i & 1) * 8192 + (i >> 1) * 4] = pack_bf16(acc[2 * i], acc[2 * i + 1]);
    }
  } else {
    asm volatile("setmaxnreg.dec.sync.aligned.u32 56;");
    auto chunk = [&](int ks) { const int c = ks >= 9, t = ks - 2 - 7 * c; return ks < 2 ? 2 * j + ks : 2 * (t + (t >= j)) + c; };
    auto load_q = [&](int n) {
      mbar_expect(bar(B_Q_FULL + (n & 3)), 4096);
      tma2d(sb + SM_Q + (n & 3) * 4096, &P.q, cl * 16, rho * 1024 + n * 128, bar(B_Q_FULL + (n & 3)));
    };
    auto load_wo = [&](uint32_t dst, int c, uint32_t bytes, uint32_t fb) {
      mbar_expect(fb, bytes);
      tma2d_mc(dst + rho * 8192, &P.wo, 128 * j + 64 * rho, c * 64, fb);
    };
    uint8_t* const xch = g_xch[r * 8 + j];
    if (warp == 8) {
      int ck = 0, cw = 0, cph = 1;
      const CUtensorMap* kvmap = rho ? &P.v : &P.k;
#pragma unroll 1
      for (int it = 1; it < 32 || (ck < 16 && it < kSpinLimit); ++it) {
        if (it < 32) {
          const uint32_t st = sb + (it & 3) * QKV_STAGE, fb = bar(B_QKV_FULL + (it & 3));
          mbar_wait(bar(B_QKV_EMPTY + (it & 3)), ((it >> 2) - 1) & 1);
          if (elect()) {
            mbar_expect(fb, QKV_STAGE);
            tma2d_mc(st + 24576 + rho * 4096, &P.wk, 1024 + 128 * j + 64 * rho, 32 * it, fb);
            tma3d_mc(st + 8192 + rho * 8192, &P.w, 0, 32 * it, 32 * rho + 2 * j, fb);
            tma2d(st, &P.x, 32 * it, 128 * r, fb);
          }
          LOOPSTAMP(3, lane == 0 && it >= 4 && it < 12, 15 + it);
        }
        if (it < 32 - XPF) {
          if (((it + XPF) & 7) == rp && elect()) {
            l2_prefetch2d(&P.wk, 1024 + 128 * j + 64 * rho, 32 * (it + XPF));
            l2_prefetch3d(&P.w, 0, 32 * (it + XPF), 32 * rho + 2 * j);
          }
          if (((it + XPF) & 7) == j && elect()) l2_prefetch2d(&P.x, 32 * (it + XPF), 128 * r);
        }
        const int n = it - HSTART;
        if (n >= 0 && n < 8) {
          if (elect()) bulk_load(sb + SM_SIG + n * 8192 + 4096, P.ssm_k + (size_t)(cta * 8 + n) * 2048, 4096, bar(B_H_FULL + (n >= 3) + (n >= 6)));
        } else if (n >= 8 && n < 19) {
          if (elect()) bulk_store(xch + (n - 8) * 4096, sb + SM_F1, 4096);
        } else if (it >= PF0 && it < PF0 + 6) {
          if (elect()) l2_prefetch(it < PF0 + 2 ? P.wo_ptr + cta * 8192 + (it - PF0) * 4096 : P.q_ptr + cta * 16384 + (it - PF0 - 2) * 4096, 8192);
        }
        if (ck < 16 && it >= PSTART && __all_sync(0xffffffffu, mbar_test(bar(B_PREP_EMPTY + cw), cph))) {
          if (elect()) {
            mbar_expect(bar(B_PREP_FULL + cw), 8704);
            tma3d_mc(sb + SM_STG + cw * 8704 + rho * 4608, kvmap, cl * 16, ck * 8 - 1 + rho, 0, bar(B_PREP_FULL + cw));
          }
          ++ck;
          if (++cw == 3) { cw = 0; cph ^= 1; }
        }
      }
      if (elect()) {
        bulk_commit();
        bulk_wait_read();
        mbar_wait(bar(B_STG_FREE), 0);
        mbar_expect(bar(B_SIG_READY), 10240);
        bulk_load(sb + SM_TW, g_tables, 10240, bar(B_SIG_READY));
        flag_add(&g_ready);
        prefetch_map(&P.wo); prefetch_map(&P.outa); prefetch_map(&P.q);
        flag_wait(&g_ready, kCtas * (load_epoch(cta) + 1));
        mbar_arrive(bar(B_ZEROED));
        TSTAMP(true, 27);
      }
      __syncwarp();
      mbar_wait(bar(B_QKV_DONE), 0);
#pragma unroll 1
      for (int ks = 0; ks < NB0; ++ks) if (elect()) load_wo(sb + (4 + ks) * SLOT, chunk(ks), ks < 2 ? SLOT : 2 * SLOT, bar(B_OUT_FULL + ks));
    } else {
      const int at = tid - 288, aw = warp - 9, ch0 = cta * 8;
      {
        const uint32_t stg = sb + SM_STG + aw * 8704, pf = bar(B_PREP_FULL + aw), pe = bar(B_PREP_EMPTY + aw);
        const uint4 wv = __ldg(reinterpret_cast<const uint4*>(P.shift_k + (ch0 + 2 * (lane & 3)) * 4));
        const float skip = __bfloat162float(P.ssm_d[ch0 + (lane & 7)]);
        const uint32_t w0 = __byte_perm(wv.x, wv.z, 0x5410), w1 = __byte_perm(wv.x, wv.z, 0x7632);
        const uint32_t w2 = __byte_perm(wv.y, wv.w, 0x5410), w3 = __byte_perm(wv.y, wv.w, 0x7632);
        auto swz32 = [](uint32_t a) { return a ^ ((a >> 3) & 16); };
        const uint32_t kl = (lane >> 3) * 288 + (lane & 7) * 32 + rho * 16;
        const uint32_t ka = stg + swz32(kl + 32), kh = stg + swz32(kl + 12 * 288), va = stg + 4608 + swz32(lane * 32 + rho * 16);
        const uint32_t ua = sb + SM_SIG + (lane & 7) * 8192 + (((lane >> 3) ^ (lane & 7)) << 4);
        uint32_t eh = 0;
#pragma unroll 1
        for (int ck = aw, rd = 0; rd < 9; ck += 3, ++rd) {
          if (rd == 6) {
            if (lane == 0) mbar_arrive(bar(B_STG_FREE));
            bar_sync(4, 96);
          }
          const int c = rd < 6 ? ck : ck - 18;
          if (c < 8) {
            uint32_t x[32], dst = sb + SM_SIG + c * 8192;
            if (rd < 6) {
              mbar_wait(bar(B_H_FULL + rd), 0);
#pragma unroll
              for (int i = 0; i < 8; i++) ldsm4(x + 4 * i, dst + 4096 + i * 512 + lane * 16);
              const float d = __shfl_sync(0xffffffffu, skip, c);
              if (lane == 0) x[0] = pack_bf16(bf_lo(x[0]) + d, bf_hi(x[0]));
              dst += 4096 + (lane >> 1) * 128 + ((((lane & 1) * 4) ^ ((lane >> 1) & 7)) << 4);
            } else {
#pragma unroll
              for (int i = 0; i < 8; i++) ldsm4_t(x + 4 * i, dst + i * 512 + ((lane ^ c) << 4));
              dst += (lane >> 4) * 1024 + (lane & 7) * 128 + ((((lane >> 1) & 4) ^ (lane & 7)) << 4);
            }
            const uint32_t e = normalize(x, dst);
            if (rd < 6) {
              eh |= e << (8 * rd);
            } else {
              const int f = min(max((int)(e + (eh & 255)) - 125, 0), 254);
              eh >>= 8;
              if (lane == 0) asm volatile("st.shared.b16 [%0], %1;" :: "r"(sb + SM_SC + rho * 16 + 2 * c), "h"((uint16_t)(f << 7)) : "memory");
            }
          }
          if (ck < 16) {
            mbar_wait(pf, rd & 1);
            uint32_t k[20], v[16];
            ldsm4(k, kh);
#pragma unroll
            for (int m = 0; m < 4; m++) { ldsm4(k + 4 + 4 * m, (ka ^ ((m & 1) << 4)) + m * 1152); ldsm4(v + 4 * m, va + m * 1024); }
            arrive_both(pe + ((k[3] | k[4] | k[8] | k[12] | k[16] | v[0] | v[4] | v[8] | v[12]) & P.zero), lane, ck < 13);
#pragma unroll
            for (int m = 0; m < 4; m++) {
              uint32_t u[4];
#pragma unroll
              for (int n = 0; n < 4; n++) {
                const uint32_t* kk = k + 4 + 4 * m + n;
                u[n] = bmul2(bfma2(kk[0], w0, bfma2(kk[-1], w1, bfma2(kk[-2], w2, bmul2(kk[-3], w3)))), v[4 * m + n]);
              }
              stsm4_t((ua ^ (m << 6)) + ck * 256, u[0], u[1], u[2], u[3]);
            }
          }
        }
        fence_async_smem();
        __syncwarp();
        if (lane == 0) mbar_arrive(bar(B_SIG_READY));
        bar_sync(4, 96);
        if (at == 32) {
          const uint4 s = lds128(sb + SM_SC + rho * 16);
          asm volatile("st.async.weak.shared::cluster.mbarrier::complete_tx::bytes.v4.b32 [%0], {%1,%2,%3,%4}, [%5];"
                       :: "r"(peer_addr(sb + SM_SC + rho * 16, rho ^ 1)), "r"(s.x), "r"(s.y), "r"(s.z), "r"(s.w), "r"(peer_addr(bar(B_RDY0), rho ^ 1)) : "memory");
        }
        TSTAMP(at == 0, 20); LOOPSTAMP(4, at == 0, 22);
      }
    }
    __syncwarp();
    const unsigned epoch = load_epoch(cta);
    mbar_wait(bar(B_KVP), 0);
    {
      const int a4 = warp - 8;
      uint32_t v[20];
      int n = 0;
      do {
#pragma unroll
        for (int i = 0; i < 4; i++) ld_relaxed4(v + 4 * i, xch + 2 * SLOT + ((lane >> 3) * 4 + i) * KV_SLICE + (a4 * 8 + (lane & 7)) * 16);
        v[16] = ld_relaxed(xch + 2 * SLOT + (lane & 15) * KV_SLICE + 512 + (a4 * 2 + (lane >> 4)) * 4);
      } while (!all_arrived<17>(v) && ++n < kSpinLimit);
      TSTAMP(tid == 288, 21);
      float lo[4], hi[4], z = __uint_as_float(v[16]);
#pragma unroll
      for (int b = 0; b < 4; b++) {
        lo[b] = (bf_lo(v[b]) + bf_lo(v[4 + b])) + (bf_lo(v[8 + b]) + bf_lo(v[12 + b]));
        hi[b] = (bf_hi(v[b]) + bf_hi(v[4 + b])) + (bf_hi(v[8 + b]) + bf_hi(v[12 + b]));
      }
      const bool u16 = lane & 16, u8 = lane & 8;
#pragma unroll
      for (int b = 0; b < 2; b++) {
        lo[b] = (u16 ? lo[b + 2] : lo[b]) + __shfl_xor_sync(0xffffffffu, u16 ? lo[b] : lo[b + 2], 16);
        hi[b] = (u16 ? hi[b + 2] : hi[b]) + __shfl_xor_sync(0xffffffffu, u16 ? hi[b] : hi[b + 2], 16);
      }
      const float l = (u8 ? lo[1] : lo[0]) + __shfl_xor_sync(0xffffffffu, u8 ? lo[0] : lo[1], 8);
      const float h = (u8 ? hi[1] : hi[0]) + __shfl_xor_sync(0xffffffffu, u8 ? hi[0] : hi[1], 8);
      uint8_t* red = xch + 2 * SLOT + 16 * KV_SLICE;
      st_relaxed(red + (a4 * 8 + (lane & 7)) * 16 + (lane >> 3) * 4, pack_bf16(l, h));
#pragma unroll
      for (int o = 8; o; o >>= 1) z += __shfl_xor_sync(0xffffffffu, z, o);
      if ((lane & 15) == 0) st_relaxed(red + 512 + (a4 * 2 + (lane >> 4)) * 4, pack_bf16(z, z));
      TSTAMP(tid == 288, 22);
      n = 0;
      do {
#pragma unroll
        for (int i = 0; i < 4; i++) {
          const uint8_t* src = g_xch[(a4 * 4 + i) * 8 + j] + 2 * SLOT + 16 * KV_SLICE;
          ld_relaxed4(v + 4 * i, src + lane * 16);
          v[16 + i] = ld_relaxed(src + 512 + (lane & 28));
        }
      } while (!all_arrived<20>(v) && ++n < kSpinLimit);
#pragma unroll
      for (int i = 0; i < 4; i++) {
        const uint32_t dst = sb + SM_KV + (a4 * 4 + i) * 640;
        stsm4(dst + lane * 16, v[4 * i], v[4 * i + 1], v[4 * i + 2], v[4 * i + 3]);
        asm volatile("st.shared.b32 [%0], %1;" :: "r"(dst + 512 + lane * 4), "r"(v[16 + i]) : "memory");
      }
      fence_async_smem();
      __syncwarp();
      if (lane == 0) mbar_arrive(bar(B_KV_READY));
      TSTAMP(tid == 288, 23);
    }
    if (warp != 10) cluster_arrive();
    if (warp == 8) {
#pragma unroll 1
      for (int ks = NB0; ks < 4; ++ks) if (elect()) load_wo(sb + (4 + ks) * SLOT, chunk(ks), ks < 2 ? SLOT : 2 * SLOT, bar(B_OUT_FULL + ks));
#pragma unroll 1
      for (int n = 0; n < 4; ++n) if (elect()) load_q(n);
      int s = 4;
      uint32_t ph = 1;
#pragma unroll 1
      for (int ks = 4; ks < 16; ++ks) {
        uint32_t fb = bar(B_OUT_FULL + s), dst = sb + ((B_SLOTS >> (4 * s)) & 15) * SLOT;
        int c = chunk(ks);
        keep(fb); keep(dst); keep(c);
        mbar_wait(bar(ks == 4 ? B_CONV_DONE : B_OUT_EMPTY + s), ks == 4 ? 0 : ph);
        if (elect()) load_wo(dst, c, 2 * SLOT, fb);
        if (++s == 5) { s = 0; ph ^= 1; }
      }
    } else {
      auto wait_chunks = [&](unsigned mask) {
        unsigned ready;
        int n = 0;
        do {
          const unsigned f = ld_relaxed(&g_oflag[(r * 8 + ((lane >> 1) & 7)) * 32]);
          ready = __ballot_sync(0xffffffffu, (int)(f - (2 * epoch + 1 + (lane & 1))) >= 0);
        } while ((~ready & mask) && ++n < kSpinLimit);
        return ready;
      };
      if (warp == 9) {
        if (elect()) {
#pragma unroll 1
          for (int c = 0; c < 2; c++) {
            mbar_wait(bar(B_O_WRITTEN + c), 0);
            TSTAMP(c == 0, 19);
            bulk_store(xch + c * SLOT, sb + c * SLOT, SLOT);
            bulk_commit();
            bulk_wait_read();
            mbar_arrive(bar(B_OT_FREE + c));
            delay(FDELAY);
            st_relaxed(&g_oflag[(r * 8 + j) * 32], 2 * epoch + 1 + c);
            TSTAMP(c == 0, 29); TSTAMP(c == 1, 25);
          }
          g_epoch[cta] = epoch + 1;
        }
        __syncwarp();
        wait_chunks(0xaaaa);
        if (lane == 0) mbar_arrive(bar(B_FLAGS1));
      } else if (warp == 10) {
        mbar_wait(bar(B_RDY0), 0);
#pragma unroll 1
        for (int n = 0; n < 4; n++) {
          const int w = n & 1;
          mbar_wait(bar(B_SEG + n), 0);
          if (elect()) bulk_to_peer(sb + (n < 2 ? SM_Y0 : SM_SIG) + w * 8192 + 4096, sb + SM_YT + w * 4096, 4096, bar(B_YIN + (n >> 1)), rho ^ 1);
          if (w) {
            mbar_wait(bar(B_YIN + (n >> 1)), 0);
            if (lane == 0) asm volatile("mbarrier.arrive.shared::cluster.b64 _, [%0];" :: "r"(n < 2 ? peer_addr(bar(B_RDY1), rho ^ 1) : bar(B_Y_READY)) : "memory");
          }
        }
        __syncwarp();
        cluster_arrive();
        TSTAMP(lane == 0, 26);
      } else {
        mbar_wait(bar(B_O_WRITTEN + 1), 0);
        unsigned ready = 0;
        int s = 2;
        uint32_t ph = 1;
#pragma unroll 1
        for (int ks = 2; ks < 16; ++ks) {
          const int c = chunk(ks);
          uint32_t fb = bar(B_OUT_FULL + s), dst = sb + ((A_SLOTS >> (4 * s)) & 15) * SLOT;
          uint8_t* src = g_xch[r * 8 + (c >> 1)] + (c & 1) * SLOT;
          keep(fb); keep(dst); keep(src);
          if (ks < 5 || ks == 9) {
            const unsigned need = ks < 4 ? 1u << c : 0x5555u;
            if (ks == 9) mbar_wait(bar(B_FLAGS1), 0);
            else if (~ready & need) ready = wait_chunks(need);
          }
          if (ks == 5 || ks == 6) mbar_wait(bar(B_OT_FREE + s), 0);
          if (ks >= 4) mbar_wait(bar(ks == 4 ? B_CONV_DONE : B_OUT_EMPTY + s), ks == 4 ? 0 : ph);
          if (elect()) bulk_load(dst, src, SLOT, fb);
          TSTAMP(ks == 2 && lane == 0, 18); LOOPSTAMP(2, lane == 0, 11 + ks);
          if (++s == 5) { s = 0; ph ^= 1; }
        }
      }
      if (warp < 11) {
        const int yc = (lane & 1) + ((lane >> 2) & 2) + (lane & 2) * 2, ysrc = (lane >> 2) & 1;
        const uint32_t ya = sb + (yc & 4 ? SM_SIG : SM_Y0) + (yc & 1) * 8192 + (yc & 2) * 1024 + (ysrc ^ rho) * 4096 +
                            (lane >> 4) * 128 + ((yc ^ (2 * ysrc)) << 4);
        uint32_t s0, s1;
        mbar_wait(bar(B_Y_READY), 0);
        asm volatile("ld.shared.v2.b32 {%0,%1}, [%2];" : "=r"(s0), "=r"(s1) : "r"(sb + SM_SC + (lane & 3) * 8) : "memory");
#pragma unroll 1
        for (int n = warp - 9; n < 8; n += 2) {
          __nv_bfloat16* op = P.out_ptr + (rho * 1024 + n * 128 + (lane >> 2)) * 2048 + 1024 + cl * 16 + (lane & 3) * 4;
          const uint32_t qa = sb + SM_Q + (n & 3) * 4096 + lane * 8;
          mbar_wait(bar(B_Q_FULL + (n & 3)), n >> 2);
#pragma unroll 1
          for (int u0 = 0; u0 < 8; u0 += 2) {
            const uint32_t t0 = clock32();
            uint32_t y[2][4], q[2][4];
#pragma unroll
            for (int u = 0; u < 2; u++) {
              ldsm4_t(y[u], (ya ^ ((u0 + u) << 4)) + n * 256);
#pragma unroll
              for (int m = 0; m < 2; m++)
                asm volatile("ld.shared.v2.b32 {%0,%1}, [%2];" : "=r"(q[u][2 * m]), "=r"(q[u][2 * m + 1]) : "r"(qa + (u0 + u) * 512 + m * 256) : "memory");
            }
#pragma unroll
            for (int u = 0; u < 2; u++)
#pragma unroll
              for (int m = 0; m < 2; m++)
                asm volatile("st.global.v2.b32 [%0], {%1,%2};" :: "l"(op + (u0 * 16 + u * 16 + m * 8) * 2048),
                             "r"(bmul2(q[u][2 * m], bmul2(y[u][2 * m], s0))), "r"(bmul2(q[u][2 * m + 1], bmul2(y[u][2 * m + 1], s1))) : "memory");
            while (clock32() - t0 < PPACE) { }
          }
          __syncwarp();
          if (n < 4 && elect()) load_q(n + 4);
        }
        TSTAMP(tid == 320, 24);
      }
    }
    __syncwarp();
    cluster_wait();
  }
}

typedef CUresult (*EncodeFn)(CUtensorMap*, CUtensorMapDataType, cuuint32_t, void*, const cuuint64_t*, const cuuint64_t*,
                             const cuuint32_t*, const cuuint32_t*, CUtensorMapInterleave, CUtensorMapSwizzle,
                             CUtensorMapL2promotion, CUtensorMapFloatOOBfill);

void encode(EncodeFn fn, CUtensorMap* m, const void* p, int rank, const cuuint64_t* dims, const cuuint64_t* strides,
            const cuuint32_t* box, CUtensorMapSwizzle sw) {
  const cuuint32_t es[3] = {1, 1, 1};
  fn(m, CU_TENSOR_MAP_DATA_TYPE_BFLOAT16, rank, const_cast<void*>(p), dims, strides, box, es, CU_TENSOR_MAP_INTERLEAVE_NONE, sw,
     CU_TENSOR_MAP_L2_PROMOTION_NONE, CU_TENSOR_MAP_FLOAT_OOB_FILL_NONE);
}
void encode2d(EncodeFn fn, CUtensorMap* m, const void* p, uint64_t cols, uint64_t rows, uint32_t bc, uint32_t br, CUtensorMapSwizzle sw) {
  const cuuint64_t dims[2] = {cols, rows}, strides[1] = {cols * 2};
  const cuuint32_t box[2] = {bc, br};
  encode(fn, m, p, 2, dims, strides, box, sw);
}
void encode3d(EncodeFn fn, CUtensorMap* m, const void* p, uint32_t nblk) {
  const cuuint64_t dims[3] = {1024, 128, 16}, strides[2] = {2048 * 16, 2048};
  const cuuint32_t box[3] = {16, nblk, 16};
  encode(fn, m, p, 3, dims, strides, box, CU_TENSOR_MAP_SWIZZLE_32B);
}

}

extern "C" void kernel_launch(void* const* d_in, const int* in_sizes, int n_in, void* d_out, int out_size) {
  static EncodeFn fn = nullptr;
  if (!fn) {
    cudaDriverEntryPointQueryResult qr;
    cudaGetDriverEntryPoint("cuTensorMapEncodeTiled", (void**)&fn, cudaEnableDefault, &qr);
    cudaFuncSetAttribute(fused_kernel, cudaFuncAttributeMaxDynamicSharedMemorySize, SM_TOTAL);
  }
  Params P;
  encode2d(fn, &P.x, d_in[0], 1024, 2048, 32, 128, CU_TENSOR_MAP_SWIZZLE_64B);
  {
    const cuuint64_t dims[3] = {64, 1024, 48}, strides[2] = {6144, 128};
    const cuuint32_t box[3] = {64, 32, 2};
    encode(fn, &P.w, d_in[1], 3, dims, strides, box, CU_TENSOR_MAP_SWIZZLE_128B);
  }
  encode2d(fn, &P.wk, d_in[1], 3072, 1024, 64, 32, CU_TENSOR_MAP_SWIZZLE_128B);
  encode2d(fn, &P.wo, d_in[2], 1024, 1024, 64, 64, CU_TENSOR_MAP_SWIZZLE_128B);
  encode2d(fn, &P.outa, d_out, 2048, 2048, 64, 16, CU_TENSOR_MAP_SWIZZLE_128B);
  encode3d(fn, &P.k, d_in[4], 9);
  encode3d(fn, &P.v, d_in[5], 8);
  encode2d(fn, &P.q, d_in[3], 1024, 2048, 16, 128, CU_TENSOR_MAP_SWIZZLE_NONE);
  P.shift_k = (const __nv_bfloat16*)d_in[6];
  P.ssm_k = (const __nv_bfloat16*)d_in[7];
  P.ssm_d = (const __nv_bfloat16*)d_in[8];
  P.zero = 0;
  for (int cl = 0; cl < 64; cl++) {
    const int gpc = cl < 4 ? 0 : cl < 36 ? (cl - 4) & 7 : 1 + (cl - 36) % 7, mem = cl < 4 ? 4 + cl : cl < 36 ? (cl - 4) >> 3 : 4 + (cl - 36) / 7;
    P.tile[cl] = (uint8_t)(8 * gpc + mem);
  }
  P.q_ptr = (const __nv_bfloat16*)d_in[3];
  P.out_ptr = (__nv_bfloat16*)d_out;
  P.wo_ptr = (const __nv_bfloat16*)d_in[2];
  fused_kernel<<<kCtas, kThreads, SM_TOTAL>>>(P);
}
```

```cpp
#include <cuda.h>
#include <cuda_runtime.h>
#include <cuda_bf16.h>
#include <stdint.h>

#define DEVI __device__ __forceinline__

namespace {

DEVI void mma_nt(float* d, uint64_t da, uint64_t db, int sd) {
  asm volatile("{\n.reg .pred p;\nsetp.ne.b32 p, %66, 0;\nwgmma.mma_async.sync.aligned.m64n128k16.f32.bf16.bf16 {%0, %1, %2, %3, %4, %5, %6, %7, %8, %9, %10, %11, %12, %13, %14, %15, %16, %17, %18, %19, %20, %21, %22, %23, %24, %25, %26, %27, %28, %29, %30, %31, %32, %33, %34, %35, %36, %37, %38, %39, %40, %41, %42, %43, %44, %45, %46, %47, %48, %49, %50, %51, %52, %53, %54, %55, %56, %57, %58, %59, %60, %61, %62, %63}, %64, %65, p, 1, 1, 0, 1;\n}\n"
    : "+f"(d[0]), "+f"(d[1]), "+f"(d[2]), "+f"(d[3]), "+f"(d[4]), "+f"(d[5]), "+f"(d[6]), "+f"(d[7]), "+f"(d[8]), "+f"(d[9]), "+f"(d[10]), "+f"(d[11]), "+f"(d[12]), "+f"(d[13]), "+f"(d[14]), "+f"(d[15]), "+f"(d[16]), "+f"(d[17]), "+f"(d[18]), "+f"(d[19]), "+f"(d[20]), "+f"(d[21]), "+f"(d[22]), "+f"(d[23]), "+f"(d[24]), "+f"(d[25]), "+f"(d[26]), "+f"(d[27]), "+f"(d[28]), "+f"(d[29]), "+f"(d[30]), "+f"(d[31]), "+f"(d[32]), "+f"(d[33]), "+f"(d[34]), "+f"(d[35]), "+f"(d[36]), "+f"(d[37]), "+f"(d[38]), "+f"(d[39]), "+f"(d[40]), "+f"(d[41]), "+f"(d[42]), "+f"(d[43]), "+f"(d[44]), "+f"(d[45]), "+f"(d[46]), "+f"(d[47]), "+f"(d[48]), "+f"(d[49]), "+f"(d[50]), "+f"(d[51]), "+f"(d[52]), "+f"(d[53]), "+f"(d[54]), "+f"(d[55]), "+f"(d[56]), "+f"(d[57]), "+f"(d[58]), "+f"(d[59]), "+f"(d[60]), "+f"(d[61]), "+f"(d[62]), "+f"(d[63])
    : "l"(da), "l"(db), "r"(sd));
}
DEVI void mma_tn(float* d, uint64_t da, uint64_t db, int sd) {
  asm volatile("{\n.reg .pred p;\nsetp.ne.b32 p, %66, 0;\nwgmma.mma_async.sync.aligned.m64n128k16.f32.bf16.bf16 {%0, %1, %2, %3, %4, %5, %6, %7, %8, %9, %10, %11, %12, %13, %14, %15, %16, %17, %18, %19, %20, %21, %22, %23, %24, %25, %26, %27, %28, %29, %30, %31, %32, %33, %34, %35, %36, %37, %38, %39, %40, %41, %42, %43, %44, %45, %46, %47, %48, %49, %50, %51, %52, %53, %54, %55, %56, %57, %58, %59, %60, %61, %62, %63}, %64, %65, p, 1, 1, 1, 0;\n}\n"
    : "+f"(d[0]), "+f"(d[1]), "+f"(d[2]), "+f"(d[3]), "+f"(d[4]), "+f"(d[5]), "+f"(d[6]), "+f"(d[7]), "+f"(d[8]), "+f"(d[9]), "+f"(d[10]), "+f"(d[11]), "+f"(d[12]), "+f"(d[13]), "+f"(d[14]), "+f"(d[15]), "+f"(d[16]), "+f"(d[17]), "+f"(d[18]), "+f"(d[19]), "+f"(d[20]), "+f"(d[21]), "+f"(d[22]), "+f"(d[23]), "+f"(d[24]), "+f"(d[25]), "+f"(d[26]), "+f"(d[27]), "+f"(d[28]), "+f"(d[29]), "+f"(d[30]), "+f"(d[31]), "+f"(d[32]), "+f"(d[33]), "+f"(d[34]), "+f"(d[35]), "+f"(d[36]), "+f"(d[37]), "+f"(d[38]), "+f"(d[39]), "+f"(d[40]), "+f"(d[41]), "+f"(d[42]), "+f"(d[43]), "+f"(d[44]), "+f"(d[45]), "+f"(d[46]), "+f"(d[47]), "+f"(d[48]), "+f"(d[49]), "+f"(d[50]), "+f"(d[51]), "+f"(d[52]), "+f"(d[53]), "+f"(d[54]), "+f"(d[55]), "+f"(d[56]), "+f"(d[57]), "+f"(d[58]), "+f"(d[59]), "+f"(d[60]), "+f"(d[61]), "+f"(d[62]), "+f"(d[63])
    : "l"(da), "l"(db), "r"(sd));
}
DEVI void mma_nt256(float* d, uint64_t da, uint64_t db, int sd) {
  asm volatile("{\n.reg .pred p;\nsetp.ne.b32 p, %130, 0;\nwgmma.mma_async.sync.aligned.m64n256k16.f32.bf16.bf16 {%0, %1, %2, %3, %4, %5, %6, %7, %8, %9, %10, %11, %12, %13, %14, %15, %16, %17, %18, %19, %20, %21, %22, %23, %24, %25, %26, %27, %28, %29, %30, %31, %32, %33, %34, %35, %36, %37, %38, %39, %40, %41, %42, %43, %44, %45, %46, %47, %48, %49, %50, %51, %52, %53, %54, %55, %56, %57, %58, %59, %60, %61, %62, %63, %64, %65, %66, %67, %68, %69, %70, %71, %72, %73, %74, %75, %76, %77, %78, %79, %80, %81, %82, %83, %84, %85, %86, %87, %88, %89, %90, %91, %92, %93, %94, %95, %96, %97, %98, %99, %100, %101, %102, %103, %104, %105, %106, %107, %108, %109, %110, %111, %112, %113, %114, %115, %116, %117, %118, %119, %120, %121, %122, %123, %124, %125, %126, %127}, %128, %129, p, 1, 1, 0, 1;\n}\n"
    : "+f"(d[0]), "+f"(d[1]), "+f"(d[2]), "+f"(d[3]), "+f"(d[4]), "+f"(d[5]), "+f"(d[6]), "+f"(d[7]), "+f"(d[8]), "+f"(d[9]), "+f"(d[10]), "+f"(d[11]), "+f"(d[12]), "+f"(d[13]), "+f"(d[14]), "+f"(d[15]), "+f"(d[16]), "+f"(d[17]), "+f"(d[18]), "+f"(d[19]), "+f"(d[20]), "+f"(d[21]), "+f"(d[22]), "+f"(d[23]), "+f"(d[24]), "+f"(d[25]), "+f"(d[26]), "+f"(d[27]), "+f"(d[28]), "+f"(d[29]), "+f"(d[30]), "+f"(d[31]), "+f"(d[32]), "+f"(d[33]), "+f"(d[34]), "+f"(d[35]), "+f"(d[36]), "+f"(d[37]), "+f"(d[38]), "+f"(d[39]), "+f"(d[40]), "+f"(d[41]), "+f"(d[42]), "+f"(d[43]), "+f"(d[44]), "+f"(d[45]), "+f"(d[46]), "+f"(d[47]), "+f"(d[48]), "+f"(d[49]), "+f"(d[50]), "+f"(d[51]), "+f"(d[52]), "+f"(d[53]), "+f"(d[54]), "+f"(d[55]), "+f"(d[56]), "+f"(d[57]), "+f"(d[58]), "+f"(d[59]), "+f"(d[60]), "+f"(d[61]), "+f"(d[62]), "+f"(d[63]), "+f"(d[64]), "+f"(d[65]), "+f"(d[66]), "+f"(d[67]), "+f"(d[68]), "+f"(d[69]), "+f"(d[70]), "+f"(d[71]), "+f"(d[72]), "+f"(d[73]), "+f"(d[74]), "+f"(d[75]), "+f"(d[76]), "+f"(d[77]), "+f"(d[78]), "+f"(d[79]), "+f"(d[80]), "+f"(d[81]), "+f"(d[82]), "+f"(d[83]), "+f"(d[84]), "+f"(d[85]), "+f"(d[86]), "+f"(d[87]), "+f"(d[88]), "+f"(d[89]), "+f"(d[90]), "+f"(d[91]), "+f"(d[92]), "+f"(d[93]), "+f"(d[94]), "+f"(d[95]), "+f"(d[96]), "+f"(d[97]), "+f"(d[98]), "+f"(d[99]), "+f"(d[100]), "+f"(d[101]), "+f"(d[102]), "+f"(d[103]), "+f"(d[104]), "+f"(d[105]), "+f"(d[106]), "+f"(d[107]), "+f"(d[108]), "+f"(d[109]), "+f"(d[110]), "+f"(d[111]), "+f"(d[112]), "+f"(d[113]), "+f"(d[114]), "+f"(d[115]), "+f"(d[116]), "+f"(d[117]), "+f"(d[118]), "+f"(d[119]), "+f"(d[120]), "+f"(d[121]), "+f"(d[122]), "+f"(d[123]), "+f"(d[124]), "+f"(d[125]), "+f"(d[126]), "+f"(d[127])
    : "l"(da), "l"(db), "r"(sd));
}
DEVI void mma_kv_init(float* d, uint32_t a0, uint32_t a1, uint32_t a2, uint32_t a3, uint64_t db) {
  asm volatile("wgmma.mma_async.sync.aligned.m64n72k16.f32.bf16.bf16 {%0, %1, %2, %3, %4, %5, %6, %7, %8, %9, %10, %11, %12, %13, %14, %15, %16, %17, %18, %19, %20, %21, %22, %23, %24, %25, %26, %27, %28, %29, %30, %31, %32, %33, %34, %35}, {%36,%37,%38,%39}, %40, 0, 1, 1, 1;\n"
    : "=f"(d[0]), "=f"(d[1]), "=f"(d[2]), "=f"(d[3]), "=f"(d[4]), "=f"(d[5]), "=f"(d[6]), "=f"(d[7]), "=f"(d[8]), "=f"(d[9]), "=f"(d[10]), "=f"(d[11]), "=f"(d[12]), "=f"(d[13]), "=f"(d[14]), "=f"(d[15]), "=f"(d[16]), "=f"(d[17]), "=f"(d[18]), "=f"(d[19]), "=f"(d[20]), "=f"(d[21]), "=f"(d[22]), "=f"(d[23]), "=f"(d[24]), "=f"(d[25]), "=f"(d[26]), "=f"(d[27]), "=f"(d[28]), "=f"(d[29]), "=f"(d[30]), "=f"(d[31]), "=f"(d[32]), "=f"(d[33]), "=f"(d[34]), "=f"(d[35])
    : "r"(a0), "r"(a1), "r"(a2), "r"(a3), "l"(db));
}
DEVI void mma_kv_acc(float* d, uint32_t a0, uint32_t a1, uint32_t a2, uint32_t a3, uint64_t db) {
  asm volatile("wgmma.mma_async.sync.aligned.m64n72k16.f32.bf16.bf16 {%0, %1, %2, %3, %4, %5, %6, %7, %8, %9, %10, %11, %12, %13, %14, %15, %16, %17, %18, %19, %20, %21, %22, %23, %24, %25, %26, %27, %28, %29, %30, %31, %32, %33, %34, %35}, {%36,%37,%38,%39}, %40, 1, 1, 1, 1;\n"
    : "+f"(d[0]), "+f"(d[1]), "+f"(d[2]), "+f"(d[3]), "+f"(d[4]), "+f"(d[5]), "+f"(d[6]), "+f"(d[7]), "+f"(d[8]), "+f"(d[9]), "+f"(d[10]), "+f"(d[11]), "+f"(d[12]), "+f"(d[13]), "+f"(d[14]), "+f"(d[15]), "+f"(d[16]), "+f"(d[17]), "+f"(d[18]), "+f"(d[19]), "+f"(d[20]), "+f"(d[21]), "+f"(d[22]), "+f"(d[23]), "+f"(d[24]), "+f"(d[25]), "+f"(d[26]), "+f"(d[27]), "+f"(d[28]), "+f"(d[29]), "+f"(d[30]), "+f"(d[31]), "+f"(d[32]), "+f"(d[33]), "+f"(d[34]), "+f"(d[35])
    : "r"(a0), "r"(a1), "r"(a2), "r"(a3), "l"(db));
}
DEVI void mma_o_init(float* d, uint32_t a0, uint32_t a1, uint32_t a2, uint32_t a3, uint64_t db) {
  asm volatile("wgmma.mma_async.sync.aligned.m64n40k16.f32.bf16.bf16 {%0, %1, %2, %3, %4, %5, %6, %7, %8, %9, %10, %11, %12, %13, %14, %15, %16, %17, %18, %19}, {%20,%21,%22,%23}, %24, 0, 1, 1, 1;\n"
    : "=f"(d[0]), "=f"(d[1]), "=f"(d[2]), "=f"(d[3]), "=f"(d[4]), "=f"(d[5]), "=f"(d[6]), "=f"(d[7]), "=f"(d[8]), "=f"(d[9]), "=f"(d[10]), "=f"(d[11]), "=f"(d[12]), "=f"(d[13]), "=f"(d[14]), "=f"(d[15]), "=f"(d[16]), "=f"(d[17]), "=f"(d[18]), "=f"(d[19])
    : "r"(a0), "r"(a1), "r"(a2), "r"(a3), "l"(db));
}
DEVI void mma_o_acc(float* d, uint32_t a0, uint32_t a1, uint32_t a2, uint32_t a3, uint64_t db) {
  asm volatile("wgmma.mma_async.sync.aligned.m64n40k16.f32.bf16.bf16 {%0, %1, %2, %3, %4, %5, %6, %7, %8, %9, %10, %11, %12, %13, %14, %15, %16, %17, %18, %19}, {%20,%21,%22,%23}, %24, 1, 1, 1, 1;\n"
    : "+f"(d[0]), "+f"(d[1]), "+f"(d[2]), "+f"(d[3]), "+f"(d[4]), "+f"(d[5]), "+f"(d[6]), "+f"(d[7]), "+f"(d[8]), "+f"(d[9]), "+f"(d[10]), "+f"(d[11]), "+f"(d[12]), "+f"(d[13]), "+f"(d[14]), "+f"(d[15]), "+f"(d[16]), "+f"(d[17]), "+f"(d[18]), "+f"(d[19])
    : "r"(a0), "r"(a1), "r"(a2), "r"(a3), "l"(db));
}
DEVI void fft1_init(uint32_t* d, uint32_t a0, uint32_t a1, uint32_t a2, uint32_t a3, uint64_t db) {
  asm volatile("wgmma.mma_async.sync.aligned.m64n128k16.f16.f16.f16 {%0, %1, %2, %3, %4, %5, %6, %7, %8, %9, %10, %11, %12, %13, %14, %15, %16, %17, %18, %19, %20, %21, %22, %23, %24, %25, %26, %27, %28, %29, %30, %31}, {%32,%33,%34,%35}, %36, 0, 1, 1, 1;\n"
    : "=r"(d[0]), "=r"(d[1]), "=r"(d[2]), "=r"(d[3]), "=r"(d[4]), "=r"(d[5]), "=r"(d[6]), "=r"(d[7]), "=r"(d[8]), "=r"(d[9]), "=r"(d[10]), "=r"(d[11]), "=r"(d[12]), "=r"(d[13]), "=r"(d[14]), "=r"(d[15]), "=r"(d[16]), "=r"(d[17]), "=r"(d[18]), "=r"(d[19]), "=r"(d[20]), "=r"(d[21]), "=r"(d[22]), "=r"(d[23]), "=r"(d[24]), "=r"(d[25]), "=r"(d[26]), "=r"(d[27]), "=r"(d[28]), "=r"(d[29]), "=r"(d[30]), "=r"(d[31])
    : "r"(a0), "r"(a1), "r"(a2), "r"(a3), "l"(db));
}
DEVI void fft1_acc(uint32_t* d, uint32_t a0, uint32_t a1, uint32_t a2, uint32_t a3, uint64_t db) {
  asm volatile("wgmma.mma_async.sync.aligned.m64n128k16.f16.f16.f16 {%0, %1, %2, %3, %4, %5, %6, %7, %8, %9, %10, %11, %12, %13, %14, %15, %16, %17, %18, %19, %20, %21, %22, %23, %24, %25, %26, %27, %28, %29, %30, %31}, {%32,%33,%34,%35}, %36, 1, 1, 1, 1;\n"
    : "+r"(d[0]), "+r"(d[1]), "+r"(d[2]), "+r"(d[3]), "+r"(d[4]), "+r"(d[5]), "+r"(d[6]), "+r"(d[7]), "+r"(d[8]), "+r"(d[9]), "+r"(d[10]), "+r"(d[11]), "+r"(d[12]), "+r"(d[13]), "+r"(d[14]), "+r"(d[15]), "+r"(d[16]), "+r"(d[17]), "+r"(d[18]), "+r"(d[19]), "+r"(d[20]), "+r"(d[21]), "+r"(d[22]), "+r"(d[23]), "+r"(d[24]), "+r"(d[25]), "+r"(d[26]), "+r"(d[27]), "+r"(d[28]), "+r"(d[29]), "+r"(d[30]), "+r"(d[31])
    : "r"(a0), "r"(a1), "r"(a2), "r"(a3), "l"(db));
}
DEVI void fft2_init(uint32_t* d, uint32_t a0, uint32_t a1, uint32_t a2, uint32_t a3, uint64_t db) {
  asm volatile("wgmma.mma_async.sync.aligned.m64n32k16.f16.f16.f16 {%0, %1, %2, %3, %4, %5, %6, %7}, {%8,%9,%10,%11}, %12, 0, 1, 1, 0;\n"
    : "=r"(d[0]), "=r"(d[1]), "=r"(d[2]), "=r"(d[3]), "=r"(d[4]), "=r"(d[5]), "=r"(d[6]), "=r"(d[7])
    : "r"(a0), "r"(a1), "r"(a2), "r"(a3), "l"(db));
}
DEVI void fft2_acc(uint32_t* d, uint32_t a0, uint32_t a1, uint32_t a2, uint32_t a3, uint64_t db) {
  asm volatile("wgmma.mma_async.sync.aligned.m64n32k16.f16.f16.f16 {%0, %1, %2, %3, %4, %5, %6, %7}, {%8,%9,%10,%11}, %12, 1, 1, 1, 0;\n"
    : "+r"(d[0]), "+r"(d[1]), "+r"(d[2]), "+r"(d[3]), "+r"(d[4]), "+r"(d[5]), "+r"(d[6]), "+r"(d[7])
    : "r"(a0), "r"(a1), "r"(a2), "r"(a3), "l"(db));
}
DEVI void fft3r_init(float* d, uint32_t a0, uint32_t a1, uint32_t a2, uint32_t a3, uint64_t db) {
  asm volatile("wgmma.mma_async.sync.aligned.m64n32k16.f32.f16.f16 {%0, %1, %2, %3, %4, %5, %6, %7, %8, %9, %10, %11, %12, %13, %14, %15}, {%16,%17,%18,%19}, %20, 0, 1, 1, 0;\n"
    : "=f"(d[0]), "=f"(d[1]), "=f"(d[2]), "=f"(d[3]), "=f"(d[4]), "=f"(d[5]), "=f"(d[6]), "=f"(d[7]), "=f"(d[8]), "=f"(d[9]), "=f"(d[10]), "=f"(d[11]), "=f"(d[12]), "=f"(d[13]), "=f"(d[14]), "=f"(d[15])
    : "r"(a0), "r"(a1), "r"(a2), "r"(a3), "l"(db));
}
DEVI void fft3r_acc(float* d, uint32_t a0, uint32_t a1, uint32_t a2, uint32_t a3, uint64_t db) {
  asm volatile("wgmma.mma_async.sync.aligned.m64n32k16.f32.f16.f16 {%0, %1, %2, %3, %4, %5, %6, %7, %8, %9, %10, %11, %12, %13, %14, %15}, {%16,%17,%18,%19}, %20, 1, 1, 1, 0;\n"
    : "+f"(d[0]), "+f"(d[1]), "+f"(d[2]), "+f"(d[3]), "+f"(d[4]), "+f"(d[5]), "+f"(d[6]), "+f"(d[7]), "+f"(d[8]), "+f"(d[9]), "+f"(d[10]), "+f"(d[11]), "+f"(d[12]), "+f"(d[13]), "+f"(d[14]), "+f"(d[15])
    : "r"(a0), "r"(a1), "r"(a2), "r"(a3), "l"(db));
}
DEVI void fft3_init(float* d, uint64_t da, uint64_t db) {
  asm volatile("wgmma.mma_async.sync.aligned.m64n32k16.f32.f16.f16 {%0, %1, %2, %3, %4, %5, %6, %7, %8, %9, %10, %11, %12, %13, %14, %15}, %16, %17, 0, 1, 1, 1, 0;\n"
    : "=f"(d[0]), "=f"(d[1]), "=f"(d[2]), "=f"(d[3]), "=f"(d[4]), "=f"(d[5]), "=f"(d[6]), "=f"(d[7]), "=f"(d[8]), "=f"(d[9]), "=f"(d[10]), "=f"(d[11]), "=f"(d[12]), "=f"(d[13]), "=f"(d[14]), "=f"(d[15])
    : "l"(da), "l"(db));
}
DEVI void fft3_acc(float* d, uint64_t da, uint64_t db) {
  asm volatile("wgmma.mma_async.sync.aligned.m64n32k16.f32.f16.f16 {%0, %1, %2, %3, %4, %5, %6, %7, %8, %9, %10, %11, %12, %13, %14, %15}, %16, %17, 1, 1, 1, 1, 0;\n"
    : "+f"(d[0]), "+f"(d[1]), "+f"(d[2]), "+f"(d[3]), "+f"(d[4]), "+f"(d[5]), "+f"(d[6]), "+f"(d[7]), "+f"(d[8]), "+f"(d[9]), "+f"(d[10]), "+f"(d[11]), "+f"(d[12]), "+f"(d[13]), "+f"(d[14]), "+f"(d[15])
    : "l"(da), "l"(db));
}

__device__ __align__(128) const uint32_t g_tables[2560] = {
0xa11ba1e4,0xa51ba5e4,0x18b61248,0x1cb61648,0x9f12a052,0xa311a452,0x1d7f1bdb,0x217f1fdb,0x9bdb9d7f,0x9fdba17f,0x20521f12,0x24522311,
0x924898b6,0x96489cb6,0x21e4211b,0x25e4251b,0xaa63ab5f,0xae5faf59,0x21e41bdb,0x25e41fdb,0xa86ba967,0xac6aad65,0x26e024e9,0x2ade28e8,
0xa4e9a6e0,0xa8e8aade,0x2967286b,0x2d652c6a,0x9bdba1e4,0x9fdba5e4,0x2b5f2a63,0x2f592e5f,0xadc2aea7,0xb1b6b294,0x254d1f12,0x294d2311,
0xabf6acde,0xafefb0d7,0x2a31286b,0x2e2d2c6a,0xa86baa31,0xac6aae2d,0x2cde2bf6,0x30d72fef,0x9f12a54d,0xa311a94d,0x2ea72dc2,0x329431b6,
0xb02cb0d2,0xb41ab4b7,0x27a9211b,0x2ba7251b,0xadc2af0c,0xb1b6b2f7,0x2c792a63,0x30742e5f,0xaa63ac79,0xae5fb074,0x2f0c2dc2,0x32f731b6,
0xa11ba7a9,0xa51baba7,0x30d2302c,0x34b7341a,0xb17ab257,0xb552b61a,0x290222ad,0x2d0026ad,0xaf8cb09f,0xb371b487,0x2ddc2c2e,0x31cf3029,
0xac2eaddc,0xb029b1cf,0x309f2f8c,0x34873371,0xa2ada902,0xa6adad00,0x3257317a,0x361a3552,0xb2cdb3e3,0xb682b76f,0x2a312420,0x2e2d281f,
0xb0acb1bb,0xb493b58d,0x2f3f2d2a,0x33283122,0xad2aaf3f,0xb122b328,0x31bb30ac,0x358d3493,0xa420aa31,0xa81fae2d,0x33e332cd,0x376f3682,
0xb413b4bc,0xb7a6b85a,0x2b5f24e9,0x2f5928e8,0xb194b2da,0xb56ab68d,0x30522e28,0x343e3219,0xae28b052,0xb219b43e,0x32da3194,0x368d356a,
0xa4e9ab5f,0xa8e8af59,0x34bc3413,0x385a37a6,0xb4c3b58c,0xb85fb8f3,0x2c4725b2,0x304229b1,0xb27eb3fd,0xb63cb785,0x31062f26,0x34e7330f,
0xaf26b106,0xb30fb4e7,0x33fd327e,0x3785363c,0xa5b2ac47,0xa9b1b042,0x358c34c3,0x38f3385f,0xb577b662,0xb8e5b982,0x2cde267b,0x30d72a7a,
0xb36bb493,0xb70ab83a,0x31bb3012,0x358d3402,0xb012b1bb,0xb402b58d,0x3493336b,0x383a370a,0xa67bacde,0xaa7ab0d7,0x36623577,0x398238e5,
0xb630b741,0xb962ba04,0x2d762744,0x316c2b43,0xb42eb52a,0xb7d2b8ad,0x32713092,0x3631347b,0xb092b271,0xb47bb631,0x352a342e,0x38ad37d2,
0xa744ad76,0xab43b16c,0x37413630,0x3a043962,0xb6eeb815,0xb9d6ba7a,0x2e0e2807,0x32012c06,0xb4a7b5c4,0xb84ab91b,0x33293113,0x36d234f3,
0xb113b329,0xb4f3b6d2,0x35c434a7,0x391b384a,0xa807ae0e,0xac06b201,0x381536ee,0x3a7a39d6,0xb7b4b88e,0xba41bae1,0x2ea7286b,0x32942c6a,
0xb523b662,0xb8a8b982,0x33e33194,0x376f356a,0xb194b3e3,0xb56ab76f,0x36623523,0x398238a8,0xa86baea7,0xac6ab294,0x388e37b4,0x3ae13a41,
0xb841b90f,0xbaa2bb3a,0x2f3f28d0,0x33282cce,0xb5a1b705,0xb902b9e3,0x344f3216,0x380535df,0xb216b44f,0xb5dfb805,0x370535a1,0x39e33902,
0xa8d0af3f,0xacceb328,0x390f3841,0x3b3a3aa2,0xb8acb997,0xbaf7bb83,0x2fd82935,0x33ba2d33,0xb621b7ac,0xb958ba3d,0x34ae3298,0x38503654,
0xb298b4ae,0xb654b850,0x37ac3621,0x3a3d3958,0xa935afd8,0xad33b3ba,0x399738ac,0x3b833af7,0xb91cba28,0xbb42bbbc,0x30392999,0x34262d97,
0xb6a4b82d,0xb9aaba90,0x350e331c,0x389936c6,0xb31cb50e,0xb6c6b899,0x382d36a4,0x3a9039aa,0xa999b039,0xad97b426,0x3a28391c,0x3bbc3b42,
0xb992bac3,0xbb81bbe3,0x308529fe,0x346f2dfb,0xb72ab886,0xb9f8badb,0x357033a0,0x38e03737,0xb3a0b570,0xb737b8e0,0x3886372a,0x3adb39f8,
0xa9feb085,0xadfbb46f,0x3ac33992,0x3be33b81,0x39cf3b16,0x3b9c3bf1,0xb0acaa31,0xb493ae2d,0x376f38b4,0x3a1d3afe,0xb5a1b3e3,0xb902b76f,
0x33e335a1,0x376f3902,0xb8b4b76f,0xbafeba1d,0x2a3130ac,0x2e2d3493,0xbb16b9cf,0xbbf1bb9c,0x39563a74,0x3b633bd2,0xb05fa9cc,0xb44badc9,
0x36e73859,0x39d23ab6,0xb53fb35e,0xb8bcb6ff,0x335e353f,0x36ff38bc,0xb859b6e7,0xbab6b9d2,0x29cc305f,0x2dc9344b,0xba74b956,0xbbd2bb63,
0x38e339de,0x3b1e3ba1,0xb012a967,0xb402ad65,0x36623801,0x39823a67,0xb4deb2da,0xb874b68d,0x32da34de,0x368d3874,0xb801b662,0xba67b982,
0x29673012,0x2d653402,0xb9deb8e3,0xbba1bb1e,0x38763952,0x3ace3b60,0xaf8ca902,0xb371ad00,0x35e13758,0x392e3a11,0xb47eb257,0xb82ab61a,
0x3257347e,0x361a382a,0xb758b5e1,0xba11b92e,0x29022f8c,0x2d003371,0xb952b876,0xbb60bace,0x380d38ce,0x3a733b10,0xaef3a89e,0xb2deac9c,
0x356236b3,0x38d639b3,0xb420b1d5,0xb7bdb5a5,0x31d53420,0x35a537bd,0xb6b3b562,0xb9b3b8d6,0x289e2ef3,0x2c9c32de,0xb8ceb80d,0xbb10ba73,
0x37503851,0x3a0d3ab0,0xae5aa839,0xb24bac38,0x34e53613,0x387a394f,0xb386b153,0xb721b52f,0x31533386,0x352f3721,0xb613b4e5,0xb94fb87a,
0x28392e5a,0x2c38324b,0xb851b750,0xbab0ba0d,0x368e37b4,0x399d3a41,0xadc2a7a9,0xb1b6aba7,0x346a3577,0x381a38e5,0xb2cdb0d2,0xb682b4b7,
0x30d232cd,0x34b73682,0xb577b46a,0xb8e5b81a,0x27a92dc2,0x2ba731b6,0xb7b4b68e,0xba41b99d,0x35d236d1,0x392439c5,0xad2aa6e0,0xb122aade,
0x33e334de,0x376f3874,0xb216b052,0xb5dfb43e,0x30523216,0x343e35df,0xb4deb3e3,0xb874b76f,0x26e02d2a,0x2ade3122,0xb6d1b5d2,0xb9c5b924,
0x351c35f6,0x38a3393c,0xac93a617,0xb08daa16,0x32f43448,0x36a437fe,0xb160afa5,0xb53ab389,0x2fa53160,0x3389353a,0xb448b2f4,0xb7feb6a4,
0x26172c93,0x2a16308d,0xb5f6b51c,0xb93cb8a3,0x346a3523,0x381a38a8,0xabf6a54d,0xafefa94d,0x3209336b,0x35d4370a,0xb0acaea7,0xb493b294,
0x2ea730ac,0x32943493,0xb36bb209,0xb70ab5d4,0x254d2bf6,0x294d2fef,0xb523b46a,0xb8a8b81a,0x33783456,0x3715380a,0xaac8a484,0xaec3a884,
0x3120324a,0x34ff360e,0xaff2ada9,0xb3d3b19e,0x2da92ff2,0x319e33d3,0xb24ab120,0xb60eb4ff,0x24842ac8,0x28842ec3,0xb456b378,0xb80ab715,
0x3223331c,0x35eb36c6,0xa999a376,0xad97a776,0x3039312d,0x3426350b,0xae8dacac,0xb27cb0a6,0x2cac2e8d,0x30a6327c,0xb12db039,0xb50bb426,
0x23762999,0x27762d97,0xb31cb223,0xb6c6b5eb,0x30d23194,0x34b7356a,0xa86ba1e4,0xac6aa5e4,0x2ea73012,0x32943402,0xad2aab5f,0xb122af59,
0x2b5f2d2a,0x2f593122,0xb012aea7,0xb402b294,0x21e4286b,0x25e42c6a,0xb194b0d2,0xb56ab4b7,0x2f0c3012,0x32f73402,0xa67ba052,0xaa7aa452,
0x2cde2df5,0x30d731e8,0xab91a967,0xaf8bad65,0x29672b91,0x2d652f8b,0xadf5acde,0xb1e8b0d7,0x2052267b,0x24522a7a,0xb012af0c,0xb402b2f7,
0x2c792d2a,0x30743122,0xa4209d7f,0xa81fa17f,0x2a312b91,0x2e2d2f8b,0xa8d0a6e0,0xacceaade,0x26e028d0,0x2ade2cce,0xab91aa31,0xaf8bae2d,
0x1d7f2420,0x217f281f,0xad2aac79,0xb122b074,0x27a9286b,0x2ba72c6a,0x9f1298b6,0xa3119cb6,0x254d267b,0x294d2a7a,0xa420a1e4,0xa81fa5e4,
0x21e42420,0x25e4281f,0xa67ba54d,0xaa7aa94d,0x18b61f12,0x1cb62311,0xa86ba7a9,0xac6aaba7,0x3f803f80,0x3f803f80,0x3f803f80,0x3f803f80,
0x3f803f80,0x3f803f80,0x3f803f80,0x3f803f80,0x3f803f80,0x3f803f80,0x3f803f80,0x3f803f80,0x3f803f80,0x3f803f80,0x3f803f80,0x3f803f80,
0x3f803f80,0x3f803f80,0x3f803f80,0x3f803f80,0x3f803f80,0x3f803f80,0x3f803f80,0x3f803f80,0x3f803f80,0x3f803f80,0x3f803f80,0x3f803f80,
0x3f803f80,0x3f803f80,0x3f803f80,0x3f803f80,0x3f803f80,0x3f803f80,0x3f803f80,0x3f803f80,0x3f803f80,0x3f803f80,0x3f803f80,0x3f803f80,
0x3f803f80,0x3f803f80,0x3f803f80,0x3f803f80,0x3f803f80,0x3f803f80,0x3f803f80,0x3f803f80,0x3f803f80,0x3f803f80,0x3f803f80,0x3f803f80,
0x3f803f80,0x3f803f80,0x3f803f80,0x3f803f80,0x3f803f80,0x3f803f80,0x3f803f80,0x3f803f80,0x3f803f80,0x3f803f80,0x3f803f80,0x3f803f80,
0x3f803f80,0x3f803f80,0x3f803f80,0x3f803f80,0x3f803f80,0x3f803f80,0x3f803f80,0x3f803f80,0x3f803f80,0x3f803f80,0x3f803f80,0x3f803f80,
0x3f803f80,0x3f803f80,0x3f803f80,0x3f803f80,0x3f803f80,0x3f803f80,0x3f803f80,0x3f803f80,0x3f803f80,0x3f803f80,0x3f803f80,0x3f803f80,
0x3f803f80,0x3f803f80,0x3f803f80,0x3f803f80,0x3f803f80,0x3f803f80,0x3f803f80,0x3f803f80,0x3f803f80,0x3f803f80,0x3f803f80,0x3f803f80,
0x3f803f80,0x3f803f80,0x3f803f80,0x3f803f80,0x3f803f80,0x3f803f80,0x3f803f80,0x3f803f80,0x3f803f80,0x3f803f80,0x3f803f80,0x3f803f80,
0x3f803f80,0x3f803f80,0x3f803f80,0x3f803f80,0x3f803f80,0x3f803f80,0x3f803f80,0x3f803f80,0x3f803f80,0x3f803f80,0x3f803f80,0x3f803f80,
0x3f803f80,0x3f803f80,0x3f803f80,0x3f803f80,0x3f803f80,0x3f803f80,0x3f803f80,0x3f803f80,0x3f803f80,0x3f803f80,0x3f803f80,0x3f803f80,
0x3f803f80,0x3f803f80,0x3f803f80,0x3f803f80,0x3f803f80,0x3f803f80,0x3f803f80,0x3f803f80,0x3f803f80,0x3f803f80,0x3f803f80,0x3f803f80,
0x3f803f80,0x3f803f80,0x3f803f80,0x3f803f80,0x3f803f80,0x3f803f80,0x3f803f80,0x3f803f80,0x3f803f80,0x3f803f80,0x3f803f80,0x3f803f80,
0x3f803f80,0x3f803f80,0x3f803f80,0x3f803f80,0x3f803f80,0x3f803f80,0x3f803f80,0x3f803f80,0x3f803f80,0x3f803f80,0x3f803f80,0x3f803f80,
0x3f803f80,0x3f803f80,0x3f803f80,0x3f803f80,0x3f803f80,0x3f803f80,0x3f803f80,0x3f803f80,0x3f803f80,0x3f803f80,0x3f803f80,0x3f803f80,
0x3f803f80,0x3f803f80,0x3f803f80,0x3f803f80,0x3f803f80,0x3f803f80,0x3f803f80,0x3f803f80,0x3f803f80,0x3f803f80,0x3f803f80,0x3f803f80,
0x3f803f80,0x3f803f80,0x3f803f80,0x3f803f80,0x3f803f80,0x3f803f80,0x3f803f80,0x3f803f80,0x3f803f80,0x3f803f80,0x3f803f80,0x3f803f80,
0x3f803f80,0x3f803f80,0x3f803f80,0x3f803f80,0x3f803f80,0x3f803f80,0x3f803f80,0x3f803f80,0x3f803f80,0x3f803f80,0x3f803f80,0x3f803f80,
0x3f803f80,0x3f803f80,0x3f803f80,0x3f803f80,0x3f803f80,0x3f803f80,0x3f803f80,0x3f803f80,0x3f803f80,0x3f803f80,0x3f803f80,0x3f803f80,
0x3f803f80,0x3f803f80,0x3f803f80,0x3f803f80,0x3f803f80,0x3f803f80,0x3f803f80,0x3f803f80,0x3f803f80,0x3f803f80,0x3f803f80,0x3f803f80,
0x3f803f80,0x3f803f80,0x3f803f80,0x3f803f80,0x3f803f80,0x3f803f80,0x3f803f80,0x3f803f80,0x3f803f80,0x3f803f80,0x3f803f80,0x3f803f80,
0x3f803f80,0x3f803f80,0x3f803f80,0x3f803f80,0x3f803f80,0x3f803f80,0x3f803f80,0x3f803f80,0x3f803f80,0x3f803f80,0x3f803f80,0x3f803f80,
0x3f803f80,0x3f803f80,0x3f803f80,0x3f803f80,0x3f803f80,0x3f803f80,0x3f803f80,0x3f803f80,0x3f803f80,0x3f803f80,0x3f803f80,0x3f803f80,
0x3f803f80,0x3f803f80,0x3f803f80,0x3f803f80,0x3f803f80,0x3f803f80,0x3f803f80,0x3f803f80,0x3f803f80,0x3f803f80,0x3f803f80,0x3f803f80,
0x3f803f80,0x3f803f80,0x3f803f80,0x3f803f80,0x3f803f80,0x3f803f80,0x3f803f80,0x3f803f80,0x3f803f80,0x3f803f80,0x3f803f80,0x3f803f80,
0x3f803f80,0x3f803f80,0x3f803f80,0x3f803f80,0x3f803f80,0x3f803f80,0x3f803f80,0x3f803f80,0x3f803f80,0x3f803f80,0x3f803f80,0x3f803f80,
0x3f803f80,0x3f803f80,0x3f803f80,0x3f803f80,0x3f803f80,0x3f803f80,0x3f803f80,0x3f803f80,0x3f803f80,0x3f803f80,0x3f803f80,0x3f803f80,
0x3f803f80,0x3f803f80,0x3f803f80,0x3f803f80,0x3f803f80,0x3f803f80,0x3f803f80,0x3f803f80,0x3f803f80,0x3f803f80,0x3f803f80,0x3f803f80,
0x3f803f80,0x3f803f80,0x3f803f80,0x3f803f80,0x3f803f80,0x3f803f80,0x3f803f80,0x3f803f80,0x3f803f80,0x3f803f80,0x3f803f80,0x3f803f80,
0x3f803f80,0x3f803f80,0x3f803f80,0x3f803f80,0x3f803f80,0x3f803f80,0x3f803f80,0x3f803f80,0x3f803f80,0x3f803f80,0x3f803f80,0x3f803f80,
0x3f803f80,0x3f803f80,0x3f803f80,0x3f803f80,0x3f803f80,0x3f803f80,0x3f803f80,0x3f803f80,0x3f803f80,0x3f803f80,0x3f803f80,0x3f803f80,
0x3f803f80,0x3f803f80,0x3f803f80,0x3f803f80,0x3f803f80,0x3f803f80,0x3f803f80,0x3f803f80,0x3f803f80,0x3f803f80,0x3f803f80,0x3f803f80,
0x3f803f80,0x3f803f80,0x3f803f80,0x3f803f80,0x3f803f80,0x3f803f80,0x3f803f80,0x3f803f80,0x3f803f80,0x3f803f80,0x3f803f80,0x3f803f80,
0x3f803f80,0x3f803f80,0x3f803f80,0x3f803f80,0x3f803f80,0x3f803f80,0x3f803f80,0x3f803f80,0x3f803f80,0x3f803f80,0x3f803f80,0x3f803f80,
0x3f803f80,0x3f803f80,0x3f803f80,0x3f803f80,0x3f803f80,0x3f803f80,0x3f803f80,0x3f803f80,0x3f803f80,0x3f803f80,0x3f803f80,0x3f803f80,
0x3f803f80,0x3f803f80,0x3f803f80,0x3f803f80,0x3f803f80,0x3f803f80,0x3f803f80,0x3f803f80,0x3f803f80,0x3f803f80,0x3f803f80,0x3f803f80,
0x3f803f80,0x3f803f80,0x3f803f80,0x3f803f80,0x3f803f80,0x3f803f80,0x3f803f80,0x3f803f80,0x3f803f80,0x3f803f80,0x3f803f80,0x3f803f80,
0x3f803f80,0x3f803f80,0x3f803f80,0x3f803f80,0x3f803f80,0x3f803f80,0x3f803f80,0x3f803f80,0x3f803f80,0x3f803f80,0x3f803f80,0x3f803f80,
0x3f803f80,0x3f803f80,0x3f803f80,0x3f803f80,0x3f803f80,0x3f803f80,0x3f803f80,0x3f803f80,0x3f803f80,0x3f803f80,0x3f803f80,0x3f803f80,
0x3f803f80,0x3f803f80,0x3f803f80,0x3f803f80,0x3f803f80,0x3f803f80,0x3f803f80,0x3f803f80,0x3f803f80,0x3f803f80,0x3f803f80,0x3f803f80,
0x3f803f80,0x3f803f80,0x3f803f80,0x3f803f80,0x3f803f80,0x3f803f80,0x3f803f80,0x3f803f80,0x3f803f80,0x3f803f80,0x3f803f80,0x3f803f80,
0x3f803f80,0x3f803f80,0x3f803f80,0x3f803f80,0x3f803f80,0x3f803f80,0x3f803f80,0x3f803f80,0x3f803f80,0x3f803f80,0x3f803f80,0x3f803f80,
0x3f803f80,0x3f803f80,0x3f803f80,0x3f803f80,0x3bf23bff,0x3ba53bd4,0x3b163b65,0x3a493ab6,0x3b7c3bfb,0x38bc3a60,0x2b43356a,0xb7f3b359,
0x3a933bf1,0x9cb63764,0xba9eb785,0xbb73bbf3,0x39463be2,0xb8cc28e8,0xbb42bbc2,0x3328b70a,0x374e3bcf,0xbbabb648,0xaec3baa9,0x3bfa3994,
0x33403bb7,0xbb85b9fc,0x3a64b0be,0x2c6a3b47,0xa4523b9a,0xb86abbae,0x3b6a3911,0xbbd0ad65,0xb4263b78,0x2adebbe6,0x30f03bfd,0xb5b1bbbc,
0x2f5925e4,0x34b73294,0x376f361a,0x38f3385a,0x35a52c9c,0x3a7338d6,0x3bfd3b87,0x3af13bc9,0x388e2fbd,0x3c003b18,0x387f3b10,0xb5d42f27,
0x3a04316c,0x3a673bfe,0xb6bb33d3,0xbbccbb2f,0x3b1e32f7,0x34933b5c,0xbbf5b86f,0x2d00b9bc,0x3bcb343e,0xb576394f,0xb8d1bbe9,0x3bfb36a4,
0x3c0034ff,0xbaac347b,0x3602ba31,0x32de3bf9,0x3bba35bc,0xbbfdb109,0x3be7aa7a,0xbb7a341a,0x394639cd,0x381538b2,0x358136dd,0x3153341a,
0xbb1eb9c9,0xbbf5bbdd,0xba39bb65,0xb4f3b889,0xb340b93c,0x3966340e,0x3bec3b87,0x37213a7e,0x3c003a4d,0x32193a21,0xbb5eb785,0xb894bbb0,
0xb426389e,0xbb37bb45,0x38b7b3d3,0x397d3bfc,0xbafebac1,0x3b13217f,0xadc93aa9,0xba49bb59,0x3979b7e8,0xb0d73b32,0xb6f4bbe9,0x3af139da,
0x38553b24,0xb9a1ba3d,0x3ab03911,0xbb73b759,0x3a043982,0x3ae13a7a,0x3b833b3a,0x3be33bbc,0x374e3986,0xae9131e8,0xb907b61a,0xbb9cba97,
0xbbcbba0d,0xb9e7bbbd,0x3074b56a,0x3b2a38ad,0x2452b8ee,0x3bda3924,0x363c3b10,0xba90b46f,0x3bba3a89,0xb6e836af,0xba76bbc2,0x39d2ac06,
0xb7c8384a,0xb77abc00,0x3bf8386f,0xb8f33654,0xb9d6baf4,0x3be836ff,0xbb3530be,0x37f3b974,0x3abab737,0xb9af3902,0x3865ba31,0xb5d43b1b,
0x32c62fbd,0x363134cf,0x38653785,0x398b38fd,0xb715b16c,0xbae1b970,0xbbfebbc2,0xba85bb92,0x392e32f7,0x3bf53b6c,0x37a63aa9,0xb7422311,
0xba81b43e,0xb9e7bbfc,0x380fb0be,0x3b963b7f,0x3b7134ff,0x32193b04,0xbc00b911,0x319eb929,0xbbefb5bc,0x36e8b8b2,0x382a3bfd,0xbbffb805,
0x3bf23676,0xbb1331e8,0x376fb9aa,0x2f8b3bde,0xbb7cb72c,0x3be8340e,0xbbfdaa16,0x3bb8b122,0xbbd2bbf1,0xbb60bba1,0xbab0bb10,0xb9c5ba41,
0x3b2c3be2,0x381539df,0xa94d33d3,0xb8a3b52f,0xba19bbcf,0x2e91b5f7,0x3b07386f,0x3b213c00,0x38a83bb7,0xb966aba7,0xbae5bbe9,0x3517b599,
0xb5dfbb9a,0x3bda37b2,0x1fdb3a31,0xbbe0ba1d,0x30293b78,0xbb37ba7a,0x3ad5aa7a,0xa7763aeb,0x2f59bb52,0x377a3bdd,0xbb16b9a6,0x3bf231cf,
0xb5a53b27,0x30d7bbbd,0x2b433bfe,0xb432bbe5,0x3a813a0d,0x3b3f3ae8,0x3bbf3b87,0x3bfb3be5,0xb5dfb8ee,0x3263ad97,0x399d3785,0x3bd03b01,
0xbbefba89,0xb958bb81,0x3389b3d3,0x3b7a394a,0xaf59384a,0xbbf7b9b8,0xb4c3baa9,0x3afb35eb,0x3b7c3af4,0xb825353a,0xb9f8bbe9,0x3a542884,
0x388eb737,0x360e3bf4,0xbbdcb911,0x398bb4db,0xb946bb4f,0x3bc03830,0xbb832a7a,0x38a3b8db,0xbb1e35c8,0x3a35b85f,0xb90739aa,0x3742bab6,
0xb8a8b93c,0xb6c6b80a,0xb402b56a,0xac6ab122,0xbb71ba4d,0xbbd7bbf8,0xb9b3bb10,0xb2deb7bd,0x3029389e,0xb9f4b58d,0xbbc6bbc2,0xb5b1ba00,
0x3bf23ac1,0x2dfb3999,0xbba3b86f,0xb7d2bb6f,0x35a5b7e8,0x3ad83b90,0xb95430be,0xb8e5bbff,0xba93bb24,0x3b682ef5,0xb2013a31,0xb9c5bb9f,
0xba043682,0x33ebbad1,0x35813bfd,0xba85ba5c,0x374e3b76,0xb90cbab3,0x3a3939a6,0xbb21b85a,0xb7c83b52,0x391bba9b,0xba2539aa,0x3afbb889,
0xb9793b27,0x3bc5b80a,0xbb8eaa16,0x38e538ad,0xbaba3af7,0x3b60ad97,0xb27cba2d,0xb98b3bb0,0xbb943ac4,0x3815358d,0x39e3bbea,0xba852c06,
0xbbf93a8c,0xae9139b8,0x3bacb874,0x3742bb59,0xbbe43a50,0xb9663b90,0x340233ba,0x3b96b974,0xbb573a11,0xbbda3bf4,0xb99d3b0d,0xb19e3759,
0xba5839cd,0xbb373ad1,0xbbc63b89,0xbbff3bee,0x3afe3676,0xba29b884,0x391f39a6,0xb7d2ba97,0x39d6372c,0xb3a2bae8,0xb5463bfe,0x3a54ba7e,
0x385537dd,0x3631bbf8,0xbbd63916,0x39c5346f,0x35233845,0x3ae1bb81,0xb96bb0a6,0xb8a33bfc,0x2d333899,0x3bf5b999,0x3487baa5,0xbb213654,
0xb13b38ea,0x39e7b53a,0x3bbfbbc3,0x3517b9da,0xb65f3937,0x32192ef5,0x39b3b790,0x3be0bb1b,0xb8e03982,0xb6e83830,0xb389355e,0xa7763042,
0xbb943682,0x3bebb371,0xbbfe2a7a,0x3bcc3042,0xad33bb76,0xb79b3bd4,0x3b07b9aa,0xbbfa32ad,0x3be4b50b,0xb6c6b8d6,0xb80f3bfe,0x3bfbb835,
0xb65f3bb5,0x3bd7b764,0x9fdbba2d,0xbbd03a41,0xba58330f,0xb9f43bfe,0x382a30a6,0x3b7abb92,0x3a45bbe1,0xadfbb648,0xbb163874,0xbafb3c00,
0x3699afef,0x3ad8b94f,0x3bfdbbc3,0x3a54bb7f,0xbbdf3bfa,0xbb683bae,0xba9e3b0d,0xb98b3a1d,0x35233b4f,0xb08dbbc8,0xa94d3bfd,0x3328bbee,
0xbbf935c8,0x3b0a3294,0xb7a6b9a6,0xad003bd3,0x313bbb98,0xbb3f3a60,0x3ae52a16,0xac6abace,0x3b57b44b,0x3263bb18,0xbc003916,0x32de38fd,
0xb8e03bce,0x3958a8e8,0x3ad5bbea,0xb5b1b52f,0xb8f83185,0xbbf73b5c,0xb76f3aa5,0x37d2a311,0x3b4abbf0,0x3825b9fc,0xab43b3ba,0xb8e53599,
0x31b6acce,0x360eb47b,0x387fb790,0x39c5b929,0x3a9337dd,0xb9a1b924,0x387f3a2d,0xb66bbb01,0xb946b845,0x308d3b45,0x36bbbbea,0xbac73a00,
0x374e3899,0x379bbc00,0xbbf53874,0x393335eb,0xb340b8ea,0xbb3f3b32,0x38d133ba,0x3941bbff,0xa4523937,0x3bd7b902,0x3602bb0d,0xbabd34db,
0x3426b982,0xb9583371,0xbbe73b89,0xb68d3a5c,0xb7c839c9,0x2dfb3294,0x391fb625,0x3bb3bab6,0x3979ba0d,0x3825b8d6,0x3546b6d2,0x3010b359,
0x388ebaf7,0xb9af3a21,0x3a9eb916,0xbb5437bd,0xba043ac4,0x3bebb6af,0xbb42b0a6,0x3840394a,0x3b1eba8c,0xbb0aa17f,0x2ec33aa5,0x3a15bb6f,
0xbbcb3a50,0x36c636ff,0x3a64bbc3,0xba09a884,0x3c00ba11,0x3263ba3d,0xbb6a3790,0xb8503b9f,0xbbba39cd,0xb9f43bc8,0x30f0355e,0x3b4cb8db,
0x3afeb986,0x3bf7bbd4,0x3a25bb63,0x3457b85a,0xb9d6393c,0xbad83a60,0xbb8e3b3d,0xbbef3bc9,0x33403b98,0xa9b1bbed,0xb0743bfe,0x3517bbc9,
0x3c00b44b,0xbaa2b4cf,0x363c3a2d,0x319ebbf3,0x3426bbce,0xbb8b39df,0x3a7630a6,0x2776bb2f,0xbafe3185,0xb4b73b6c,0x3bf8b874,0xaf8bb994,
0xb9793bf0,0x38bc2ba7,0x3b35bbc3,0xb432b6a4,0x3855acce,0x3c00bb04,0x3865bb0d,0xb66bad65,0x3b94bbff,0x38ccba7a,0x294db55e,0xb840341a,
0xad33a5e4,0xb49331e8,0xb7a63625,0xb9333889,0x3bcbb50b,0xbbfe305b,0x3bec2a16,0xbb96b359,0x2452bbb5,0xb87a3ba1,0x3b5eb916,0xbbe02f27,
0xbbba330f,0x35523970,0x38b7bbea,0xbbff370a,0xb7c83be1,0x3ba5b5f7,0x2dc9baa5,0xbbf239bc,0x39d6afef,0x3a73bbfc,0xb6f4b3ba,0xbbb83b47,
0x3ababbfa,0x1cb6b7b2,0xbab03790,0xbb543bf9,0xb52326ad,0xba6738b2,0xbbfe3b89,0xbac73bbc,0xbbf93bff,0xbbab3bdd,0xbb073b63,0xba153a97,
0xb8f83986,0xb77a385f,0xb4c33625,0xaf8b32ad,0xb699393c,0x30d7305b,0x3954b6d2,0x3bb8bace,0xb1b638ee,0x39afb4cf,0x3bdcbba7,0x366bba41,
0x2c38389e,0x3bebb970,0x3581bade,0xbac7352f,0x34e7384a,0x3b0abb6c,0xb907b24b,0xb9333c00,0x383a37e8,0x36c6bbfc,0xbbec38c1,0x39413599,
0x39c03737,0xb263bb04,0xb63c3bf6,0x3abdba1d,0x3aee3682,0xb9f4b8b2,0x38b739f0,0xb68dbaeb,0xba4539c9,0xbb133ab3,0xbba33b63,0xbbf23bd3,
0xbb4a3a0d,0xbbe83bed,0xb9f83b3d,0xb4323835,0xbbdf3a4d,0xb9a13ba1,0x320134ab,0x3b54b8fd,0xbbfc3a89,0xb08d39df,0x3b83b81a,0x3840bb92,
0xbb9e3ac1,0x379b35f7,0x3a39bbd8,0xba15a311,0xbacb3af4,0x3b3faba7,0xb074ba6f,0xba093b7f,0xb9903b24,0x3bd7b7b2,0xbb5eae5f,0x38503929,
0xb7fe3b4f,0x3958ba7a,0xba76395d,0x3b4cb805,0x2c3826ad,0x33ebb109,0x36bbb55e,0x38a3b805,0x3b9ebbff,0x390cba9b,0x2ec3b625,0xb74231cf,
0xb83a2c9c,0xbbfe3ae8,0xb8d13b3d,0x35173122,0xb9903bf1,0x387a2d97,0x3b6abba7,0xb19eb7bd,0x3aeeb16c,0x3552bb81,0xbbe7381a,0x27763a00,
0x3463bbcf,0xbba539b8,0x3a25324b,0x2f8bbb6f,0xbbff343e,0x3a73353a,0xb546ba6f,0xb4323bff,0x32c63b9a,0x9cb6bbf4,0xb27c3bf6,0x366bbb9f,
0xbbfc3bff,0xbbc03be6,0xbb423b89,0xba853aeb,0x34e7a5e4,0x3a35b884,0x3bf5bb63,0x3b21bbde,0x3acbbbfb,0x29b1b80a,0xba6436d2,0xbb963be5,
0xb9c02fbd,0xbaa23bf8,0x360234ab,0x3be0bb01,0xb7fe3be2,0x3b8bb58d,0x30f0bade,0xbbff394a,0x3bb2b2f7,0xb4b7b999,0xb91f3bd8,0x3bf2b5eb,
0x281fbbb7,0xb8bc3b90,0x3b8eb8c1,0xbbb82884,0xbbd234ff,0x3c00aef5,0xbbd6ae5f,0x3b5434db,0xbaba3a4d,0xbb683b18,0xbbd63ba7,0xbc003bf3,
0x3b94ba89,0x3bc0bbfe,0x396bbade,0x3153b70a,0xbbf93ac1,0xb90c3b5c,0x3487324b,0x3b9cb994,0x3be4baf4,0x29b1b94f,0xbbbf38c1,0xb7213b47,
0xbb573b24,0x387a347b,0x39b3bbf6,0xba902d65,0x3a58bb4f,0xbb8b3109,0x338939f0,0x397dbbbc,0xb8f83b76,0x3ba5b884,0xbba39648,0x38f33889,
0x3699bb98,0xb8bc3ae8,0x39f8b9eb,0xbaf138ad,0x3855b8ee,0x360eb764,0x327cb4ab,0x251baf27,0xb523389e,0x33eb28e8,0x39e3b81a,0x3be3bb2f,
0x2d33b84a,0xba353648,0xbbac3bd8,0xb4f339bc,0x313b37e8,0x3bfeb9fc,0x3402ba6f,0xbb2a36a4,0xb65fb737,0xbaa23bae,0x399d2e5f,0x3894bbf9,
0x38e03682,0x3552bbe6,0xbbc6395d,0x39d2341a,0xba45b5c8,0x34b73a9b,0x34c3bc00,0xba493a97,0x3b4a350b,0xba73b80a,0x39543962,0xb7f3ba7e,
0xbbe43bfb,0xbb853bbd,0xbae53b3d,0xba093a7e,0xb65f2fbd,0xbaac3924,0xbc003ba7,0xbabd3bb0,0x3a58bbe2,0xaadeb6af,0xbad5381a,0xbb4c3bfc,
0x3a45b2f7,0x3a29bc00,0xb76fb24b,0xbbb33b59,0xb6993bb7,0x3bc5b6ff,0x2b43ba6f,0xbbef39da,0xbbdf34ff,0x36313902,0x387fbbf6,0xbc003759,
0xac38bb78,0xb8153bc8,0x3b42b95d,0xbbe33042,0x3b9eb676,0xbbf53294,0x3bf51648,0xbb9cb2ad,0xb13b2c9c,0xb576340e,0xb80f36d2,0xb94138ad,
0x3b57bbf1,0x386aba21,0x1fdbb4ab,0xb850346f,0x38e0b16c,0x3bfdbb45,0x382abade,0xb68dac06,0xb8f83bcf,0x391ba17f,0x3b16bbd8,0xb457b654,
0xbb4a343e,0xb3a23b32,0x3bfdb8c1,0xb010b974,0x31b6bb9a,0xbb603a3d,0x3a9e2e5f,0x251bbb1b,0x3bfcb5bc,0xbae1b371,0x36bb39f0,0x3153bbee,
0x34e73b52,0xae91bbd4,0xaec33c00,0x34f3bbd3,0x3bb235c8,0xbbf7b1e8,0x3bf81648,0xbbb331cf,0x3bff350b,0xbad8340e,0x36f4b9eb,0x30103be5,
0x3bd2344b,0xb60e3924,0xb865bbf6,0x3c0037bd,0x3b2c330f,0x33eb3b45,0xbbfeb8c7,0x3153b94a,0x3a193185,0x3a353c00,0xb7a63232,0xbb9cbb6f,
0x38a82fef,0x3bfe3b32,0x380f3adb,0xb7212884,0x35df2cce,0x3aa23902,0x3c003ba9,0x3a903b9f,0x302926ad,0x35523371,0x382a36dd,0x397d38db,
0xb4633b76,0x2dfbbbdd,0x2dc93c00,0xb457bbde,0xa81f3b98,0xb825bbbd,0x3b353962,0xbbefb122,0x32c63bb5,0xbb68ba21,0x3ab0ae2d,0xa51b3b01,
0x37153bce,0xbbc0b6af,0xa94dba6b,0x3be33a00,0x392e3be1,0xb90c217f,0xbb07bbd9,0x34f3b5eb,0x3a813bf0,0xa9b136ff,0xbae5b820,0xbb2abbff,
0x3b713bfa,0x387a3a3d,0x9fdb349f,0xb894b4db,0x3bef3bff,0x3b8b3bc8,0x3ad53b3a,0x39d23a5c,0x3b2cb5bc,0xba673830,0x396bb95d,0xb8403a5c,
0xb92ebb52,0x3bab385f,0xbbac9648,0x3933b85a,0xb8a8372c,0xb576bbed,0x3bbf3962,0xba093359,0x3b713af7,0xb86a34cf,0xb99dbbf6,0x3abd2f27,
0x3029b845,0x3bfd39df,0x33893a6b,0xbb4cb70a,0xbbf2ba8c,0xb91bbb6c,0x34c3b232,0x3bb339bc,0x35a538ea,0xb3a22ba7,0xb9f8b820,0xbbefbb47,
0x3a933a11,0x3b603b04,0x3bdc3ba9,0x3c003bf9,0x37153b78,0xb8ccbad1,0x39e339f0,0xbac7b8db,0x3a19b676,0xb4933ab3,0xb487bc00,0x3a153ab6,
0xba81bb27,0x3b85305b,0xb40239eb,0xb941bbc9,0xb5df37dd,0xbaacbba1,0x39b3ae2d,0x38503bf3,0x3bef3ac4,0x2ade3970,0xbbc6b8c7,0xb68dbb2f,
0xaf59b899,0x3a2935f7,0x3ba33bd9,0x34573994,0xbb7cba50,0xbbc5bbfc,0xb954badb,0xb010b6a4,0x388e3937,0x363137b2,0x3201349f,0xa51b2d65,
0xb1b63bb5,0x9cb6bbf8,0x32013bf6,0xb5d4bbb0,0xac38bbce,0x38cc3b81,0xbb83b8c7,0x3bcc2c06,0x34e73be1,0xbbabb999,0x3a39b232,0x2d003b59,
0xb83abbf0,0x3b85353a,0x30743adb,0xbbfbb974,0x39c03bfa,0xb86a2ef5,0xbb5ebba9,0x32deb759,0xbaeebbff,0xaadeb830,0x3a7636dd,0x3b7a3bee,
0x3bb23bff,0x391b3ab3,0x2dc9361a,0xb7d2b2ad,0xbbffbbfb,0xbbc5bbed,0xbb35bb87,0xba54bace,0xbbdfb44b,0x3c002d97,0xbbdc2e2d,0x3b73b46f,
0x3bfc330f,0xba67358d,0x3581ba6b,0x33283bfc,0xbb9eb185,0x3493b9b8,0x39073bd9,0xbbfab654,0x3acb2fef,0x35763b90,0xbbecb820,0x2c6ab9da,
0xb990acce,0xbaacbbf4,0x363cb49f,0x3bd03b1b,0x37fe26ad,0x3bfd3ad1,0x38b73b3a,0xb5b13042,0xb46325e4,0xba29b85f,0xbbf8bb65,0xbafbbbd3,
0x281fac9c,0x33a2305b,0x36f4356a,0x38e53835,0x383a3b27,0xb966ba60,0x3a643962,0xbb2ab835,0xb99037dd,0x3219bb18,0x36023bf6,0xba90ba41,
0xbaeebac4,0x3b3728e8,0xb0f03a6b,0xb9d2bb92,0x3463b899,0x3b133b5c,0xb91f3232,0xb8f3bc00,0x3bff3a50,0x30d739fc,0xbb8eb820,0xb7f3bb7f,
0x32c63937,0xb9a1b47b,0xbbd6bba9,0xb5d4ba1d,0xbb2cb9cd,0xbbebbbe6,0xb9e3bb3a,0xb328b805,0xb92eb9c9,0xb79bb884,0xb487b61a,0xad00b1cf,
0xbacb372c,0x39e7b8d6,0xb8d139eb,0x3721bace,0xb9c0baf7,0x3bda3764,0xbb6a2e2d,0x3894b8fd,0x37feb845,0x36e83bfe,0xbbe7b8c7,0x397db52f,
0x3bb23a8c,0xb77a3648,0xba25bbd9,0x3a492311,0xa81f38ea,0xbbe8b94f,0xb546badb,0x3af13599,0xbbd2ba11,0xb9afbbae,0x327cb49f,0x3b733929,
0xb715b982,0x308db109,0x396b36dd,0x3bcc3aeb,0x3a193986,0x3b0a3a9b,0x3bac3b65,0x3bfa3bde,0x30003000,0x30003000,0x30003000,0x30003000,
0x2f643000,0x2a1f2da8,0xaa1f0000,0xaf64ada8,0x2da83000,0xada80000,0xada8b000,0x2da88000,0x2a1f3000,0xaf64ada8,0x2f648000,0xaa1f2da8,
0x00003000,0x8000b000,0x00003000,0x8000b000,0xaa1f3000,0x2f64ada8,0xaf640000,0x2a1f2da8,0xada83000,0x2da88000,0x2da8b000,0xada80000,
0xaf643000,0xaa1f2da8,0x2a1f8000,0x2f64ada8,0x30003000,0x30003000,0x30003000,0x30003000,0xaf64b000,0xaa1fada8,0x2a1f8000,0x2f642da8,
0x2da83000,0xada80000,0xada8b000,0x2da88000,0xaa1fb000,0x2f642da8,0xaf640000,0x2a1fada8,0x00003000,0x8000b000,0x00003000,0x8000b000,
0x2a1fb000,0xaf642da8,0x2f648000,0xaa1fada8,0xada83000,0x2da88000,0x2da8b000,0xada80000,0x2f64b000,0x2a1fada8,0xaa1f0000,0xaf642da8,
0x80008000,0x80008000,0x80008000,0x80008000,0xaa1f8000,0xaf64ada8,0xaf64b000,0xaa1fada8,0xada88000,0xada8b000,0x2da88000,0x2da83000,
0xaf648000,0x2a1fada8,0x2a1f3000,0xaf64ada8,0xb0008000,0x30008000,0xb0008000,0x30008000,0xaf648000,0x2a1f2da8,0x2a1fb000,0xaf642da8,
0xada88000,0xada83000,0x2da88000,0x2da8b000,0xaa1f8000,0xaf642da8,0xaf643000,0xaa1f2da8,0x80008000,0x80008000,0x80008000,0x80008000,
0x2a1f8000,0x2f642da8,0x2f643000,0x2a1f2da8,0xada88000,0xada8b000,0x2da88000,0x2da83000,0x2f648000,0xaa1f2da8,0xaa1fb000,0x2f642da8,
0xb0008000,0x30008000,0xb0008000,0x30008000,0x2f648000,0xaa1fada8,0xaa1f3000,0x2f64ada8,0xada88000,0xada83000,0x2da88000,0x2da8b000,
0x2a1f8000,0x2f64ada8,0x2f64b000,0x2a1fada8,0xb0003000,0xb0003000,0xb0003000,0xb0003000,0xaf643000,0xaa1f2da8,0x2a1f0000,0x2f64ada8,
0xada83000,0x2da80000,0x2da8b000,0xada88000,0xaa1f3000,0x2f64ada8,0xaf648000,0x2a1f2da8,0x80003000,0x0000b000,0x80003000,0x0000b000,
0x2a1f3000,0xaf64ada8,0x2f640000,0xaa1f2da8,0x2da83000,0xada88000,0xada8b000,0x2da80000,0x2f643000,0x2a1f2da8,0xaa1f8000,0xaf64ada8,
0xb0003000,0xb0003000,0xb0003000,0xb0003000,0x2f64b000,0x2a1fada8,0xaa1f8000,0xaf642da8,0xada83000,0x2da80000,0x2da8b000,0xada88000,
0x2a1fb000,0xaf642da8,0x2f640000,0xaa1fada8,0x80003000,0x0000b000,0x80003000,0x0000b000,0xaa1fb000,0x2f642da8,0xaf648000,0x2a1fada8,
0x2da83000,0xada88000,0xada8b000,0x2da80000,0xaf64b000,0xaa1fada8,0x2a1f0000,0x2f642da8,0x80008000,0x80008000,0x80008000,0x80008000,
0x2a1f8000,0x2f64ada8,0x2f64b000,0x2a1fada8,0x2da88000,0x2da8b000,0xada88000,0xada83000,0x2f648000,0xaa1fada8,0xaa1f3000,0x2f64ada8,
0x30008000,0xb0008000,0x30008000,0xb0008000,0x2f648000,0xaa1f2da8,0xaa1fb000,0x2f642da8,0x2da88000,0x2da83000,0xada88000,0xada8b000,
0x2a1f8000,0x2f642da8,0x2f643000,0x2a1f2da8,0x80008000,0x80008000,0x80008000,0x80008000,0xaa1f8000,0xaf642da8,0xaf643000,0xaa1f2da8,
0x2da88000,0x2da8b000,0xada88000,0xada83000,0xaf648000,0x2a1f2da8,0x2a1fb000,0xaf642da8,0x30008000,0xb0008000,0x30008000,0xb0008000,
0xaf648000,0x2a1fada8,0x2a1f3000,0xaf64ada8,0x2da88000,0x2da83000,0xada88000,0xada8b000,0xaa1f8000,0xaf64ada8,0xaf64b000,0xaa1fada8,
0x00000000,0x00000000,0x00000000,0x00000000,0x2a1f0000,0x2f642da8,0x2f643000,0x2a1f2da8,0x2da80000,0x2da83000,0xada80000,0xada8b000,
0x2f640000,0xaa1f2da8,0xaa1fb000,0x2f642da8,0x30000000,0xb0000000,0x30000000,0xb0000000,0x2f640000,0xaa1fada8,0xaa1f3000,0x2f64ada8,
0x2da80000,0x2da8b000,0xada80000,0xada83000,0x2a1f0000,0x2f64ada8,0x2f64b000,0x2a1fada8,0x00000000,0x00000000,0x00000000,0x00000000,
0xaa1f0000,0xaf64ada8,0xaf64b000,0xaa1fada8,0x2da80000,0x2da83000,0xada80000,0xada8b000,0xaf640000,0x2a1fada8,0x2a1f3000,0xaf64ada8,
0x30000000,0xb0000000,0x30000000,0xb0000000,0xaf640000,0x2a1f2da8,0x2a1fb000,0xaf642da8,0x2da80000,0x2da8b000,0xada80000,0xada83000,
0xaa1f0000,0xaf642da8,0xaf643000,0xaa1f2da8,0x30003000,0x30003000,0x30003000,0x30003000,0x2f643000,0x2a1f2da8,0xaa1f0000,0xaf64ada8,
0x2da83000,0xada80000,0xada8b000,0x2da88000,0x2a1f3000,0xaf64ada8,0x2f648000,0xaa1f2da8,0x00003000,0x8000b000,0x00003000,0x8000b000,
0xaa1f3000,0x2f64ada8,0xaf640000,0x2a1f2da8,0xada83000,0x2da88000,0x2da8b000,0xada80000,0xaf643000,0xaa1f2da8,0x2a1f8000,0x2f64ada8,
0x30003000,0x30003000,0x30003000,0x30003000,0xaf64b000,0xaa1fada8,0x2a1f8000,0x2f642da8,0x2da83000,0xada80000,0xada8b000,0x2da88000,
0xaa1fb000,0x2f642da8,0xaf640000,0x2a1fada8,0x00003000,0x8000b000,0x00003000,0x8000b000,0x2a1fb000,0xaf642da8,0x2f648000,0xaa1fada8,
0xada83000,0x2da88000,0x2da8b000,0xada80000,0x2f64b000,0x2a1fada8,0xaa1f0000,0xaf642da8,0x00000000,0x00000000,0x00000000,0x00000000,
0xaa1f0000,0xaf642da8,0xaf643000,0xaa1f2da8,0xada80000,0xada83000,0x2da80000,0x2da8b000,0xaf640000,0x2a1f2da8,0x2a1fb000,0xaf642da8,
0xb0000000,0x30000000,0xb0000000,0x30000000,0xaf640000,0x2a1fada8,0x2a1f3000,0xaf64ada8,0xada80000,0xada8b000,0x2da80000,0x2da83000,
0xaa1f0000,0xaf64ada8,0xaf64b000,0xaa1fada8,0x00000000,0x00000000,0x00000000,0x00000000,0x2a1f0000,0x2f64ada8,0x2f64b000,0x2a1fada8,
0xada80000,0xada83000,0x2da80000,0x2da8b000,0x2f640000,0xaa1fada8,0xaa1f3000,0x2f64ada8,0xb0000000,0x30000000,0xb0000000,0x30000000,
0x2f640000,0xaa1f2da8,0xaa1fb000,0x2f642da8,0xada80000,0xada8b000,0x2da80000,0x2da83000,0x2a1f0000,0x2f642da8,0x2f643000,0x2a1f2da8,
0xb0003000,0xb0003000,0xb0003000,0xb0003000,0xaf643000,0xaa1f2da8,0x2a1f0000,0x2f64ada8,0xada83000,0x2da80000,0x2da8b000,0xada88000,
0xaa1f3000,0x2f64ada8,0xaf648000,0x2a1f2da8,0x80003000,0x0000b000,0x80003000,0x0000b000,0x2a1f3000,0xaf64ada8,0x2f640000,0xaa1f2da8,
0x2da83000,0xada88000,0xada8b000,0x2da80000,0x2f643000,0x2a1f2da8,0xaa1f8000,0xaf64ada8,0xb0003000,0xb0003000,0xb0003000,0xb0003000,
0x2f64b000,0x2a1fada8,0xaa1f8000,0xaf642da8,0xada83000,0x2da80000,0x2da8b000,0xada88000,0x2a1fb000,0xaf642da8,0x2f640000,0xaa1fada8,
0x80003000,0x0000b000,0x80003000,0x0000b000,0xaa1fb000,0x2f642da8,0xaf648000,0x2a1fada8,0x2da83000,0xada88000,0xada8b000,0x2da80000,
0xaf64b000,0xaa1fada8,0x2a1f0000,0x2f642da8};

constexpr int kThreads = 384;
constexpr int kCtas = 128;

constexpr uint32_t SM_BASE = 1024;
constexpr uint32_t QKV_STAGE = 32768;
constexpr uint32_t SLOT = 16384;
constexpr uint32_t SM_KV = 2 * SLOT;
constexpr uint32_t SM_Q = 3 * SLOT;
constexpr uint32_t SM_SIG = 131072;
constexpr uint32_t SM_STG = 196608;
constexpr uint32_t SM_Y0 = SM_STG;
constexpr uint32_t SM_YT = SM_STG + 16384;
constexpr uint32_t SM_TW = SM_STG + 24576, SM_ONES = SM_TW + 2048, SM_F1 = SM_ONES + 2048, SM_F2 = SM_F1 + 4096;
constexpr uint32_t SM_BAR = SM_F2 + 2048;
constexpr uint32_t SM_SC = SM_BAR + 640;
constexpr uint32_t SM_TOTAL = 232448;
constexpr uint32_t A_SLOTS = 0xB2910, B_SLOTS = 0xA7654;

enum Bar { B_QKV_EMPTY = 0, B_QKV_DONE = 4, B_CONV_DONE = 5,
           B_OUT_EMPTY = 8,
           B_H_FULL = 16, B_YIN = 19, B_RDY0 = 21, B_RDY1 = 22, B_ZEROED = 23,
           B_OUT_FULL = 24, B_PREP_FULL = 29,
           B_Q_FULL = 32, B_OT_FREE = 36, B_Y_READY = 38, B_FLAGS1 = 39,
           B_SEG = 40, B_SIG_READY = 44, B_KV_READY = 45,
           B_KVP = 48, B_O_WRITTEN = 49,
           B_PREP_EMPTY = 56,
           B_QKV_FULL = 64, B_STG_FREE = 68 };
constexpr uint32_t BAR_LOG2 = 0x13200044;

constexpr int KV_SLICE = 640;
constexpr int XCH_BYTES = 11 * 4096;

struct Params {
  CUtensorMap x, w, wk, wo, outa, k, v, q;
  const __nv_bfloat16* shift_k;
  const __nv_bfloat16* ssm_k;
  const __nv_bfloat16* ssm_d;
  const __nv_bfloat16* q_ptr;
  __nv_bfloat16* out_ptr;
  const __nv_bfloat16* wo_ptr;
  int zero;
};

__device__ __align__(128) uint8_t g_xch[kCtas][XCH_BYTES];
__device__ __align__(128) unsigned g_oflag[128 * 32];
__device__ unsigned g_ready, g_epoch[kCtas];

#define TSTAMP(cond, i) do { } while (0)
#define GSTAMP(cond, i) do { } while (0)
#define LOOPSTAMP(id, cond, i) do { } while (0)

constexpr int kSpinLimit = 1 << 17;

DEVI void mbar_init(uint32_t a, uint32_t c) { asm volatile("mbarrier.init.shared::cta.b64 [%0], %1;" :: "r"(a), "r"(c) : "memory"); }
DEVI void mbar_expect(uint32_t a, uint32_t b) { asm volatile("mbarrier.arrive.expect_tx.shared::cta.b64 _, [%0], %1;" :: "r"(a), "r"(b) : "memory"); }
DEVI void mbar_arrive(uint32_t a) { asm volatile("mbarrier.arrive.shared::cta.b64 _, [%0];" :: "r"(a) : "memory"); }
DEVI void mbar_arrive_if(uint32_t a, bool pred) {
  asm volatile("{\n.reg .pred p;\nsetp.ne.b32 p, %1, 0;\n@p mbarrier.arrive.shared::cta.b64 _, [%0];\n}" :: "r"(a), "r"((int)pred) : "memory");
}
DEVI void mbar_wait(uint32_t a, uint32_t parity) {
  asm volatile("{\n.reg .pred p;\n.reg .u32 n;\nmov.u32 n, 0;\nW_LOOP:\n"
               "mbarrier.try_wait.parity.shared::cta.b64 p, [%0], %1;\nadd.u32 n, n, 1;\n"
               "setp.lt.and.u32 p, n, %2, !p;\n@p bra W_LOOP;\n}"
               :: "r"(a), "r"(parity), "n"(kSpinLimit) : "memory");
}
DEVI bool mbar_test(uint32_t a, uint32_t parity) {
  uint32_t ok;
  asm volatile("{\n.reg .pred p;\nmbarrier.test_wait.parity.shared::cta.b64 p, [%1], %2;\nselp.u32 %0, 1, 0, p;\n}" : "=r"(ok) : "r"(a), "r"(parity) : "memory");
  return ok;
}
DEVI bool elect() {
  uint32_t ok;
  asm volatile("{\n.reg .pred p;\nelect.sync _|p, 0xffffffff;\nselp.u32 %0, 1, 0, p;\n}" : "=r"(ok));
  return ok;
}
DEVI void flag_wait(const unsigned* p, unsigned target) {
  int n = 0; unsigned v;
  do {
    asm volatile("ld.acquire.gpu.global.u32 %0, [%1];" : "=r"(v) : "l"(p) : "memory");
  } while ((int)(v - target) < 0 && ++n < kSpinLimit);
}
DEVI void st_relaxed(void* p, uint32_t v) { asm volatile("st.relaxed.gpu.global.b32 [%0], %1;" :: "l"(p), "r"(v) : "memory"); }
DEVI uint32_t ld_relaxed(const void* p) { uint32_t v; asm volatile("ld.relaxed.gpu.global.b32 %0, [%1];" : "=r"(v) : "l"(p) : "memory"); return v; }
DEVI void ld_relaxed4(uint32_t* v, const void* p) {
  asm volatile("ld.relaxed.gpu.global.v4.b32 {%0,%1,%2,%3}, [%4];" : "=r"(v[0]), "=r"(v[1]), "=r"(v[2]), "=r"(v[3]) : "l"(p) : "memory");
}
template <int N> DEVI bool all_arrived(const uint32_t* v) {
  uint32_t m = v[0];
#pragma unroll
  for (int i = 1; i + 1 < N; i += 2) m = __vimax3_u32(m, v[i], v[i + 1]);
  if (N % 2 == 0) m = max(m, v[N - 1]);
  return __all_sync(0xffffffffu, m != 0xffffffffu);
}
DEVI void flag_add(unsigned* p) {
  asm volatile("fence.release.gpu;\nred.relaxed.gpu.global.add.u32 [%0], 1;" :: "l"(p) : "memory");
}
DEVI unsigned load_epoch(int cta) {
  unsigned v; asm volatile("ld.relaxed.gpu.global.u32 %0, [%1];" : "=r"(v) : "l"(&g_epoch[cta]) : "memory"); return v;
}
DEVI void fence_async_smem() { asm volatile("fence.proxy.async.shared::cta;" ::: "memory"); }
DEVI void bar_sync(int id, int n) { asm volatile("bar.sync %0, %1;" :: "r"(id), "r"(n) : "memory"); }
DEVI void cluster_arrive() { asm volatile("barrier.cluster.arrive.relaxed.aligned;" ::: "memory"); }
DEVI void cluster_wait() { asm volatile("barrier.cluster.wait.aligned;" ::: "memory"); }
DEVI void wg_fence() { asm volatile("wgmma.fence.sync.aligned;" ::: "memory"); }
DEVI void wg_commit() { asm volatile("wgmma.commit_group.sync.aligned;" ::: "memory"); }
template <int N> DEVI void wg_wait() { asm volatile("wgmma.wait_group.sync.aligned %0;" :: "n"(N) : "memory"); }
template <int N> DEVI void pin(uint32_t* r) {
#pragma unroll
  for (int i = 0; i < N; i++) asm volatile("" : "+r"(r[i]) :: "memory");
}
template <int N> DEVI void pin(float* r) {
#pragma unroll
  for (int i = 0; i < N; i++) asm volatile("" : "+f"(r[i]) :: "memory");
}

DEVI void sched_fence(int zero, int id) { asm volatile("{\n.reg .pred p;\nsetp.eq.b32 p, %0, %1;\nS_LOOP:\n@p st.volatile.shared.b32 [%0], %0;\n@p bra S_LOOP;\n}" :: "r"(zero), "r"(id + 1) : "memory"); }
DEVI void pin_range(float* r, int i0, int i1) {
#pragma unroll
  for (int i = i0; i < i1; i++) asm volatile("" : "+f"(r[i]) :: "memory");
}
DEVI void keep(uint32_t& x) { asm volatile("" : "+r"(x) :: "memory"); }
DEVI void keep(int& x) { asm volatile("" : "+r"(x) :: "memory"); }
template <class T> DEVI void keep(T*& x) { asm volatile("" : "+l"(x) :: "memory"); }

DEVI void tma2d(uint32_t dst, const CUtensorMap* m, int c0, int c1, uint32_t bar) {
  asm volatile("cp.async.bulk.tensor.2d.shared::cluster.global.mbarrier::complete_tx::bytes [%0], [%1, {%3, %4}], [%2];"
               :: "r"(dst), "l"(m), "r"(bar), "r"(c0), "r"(c1) : "memory");
}
DEVI void tma2d_mc(uint32_t dst, const CUtensorMap* m, int c0, int c1, uint32_t bar) {
  asm volatile("cp.async.bulk.tensor.2d.shared::cluster.global.mbarrier::complete_tx::bytes.multicast::cluster [%0], [%1, {%3, %4}], [%2], %5;"
               :: "r"(dst), "l"(m), "r"(bar), "r"(c0), "r"(c1), "h"((uint16_t)3) : "memory");
}
DEVI void tma3d(uint32_t dst, const CUtensorMap* m, int c0, int c1, int c2, uint32_t bar) {
  asm volatile("cp.async.bulk.tensor.3d.shared::cluster.global.mbarrier::complete_tx::bytes [%0], [%1, {%3, %4, %5}], [%2];"
               :: "r"(dst), "l"(m), "r"(bar), "r"(c0), "r"(c1), "r"(c2) : "memory");
}
DEVI void tma3d_mc(uint32_t dst, const CUtensorMap* m, int c0, int c1, int c2, uint32_t bar) {
  asm volatile("cp.async.bulk.tensor.3d.shared::cluster.global.mbarrier::complete_tx::bytes.multicast::cluster [%0], [%1, {%3, %4, %5}], [%2], %6;"
               :: "r"(dst), "l"(m), "r"(bar), "r"(c0), "r"(c1), "r"(c2), "h"((uint16_t)3) : "memory");
}
DEVI void tma2d_store(const CUtensorMap* m, uint32_t src, int c0, int c1) {
  asm volatile("cp.async.bulk.tensor.2d.global.shared::cta.bulk_group [%0, {%2, %3}], [%1];" :: "l"(m), "r"(src), "r"(c0), "r"(c1) : "memory");
}
DEVI void bulk_load(uint32_t dst, const void* src, uint32_t bytes, uint32_t bar) {
  asm volatile("cp.async.bulk.shared::cluster.global.mbarrier::complete_tx::bytes [%0], [%1], %2, [%3];" :: "r"(dst), "l"(src), "r"(bytes), "r"(bar) : "memory");
}
DEVI void bulk_store(void* dst, uint32_t src, uint32_t bytes) {
  asm volatile("cp.async.bulk.global.shared::cta.bulk_group [%0], [%1], %2;" :: "l"(dst), "r"(src), "r"(bytes) : "memory");
}
DEVI uint32_t peer_addr(uint32_t a, int rank) { uint32_t r; asm("mapa.shared::cluster.u32 %0, %1, %2;" : "=r"(r) : "r"(a), "r"(rank)); return r; }
DEVI void bulk_to_peer(uint32_t dst, uint32_t src, uint32_t bytes, uint32_t bar, int rank) {
  asm volatile("cp.async.bulk.shared::cluster.shared::cta.mbarrier::complete_tx::bytes [%0], [%1], %2, [%3];"
               :: "r"(peer_addr(dst, rank)), "r"(src), "r"(bytes), "r"(peer_addr(bar, rank)) : "memory");
}
DEVI void l2_prefetch(const void* p, uint32_t bytes) {
  asm volatile("cp.async.bulk.prefetch.L2.global [%0], %1;" :: "l"(p), "r"(bytes) : "memory");
}
DEVI void l2_prefetch2d(const CUtensorMap* m, int c0, int c1) {
  asm volatile("cp.async.bulk.prefetch.tensor.2d.L2.global [%0, {%1, %2}];" :: "l"(m), "r"(c0), "r"(c1) : "memory");
}
DEVI void l2_prefetch3d(const CUtensorMap* m, int c0, int c1, int c2) {
  asm volatile("cp.async.bulk.prefetch.tensor.3d.L2.global [%0, {%1, %2, %3}];" :: "l"(m), "r"(c0), "r"(c1), "r"(c2) : "memory");
}
DEVI uint32_t clock32() { uint32_t t; asm volatile("mov.u32 %0, %%clock;" : "=r"(t) :: "memory"); return t; }
DEVI void delay(uint32_t cycles) { const uint32_t t = clock32(); while (clock32() - t < cycles) { } }
DEVI void bulk_commit() { asm volatile("cp.async.bulk.commit_group;" ::: "memory"); }
DEVI void bulk_wait_all() { asm volatile("cp.async.bulk.wait_group 0;" ::: "memory"); }
DEVI void bulk_wait_read() { asm volatile("cp.async.bulk.wait_group.read 0;" ::: "memory"); }
DEVI void prefetch_map(const CUtensorMap* m) { asm volatile("prefetch.tensormap [%0];" :: "l"(m) : "memory"); }
DEVI void arrive_both(uint32_t bar, int lane, bool pred = true) {
  asm volatile("{\n.reg .pred p;\n.reg .b32 r;\nsetp.ne.b32 p, %2, 0;\nmapa.shared::cluster.u32 r, %0, %1;\n@p mbarrier.arrive.shared::cluster.b64 _, [r];\n}"
               :: "r"(bar), "r"(lane & 1), "r"((int)(pred && lane < 2)) : "memory");
}

DEVI uint64_t make_desc(uint32_t off, uint32_t lbo, uint32_t sbo, uint32_t mode) {
  const uint32_t lo = (off >> 4) + (SM_BASE >> 4) + ((lbo >> 4) << 16), hi = (sbo >> 4) | (mode << 30);
  return ((uint64_t)hi << 32) | lo;
}
DEVI uint32_t pack_bf16(float lo, float hi) { uint32_t r; asm("cvt.rn.bf16x2.f32 %0, %1, %2;" : "=r"(r) : "f"(hi), "f"(lo)); return r; }
DEVI uint32_t pack_f16(float lo, float hi) { uint32_t r; asm("cvt.rn.f16x2.f32 %0, %1, %2;" : "=r"(r) : "f"(hi), "f"(lo)); return r; }
DEVI void stsm4(uint32_t addr, uint32_t r0, uint32_t r1, uint32_t r2, uint32_t r3) {
  asm volatile("stmatrix.sync.aligned.m8n8.x4.shared.b16 [%0], {%1,%2,%3,%4};" :: "r"(addr), "r"(r0), "r"(r1), "r"(r2), "r"(r3) : "memory");
}
DEVI void stsm2(uint32_t addr, uint32_t r0, uint32_t r1) {
  asm volatile("stmatrix.sync.aligned.m8n8.x2.shared.b16 [%0], {%1,%2};" :: "r"(addr), "r"(r0), "r"(r1) : "memory");
}
DEVI void stsm4_t(uint32_t addr, uint32_t r0, uint32_t r1, uint32_t r2, uint32_t r3) {
  asm volatile("stmatrix.sync.aligned.m8n8.x4.trans.shared.b16 [%0], {%1,%2,%3,%4};" :: "r"(addr), "r"(r0), "r"(r1), "r"(r2), "r"(r3) : "memory");
}
DEVI void ldsm4(uint32_t* r, uint32_t addr) {
  asm volatile("ldmatrix.sync.aligned.m8n8.x4.shared.b16 {%0,%1,%2,%3}, [%4];" : "=r"(r[0]), "=r"(r[1]), "=r"(r[2]), "=r"(r[3]) : "r"(addr) : "memory");
}
DEVI void ldsm4_t(uint32_t* r, uint32_t addr) {
  asm volatile("ldmatrix.sync.aligned.m8n8.x4.trans.shared.b16 {%0,%1,%2,%3}, [%4];" : "=r"(r[0]), "=r"(r[1]), "=r"(r[2]), "=r"(r[3]) : "r"(addr) : "memory");
}
DEVI uint32_t lds32(uint32_t a) { uint32_t v; asm volatile("ld.shared.b32 %0, [%1];" : "=r"(v) : "r"(a) : "memory"); return v; }
DEVI uint4 lds128(uint32_t a) {
  uint4 v; asm volatile("ld.shared.v4.b32 {%0,%1,%2,%3}, [%4];" : "=r"(v.x), "=r"(v.y), "=r"(v.z), "=r"(v.w) : "r"(a) : "memory"); return v;
}
DEVI uint32_t bmul2(uint32_t a, uint32_t b) { uint32_t r; asm("mul.rn.bf16x2 %0, %1, %2;" : "=r"(r) : "r"(a), "r"(b)); return r; }
DEVI uint32_t bfma2(uint32_t a, uint32_t b, uint32_t c) { uint32_t r; asm("fma.rn.bf16x2 %0, %1, %2, %3;" : "=r"(r) : "r"(a), "r"(b), "r"(c)); return r; }
DEVI float bf_lo(uint32_t w) { return __uint_as_float(w << 16); }
DEVI float bf_hi(uint32_t w) { return __uint_as_float(w & 0xffff0000u); }
DEVI uint32_t elu1(float a0, float a1) {
  constexpr float L = 1.4426950408889634f;
  float e0, e1;
  asm("ex2.approx.ftz.f32 %0, %1;" : "=f"(e0) : "f"(-fabsf(fmaf(a0, L, -L))));
  asm("ex2.approx.ftz.f32 %0, %1;" : "=f"(e1) : "f"(-fabsf(fmaf(a1, L, -L))));
  return pack_bf16(fmaxf(e0, a0), fmaxf(e1, a1));
}
DEVI float rcp(float x) { float r; asm("rcp.approx.ftz.f32 %0, %1;" : "=f"(r) : "f"(x)); return r; }
DEVI uint32_t add_eps(uint32_t x) { uint32_t r; asm("add.rn.bf16x2 %0, %1, %2;" : "=r"(r) : "r"(x), "r"(0x35863586u)); return r; }

#define FIN 0
DEVI uint32_t hmul(uint32_t a, uint32_t b) { uint32_t r; asm("mul.rn.f16x2 %0, %1, %2;" : "=r"(r) : "r"(a), "r"(b)); return r; }
DEVI uint32_t hfma(uint32_t a, uint32_t b, uint32_t c) { uint32_t r; asm("fma.rn.f16x2 %0, %1, %2, %3;" : "=r"(r) : "r"(a), "r"(b), "r"(c)); return r; }
DEVI uint32_t hneg(uint32_t a) { uint32_t r; asm("neg.f16x2 %0, %1;" : "=r"(r) : "r"(a)); return r; }
DEVI uint32_t hadd(uint32_t a, uint32_t b) { uint32_t r; asm("add.rn.f16x2 %0, %1, %2;" : "=r"(r) : "r"(a), "r"(b)); return r; }
DEVI uint32_t hsub(uint32_t a, uint32_t b) { uint32_t r; asm("sub.rn.f16x2 %0, %1, %2;" : "=r"(r) : "r"(a), "r"(b)); return r; }
struct Cx { uint32_t re, im; };
DEVI Cx cmul(Cx a, Cx b) { return {hfma(a.re, b.re, hneg(hmul(a.im, b.im))), hfma(a.re, b.im, hmul(a.im, b.re))}; }
DEVI Cx cfma(Cx a, Cx b, Cx c) { return {hfma(a.re, b.re, hfma(hneg(a.im), b.im, c.re)), hfma(a.re, b.im, hfma(a.im, b.re, c.im))}; }
DEVI Cx rot(Cx a, Cx t) {
  const uint32_t x = hfma(hneg(t.re), a.im, a.re), y = hfma(t.im, x, a.im);
  return {hfma(hneg(t.re), y, x), y};
}
struct Fft {
  uint32_t fa[8];
  Cx tw[2];
  uint32_t vld;
  uint64_t dF2a, dF2b;
  uint32_t vst;
  DEVI void stage1(uint32_t* d1, uint32_t slot) const {
    wg_fence();
    fft1_init(d1, fa[0], fa[1], fa[2], fa[3], make_desc(slot, 4096, 1024, 1));
    fft1_acc(d1, fa[4], fa[5], fa[6], fa[7], make_desc(slot + 2048, 4096, 1024, 1));
    wg_commit();
  }
  DEVI void stage2(uint32_t* d, const Cx* t) const {
    wg_fence();
    fft2_init(d, t[0].re, t[1].re, t[2].re, t[3].re, dF2a);
    fft2_acc(d, t[0].im, t[1].im, t[2].im, t[3].im, dF2b);
    wg_commit();
  }
  template <int PR> DEVI void fwd(const uint32_t* d1, uint32_t* d2) const {
    Cx t[4];
#pragma unroll
    for (int e = 0; e < 4; e++) {
      const int j = 8 * (PR & 1) + 4 * (e >> 1) + 2 * (PR >> 1) + (e & 1);
      t[e] = rot({d1[2 * j], d1[2 * j + 1]}, tw[e >> 1]);
    }
    stage2(d2 + 8 * PR, t);
  }
  static DEVI Cx U(const uint32_t* d2, int p, int hi) { return {d2[16 * (p >> 1) + 2 * hi + (p & 1)], d2[16 * (p >> 1) + 4 + 2 * hi + (p & 1)]}; }
  static DEVI Cx H(const uint32_t* d2, int p, int hi) { return U(d2 + 8, p, hi); }
  DEVI void prod01(const uint32_t* d2, Cx* p1, uint32_t* d3) const {
    Cx z[4];
#pragma unroll
    for (int hi = 0; hi < 2; hi++) {
      const Cx p0 = cmul(H(d2, 0, hi), U(d2, 0, hi));
      p1[hi] = cfma(H(d2, 1, hi), U(d2, 0, hi), cmul(H(d2, 0, hi), U(d2, 1, hi)));
      z[2 * hi] = {p0.im, p0.re};
      z[2 * hi + 1] = {hsub(p1[hi].im, p0.re), hadd(p1[hi].re, p0.im)};
    }
    stage2(d3, z);
  }
  DEVI void prod23(const uint32_t* d2, const Cx* p1, uint32_t* d3) const {
    Cx z[4];
#pragma unroll
    for (int hi = 0; hi < 2; hi++) {
      const Cx p2 = cfma(H(d2, 2, hi), U(d2, 0, hi), cfma(H(d2, 0, hi), U(d2, 2, hi), cmul(H(d2, 1, hi), U(d2, 1, hi))));
      const Cx z3 = cfma(H(d2, 3, hi), U(d2, 0, hi), cfma(H(d2, 2, hi), U(d2, 1, hi),
                    cfma(H(d2, 1, hi), U(d2, 2, hi), cfma(H(d2, 0, hi), U(d2, 3, hi), {p2.im, hneg(p2.re)}))));
      z[2 * hi] = {hsub(p2.im, p1[hi].re), hadd(p2.re, p1[hi].im)};
      z[2 * hi + 1] = {z3.im, z3.re};
    }
    stage2(d3 + 8, z);
  }
  template <int PB> DEVI void inv(const uint32_t* d3, uint32_t slot) const {
    Cx v[4];
#pragma unroll
    for (int e = 0; e < 4; e++) {
      const int r = 8 * PB + 2 * (e & 1) + (e >> 1);
      v[e] = rot({d3[r], d3[r + 4]}, tw[e & 1]);
    }
    stsm4(slot + (vst ^ (PB * 64)), v[0].im, v[1].im, v[2].im, v[3].im);
    stsm4(slot + 1024 + (vst ^ (PB * 64)), v[0].re, v[1].re, v[2].re, v[3].re);
  }
  DEVI void last(float* dy, uint32_t slot, int wg, bool fenced = false) const {
    if (!fenced) fence_async_smem();
    bar_sync(2 + wg, 128);
    wg_fence();
    fft3_init(dy, make_desc(slot, 4096, 1024, 1), make_desc(SM_F1, 128, 1024, 0));
#pragma unroll
    for (int ks = 1; ks < 4; ks++) fft3_acc(dy, make_desc(slot + ks * 2048, 4096, 1024, 1), make_desc(SM_F1 + ks * 256, 128, 1024, 0));
    wg_commit();
  }
  static DEVI void store_y(const float* dy, uint32_t a) {
    stsm4_t(a, pack_bf16(dy[0], dy[1]), pack_bf16(dy[2], dy[3]), pack_bf16(dy[4], dy[5]), pack_bf16(dy[6], dy[7]));
    stsm4_t(a + 512, pack_bf16(dy[8], dy[9]), pack_bf16(dy[10], dy[11]), pack_bf16(dy[12], dy[13]), pack_bf16(dy[14], dy[15]));
  }
};
DEVI uint32_t normalize(uint32_t* x, uint32_t dst) {
  uint32_t m = x[0];
#pragma unroll
  for (int i = 1; i < 32; i++) asm("max.xorsign.abs.bf16x2 %0, %0, %1;" : "+r"(m) : "r"(x[i]));
  const uint32_t e = min(__reduce_max_sync(0xffffffffu, max(m & 0x7fffu, (m >> 16) & 0x7fffu)) >> 7, 252u);
  if (e > 140) {
#pragma unroll
    for (int i = 0; i < 32; i++) x[i] = bmul2(x[i], 15u * 0x00800080u);
  }
  const uint32_t sc = (e > 140 ? 253u - e : 141u - e) * 0x00800080u;
#pragma unroll
  for (int i = 0; i < 8; i++) {
    uint32_t y[4];
#pragma unroll
    for (int n = 0; n < 4; n++) {
      const uint32_t w = bmul2(x[4 * i + n], sc);
      y[n] = (w & 0x7fff7fffu) * 7u + w;
    }
    stsm4((dst ^ ((i >> 1) << 4)) + (i & 1) * 2048, y[0], y[1], y[2], y[3]);
  }
  return e;
}
#define RFENCE 1
#define EFENCE 0
#define UDESC 1
#define QF 0
#define KF 1
#define TAIL 3
#define DBG 0
#define XPF 3
#define PSTART 5
#define HSTART 3
#define PF0 26
#define PPACE 300
#define FDELAY 200
#define PH0 2
#define QA 4
#define QB 2
#define QC 4
#define S1POS 1
#define NB0 3

__global__ void __cluster_dims__(2, 1, 1) __launch_bounds__(kThreads, 1)
fused_kernel(const __grid_constant__ Params P) {
  extern __shared__ __align__(1024) uint8_t smem[];
  if (threadIdx.x == 0) { prefetch_map(&P.x); prefetch_map(&P.w); prefetch_map(&P.wk); prefetch_map(blockIdx.x & 1 ? &P.v : &P.k); }
  const uint32_t sb = __shfl_sync(0xffffffffu, (uint32_t)__cvta_generic_to_shared(smem), 0);
  const int tid = threadIdx.x, lane = tid & 31;
  const int warp = __shfl_sync(0xffffffffu, tid >> 5, 0);
  const int bc = blockIdx.x >> 1, late = ((bc - 36) * 37) >> 8;
  const int rp = bc < 4 ? 0 : bc < 36 ? (bc - 4) & 7 : bc - 35 - 7 * late, j = bc < 4 ? 4 + bc : bc < 36 ? (bc - 4) >> 3 : 4 + late;
  const int rho = blockIdx.x & 1, cl = 8 * rp + j, cta = 2 * cl + rho, r = rp * 2 + rho;
  auto bar = [&](int i) { return sb + SM_BAR + 8u * i; };
  TSTAMP(tid == 0, 0); GSTAMP(tid == 0, 30);
  auto load_stage = [&](int it) {
    const uint32_t st = sb + (it & 3) * QKV_STAGE, fb = bar(B_QKV_FULL + (it & 3));
    mbar_expect(fb, QKV_STAGE);
    tma2d_mc(st + 24576 + rho * 4096, &P.wk, 1024 + 128 * j + 64 * rho, 32 * it, fb);
    tma3d_mc(st + 8192 + rho * 8192, &P.w, 0, 32 * it, 32 * rho + 2 * j, fb);
    tma2d(st, &P.x, 32 * it, 128 * r, fb);
  };
  if (warp == 8 && elect()) {
    mbar_init(bar(B_QKV_FULL), 1);
    mbar_expect(bar(B_QKV_FULL), QKV_STAGE);
    tma2d(sb, &P.x, 0, 128 * r, bar(B_QKV_FULL));
    tma3d(sb + 24576, &P.w, 0, 0, 16 + 2 * j, bar(B_QKV_FULL));
    tma3d(sb + 8192, &P.w, 0, 0, 2 * j, bar(B_QKV_FULL));
    tma3d(sb + 16384, &P.w, 0, 0, 32 + 2 * j, bar(B_QKV_FULL));
    for (int i = 1; i < 5; i++) mbar_init(bar(B_QKV_FULL + i), 1);
    asm volatile("fence.mbarrier_init.release.cluster;" ::: "memory");
  }
  LOOPSTAMP(3, tid == 256, 13);
  __syncwarp();
  cluster_arrive();

  if (warp < 8) {
    cluster_wait();
    cluster_arrive();
    asm volatile("setmaxnreg.inc.sync.aligned.u32 224;");
    const int wg = warp >> 2, wq = warp & 3;
    const int never = __shfl_sync(0xffffffffu, P.zero, 0);
    const uint32_t orow = wq * 2048 + (lane & 15) * 128, ox = ((lane >> 4) ^ (lane & 7)) << 4;
    float aq[64];
    Fft F;
    uint32_t a1[32];
    {
      float ak[64], avq[128];
      auto k_step = [&](uint32_t st, int kk, int acc) {
        mma_tn(ak, make_desc(st + 24576 + wg * 4096 + kk * 2048, 4096, 1024, 1), make_desc(st + kk * 32, 16, 512, 2), acc);
      };
      auto vq_step = [&](uint32_t st, int kk, int acc) {
        mma_nt256(avq, make_desc(st + wg * 4096 + kk * 32, 16, 512, 2), make_desc(st + 8192 + kk * 2048, 4096, 1024, 1), acc);
      };
#pragma unroll
      for (int i = 0; i < 64; i++) { ak[i] = 1.f; avq[i] = 1.f; avq[64 + i] = 0.f; }
      pin<64>(ak); pin<128>(avq);
      cluster_wait();
      LOOPSTAMP(3, tid == 0, 17);
#pragma unroll 1
      for (int it = 0; it < 29; ++it) {
        mbar_wait(bar(B_QKV_FULL + (it & 3)), (it >> 2) & 1);
        TSTAMP(tid == 0 && it == 0, 1); LOOPSTAMP(1, tid == 0 && it < 27, 1 + it); LOOPSTAMP(3, tid == 0 && it < 12, 1 + it);
        const uint32_t st = (it & 3) * QKV_STAGE;
        wg_fence();
        k_step(st, 0, 1);
        wg_commit();
        wg_wait<1>();
        arrive_both(bar(B_QKV_EMPTY + ((it - 1) & 3)), lane, it > 0);
        wg_fence();
        vq_step(st, 0, 1);
        k_step(st, 1, 1);
        vq_step(st, 1, 1);
        wg_commit();
      }
#pragma unroll 1
      for (int s = 1; s < 4; ++s) {
        mbar_wait(bar(B_QKV_FULL + s), 1);
        wg_fence();
        k_step(s * QKV_STAGE, 0, 1);
        k_step(s * QKV_STAGE, 1, 1);
        wg_commit();
      }
      uint32_t pk[32];
      auto phi_k = [&](int i0, int i1) {
#pragma unroll
        for (int i = i0; i < i1; i++) { pk[i] = elu1(ak[2 * i], ak[2 * i + 1]); asm volatile("" : "+r"(pk[i]) :: "memory"); }
        if (KF) sched_fence(never, i0);
      };
#pragma unroll
      for (int n = 0; n < 6; n++) {
        wg_fence();
        vq_step((1 + (n >> 1)) * QKV_STAGE, n & 1, 1);
        wg_commit();
        if (n == 0) {
          wg_wait<1>();
          pin<64>(ak);
          TSTAMP(tid == 0, 2);
          bar_sync(1, 256);
        }
        phi_k(n ? PH0 + (32 - PH0) * (n - 1) / 5 : 0, PH0 + (32 - PH0) * n / 5);
      }
      mbar_wait(bar(B_SIG_READY), 0);
      ldsm4_t(F.fa, sb + SM_F1 + (lane >> 4) * 1024 + wq * 256 + (lane & 15) * 16);
      ldsm4_t(F.fa + 4, sb + SM_F1 + 2048 + (lane >> 4) * 1024 + wq * 256 + (lane & 15) * 16);
      const uint4 tw = lds128(sb + SM_TW + (tid & 127) * 16);
      F.tw[0] = {tw.x, tw.y}; F.tw[1] = {tw.z, tw.w};
      F.vld = sb + ((lane >> 4) * 8 + (lane & 7)) * 128 + (((2 * wq + ((lane >> 3) & 1)) ^ (lane & 7)) << 4);
      F.dF2a = make_desc(SM_F2, 128, 512, 0) + (UDESC ? (uint64_t)never * 0x100000001ull : 0); F.dF2b = F.dF2a + 16;
      F.vst = sb + (16 * wq + (lane & 7)) * 128 + (((lane >> 3) ^ (lane & 7)) << 4);
      wg_wait<0>();
      pin<128>(avq);
      if (S1POS == 0) F.stage1(a1, SM_SIG + wg * 8192);
      arrive_both(bar(B_QKV_DONE), lane);
      TSTAMP(tid == 0, 3);
#pragma unroll
      for (int t = 0; t < 8; t++) {
        const float* b = avq + 64 + 8 * t;
        stsm4(sb + (t >> 2) * SLOT + wg * 8192 + orow + (ox ^ ((t & 3) << 5)), pack_bf16(b[0], b[1]), pack_bf16(b[2], b[3]), pack_bf16(b[4], b[5]), pack_bf16(b[6], b[7]));
      }
#pragma unroll
      for (int i = 0; i < 64; i++) aq[i] = avq[i];
      fence_async_smem();
      bar_sync(1, 256);
      float dkv[36];
#pragma unroll
      for (int ks = 0; ks < 8; ks++) {
        const uint32_t va = wg * SLOT + ks * 2048;
        const uint64_t db = make_desc(va, SM_ONES - va, 1024, 1);
        uint32_t a[4];
        pin<4>(pk + 4 * ks);
#pragma unroll
        for (int i = 0; i < 4; i++) a[i] = add_eps(pk[4 * ks + i]);
        wg_fence();
        if (ks == 0) mma_kv_init(dkv, a[0], a[1], a[2], a[3], db);
        else mma_kv_acc(dkv, a[0], a[1], a[2], a[3], db);
      }
      wg_commit();
      uint8_t* box = g_xch[warp * 16 + j] + 2 * SLOT + r * KV_SLICE + lane * 16;
      uint8_t* zbox = box + (lane & 1) * 8 * XCH_BYTES + 512 + (lane & 28) - lane * 16;
      keep(box); keep(zbox);
      if (S1POS == 1) F.stage1(a1, SM_SIG + wg * 8192);
      mbar_wait(bar(B_ZEROED), 0);
      wg_wait<S1POS == 1>();
      pin<36>(dkv);
      if (S1POS == 2) F.stage1(a1, SM_SIG + wg * 8192);
      TSTAMP(tid == 0, 4);
      auto put = [&](const float* d) {
#pragma unroll
        for (int m = 0; m < 2; m++)
          asm volatile("st.relaxed.gpu.global.v4.b32 [%0], {%1,%2,%3,%4};" :: "l"(box + m * 8 * XCH_BYTES), "r"(pack_bf16(d[2 * m], d[2 * m + 1])),
                       "r"(pack_bf16(d[2 * m + 4], d[2 * m + 5])), "r"(pack_bf16(d[2 * m + 8], d[2 * m + 9])), "r"(pack_bf16(d[2 * m + 12], d[2 * m + 13])) : "memory");
      };
      if (wq < 2) put(dkv); else put(dkv + 16);
      asm volatile("{\n.reg .pred p;\nsetp.eq.b32 p, %2, 0;\n@p st.relaxed.gpu.global.b32 [%0], %1;\n}" :: "l"(zbox), "f"(lane & 1 ? dkv[34] : dkv[32]), "r"(lane & 2) : "memory");
      __syncwarp();
      mbar_arrive_if(bar(B_KVP), lane == 0);
      TSTAMP(tid == 0, 5);
    }

    uint32_t pq[32];
    auto phi_q = [&](int i0, int i1) {
      pin_range(aq, 2 * i0, 2 * i1);
#pragma unroll
      for (int i = i0; i < i1; i++) { pq[i] = add_eps(elu1(aq[2 * i], aq[2 * i + 1])); keep(pq[i]); }
      if (QF && i1 > i0) sched_fence(never, 40 + i0);
    };
    uint32_t a2[32];
    float by[16];
    auto conv_pair = [&](uint32_t sa, uint32_t ya, uint32_t first) {
      const uint32_t sc = sa + SLOT;
      uint32_t b1[32], b2[32], a3[16], b3[16];
      float ay[16];
      Cx pa[2], pb[2];
      sched_fence(never, 80);
      F.stage1(b1, sc);
      F.prod01(a2, pa, a3);
      F.prod23(a2, pa, a3);
      wg_wait<1>(); pin<32>(b1); pin<8>(a3);
      F.inv<0>(a3, sa);
      F.fwd<0>(b1, b2);
      wg_wait<1>(); pin<8>(a3 + 8);
      F.inv<1>(a3, sa);
      F.fwd<1>(b1, b2);
      if (EFENCE == 1 && !FIN) fence_async_smem();
      F.fwd<2>(b1, b2);
      if (EFENCE == 2 && !FIN) fence_async_smem();
      F.fwd<3>(b1, b2);
      F.last(ay, sa, wg, EFENCE);
      wg_wait<3>(); pin<16>(b2);
      F.prod01(b2, pb, b3);
      wg_wait<2>(); pin<16>(b2 + 16);
      F.prod23(b2, pb, b3);
      mbar_wait(bar(B_RDY1), first);
      wg_wait<1>(); pin<8>(b3); pin<16>(ay);
      F.inv<0>(b3, sc);
      Fft::store_y(ay, ya);
      wg_wait<0>(); pin<8>(b3 + 8);
      F.inv<1>(b3, sc);
    };
    const bool ylocal = (wq >> 1) == rho;
    const uint32_t yoff = sb + (wq & 1) * 1024 + ((lane ^ wg ^ (2 * rho)) << 4);
    const uint32_t ya0 = yoff + (ylocal ? SM_Y0 + wg * 8192 : SM_YT + wg * 4096), ya1 = (yoff ^ 64) + (ylocal ? SM_SIG + wg * 8192 : SM_YT + wg * 4096);
    auto pair_done = [&](uint32_t ya, int seg) {
      pin<16>(by);
      Fft::store_y(by, (ya ^ 32) + 2048);
      if (!RFENCE) fence_async_smem();
      __syncwarp();
      mbar_arrive_if(bar(B_SEG + 2 * seg + wg), lane == 0);
    };
    const uint32_t s0 = SM_SIG + wg * 8192, s1 = s0 + 2 * SLOT;
    phi_q(0, QA);
    wg_wait<0>(); pin<32>(a1);
    bar_sync(2 + wg, 128);
    F.fwd<0>(a1, a2); phi_q(QA, QA + QB);
    F.fwd<1>(a1, a2); phi_q(QA + QB, QA + 2 * QB);
    F.fwd<2>(a1, a2); phi_q(QA + 2 * QB, QA + 3 * QB);
    F.fwd<3>(a1, a2);
    phi_q(QA + 3 * QB, QA + 3 * QB + QC);
    wg_wait<0>(); pin<32>(a2);
#pragma unroll 1
    for (uint32_t sa = s0;; sa += 2 * SLOT + P.zero) {
    conv_pair(sa, sa == s1 ? ya1 : ya0, sa != s1);
    if (sa == s1) break;
    F.last(by, s0 + SLOT, wg);
    F.stage1(a1, s1);
    phi_q(QA + 3 * QB + QC, 32);
    wg_wait<1>();
    pair_done(ya0, 0);
    TSTAMP(tid == 0, 7); TSTAMP(tid == 128, 10);
    {
      float dn[4][20];
      wg_wait<0>(); pin<32>(a1);
      bar_sync(2 + wg, 128);
      F.fwd<0>(a1, a2); F.fwd<1>(a1, a2); F.fwd<2>(a1, a2); F.fwd<3>(a1, a2);
      mbar_wait(bar(B_KV_READY), 0);
      TSTAMP(tid == 0, 8);
      auto head_mma = [&](int h) {
        wg_fence();
        const uint64_t db = make_desc(SM_KV + h * 2560, 640, 128, 0);
        const uint32_t* a = pq + 8 * h;
        mma_o_init(dn[h], a[0], a[1], a[2], a[3], db);
        mma_o_acc(dn[h], a[4], a[5], a[6], a[7], db + (1280 >> 4));
        wg_commit();
      };
      auto head_store = [&](int h) {
        pin<20>(dn[h]);
        const float i0 = rcp(dn[h][16] + 1e-6f), i1 = rcp(dn[h][18] + 1e-6f);
        const uint32_t p0 = pack_bf16(i0, i0), p1 = pack_bf16(i1, i1);
#pragma unroll
        for (int hf = 0; hf < 2; hf++) {
          const float* a = dn[h] + 8 * hf;
          const uint32_t dst = sb + (h >> 1) * SLOT + wg * 8192 + orow + (ox ^ (((h & 1) * 2 + hf) << 5));
          stsm4(dst, bmul2(pack_bf16(a[0], a[1]), p0), bmul2(pack_bf16(a[2], a[3]), p1), bmul2(pack_bf16(a[4], a[5]), p0), bmul2(pack_bf16(a[6], a[7]), p1));
        }
        if (h & 1) { if (!RFENCE) fence_async_smem(); __syncwarp(); mbar_arrive_if(bar(B_O_WRITTEN + (h >> 1)), lane == 0); }
      };
      head_mma(0); head_mma(1);
      wg_wait<1>(); head_store(0);
      head_mma(2);
      wg_wait<1>(); head_store(1);
      head_mma(3);
      wg_wait<1>(); head_store(2);
      wg_wait<0>(); head_store(3);
      TSTAMP(tid == 0, 9);
      pin<32>(a2);
    }
    }
    if (FIN && RFENCE) mbar_wait(bar(B_OT_FREE + 1), 0);
    F.last(by, s1 + SLOT, wg);

    float acc[64];
    auto stage_mma = [&](int s, int kk, int accumulate) {
      mma_nt(acc, make_desc(((A_SLOTS >> (4 * s)) & 15) * SLOT + wg * 8192 + kk * 32, 16, 1024, 1),
             make_desc(((B_SLOTS >> (4 * s)) & 15) * SLOT + kk * 2048, 8192, 1024, 1), accumulate);
    };
    {
      mbar_wait(bar(B_OUT_FULL), 0);
      wg_fence();
#pragma unroll
      for (int kk = 0; kk < 2; kk++) stage_mma(0, kk, kk);
      wg_commit();
      wg_wait<1>();
      arrive_both(bar(B_CONV_DONE), lane);
      cluster_arrive();
      wg_fence();
#pragma unroll
      for (int kk = 2; kk < 4; kk++) stage_mma(0, kk, 1);
      wg_commit();
      pair_done(ya1, 1);
      TSTAMP(tid == 0, 11); TSTAMP(tid == 128, 12);
      int s = 1, sprev = 0;
      uint32_t ph = 0;
#pragma unroll 1
      for (int ks = 1; ks < 12; ++ks) {
        mbar_wait(bar(B_OUT_FULL + s), ph);
        LOOPSTAMP(2, tid == 0, 1 + ks);
        TSTAMP(tid == 0 && ks == 2, 13); TSTAMP(tid == 0 && ks == 9, 14);
        wg_fence();
        stage_mma(s, 0, 1);
        wg_commit();
        wg_wait<1>();
        arrive_both(bar(B_OUT_EMPTY + sprev), lane);
        wg_fence();
#pragma unroll
        for (int kk = 1; kk < 4; kk++) stage_mma(s, kk, 1);
        wg_commit();
        sprev = s;
        if (++s == 5) { s = 0; ph ^= 1; }
      }
#pragma unroll 1
      for (int ks = 12; ks < 16; ++ks) {
        asm volatile("{\n.reg .pred p;\nsetp.ne.b32 p, %0, 0;\n@p bar.sync 1, 256;\n}" :: "r"((int)(ks == 16 - TAIL && wg)) : "memory");
        mbar_wait(bar(B_OUT_FULL + s), ks == 15);
        wg_fence();
#pragma unroll
        for (int kk = 0; kk < 4; kk++) stage_mma(s, kk, 1);
        wg_commit();
        if (++s == 5) s = 0;
      }
    }
    asm volatile("{\n.reg .pred p;\nsetp.eq.b32 p, %0, 0;\n@p bar.arrive 1, 256;\n}" :: "r"(wg) : "memory");
    wg_wait<0>(); pin<64>(acc);
    TSTAMP(tid == 0, 15); TSTAMP(tid == 128, 16);
#pragma unroll
    for (int hf = 0; hf < 2; hf++) {
      const uint32_t dst = sb + (1 + 8 * hf) * SLOT + wg * 8192;
#pragma unroll
      for (int t = 0; t < 4; t++) {
        const float* a = acc + 32 * hf + 8 * t;
        stsm4(dst + orow + (ox ^ (t << 5)), pack_bf16(a[0], a[1]), pack_bf16(a[2], a[3]), pack_bf16(a[4], a[5]), pack_bf16(a[6], a[7]));
      }
      fence_async_smem();
      __syncwarp();
      if (elect()) { tma2d_store(&P.outa, dst + wq * 2048, 128 * j + 64 * hf, 128 * r + 16 * warp); bulk_commit(); }
    }
    const bool stale = __any_sync(0xffffffffu, acc[0] != acc[0] || acc[2] != acc[2] || (DBG & 256));
    if (elect()) bulk_wait_read();
    TSTAMP(tid == 128, 17);
    __syncwarp();
    cluster_wait();
    TSTAMP(tid == 128, 28); GSTAMP(tid == 128, 31);
    if (stale) {
      __threadfence();
#pragma unroll
      for (int i = 0; i < 64; i++) acc[i] = 0.f;
      const int row = warp * 16 + (lane >> 2);
#pragma unroll 1
      for (int k = 0; k < 1024; k += 2) {
        const uint8_t* src = g_xch[r * 8 + (k >> 7)] + ((k >> 6) & 1) * SLOT + row * 128 + ((((k >> 3) ^ row) & 7) << 4) + (k & 7) * 2;
        uint32_t a[2];
        int n = 0;
        do { a[0] = ld_relaxed(src); a[1] = ld_relaxed(src + 1024); } while (!all_arrived<2>(a) && ++n < kSpinLimit);
#pragma unroll 1
        for (int e = 0; e < 2; e++) {
          const float a0 = e ? bf_hi(a[0]) : bf_lo(a[0]), a1 = e ? bf_hi(a[1]) : bf_lo(a[1]);
          const uint32_t* wrow = reinterpret_cast<const uint32_t*>(P.wo_ptr + (k + e) * 1024 + 128 * j) + (lane & 3);
#pragma unroll
          for (int i = 0; i < 16; i++) {
            const uint32_t w = __ldg(wrow + 4 * i);
            acc[4 * i] += a0 * bf_lo(w); acc[4 * i + 1] += a0 * bf_hi(w);
            acc[4 * i + 2] += a1 * bf_lo(w); acc[4 * i + 3] += a1 * bf_hi(w);
          }
        }
      }
      uint32_t* op = reinterpret_cast<uint32_t*>(P.out_ptr + (128 * r + row) * 2048 + 128 * j) + (lane & 3);
#pragma unroll
      for (int i = 0; i < 32; i++) op[(i & 1) * 8192 + (i >> 1) * 4] = pack_bf16(acc[2 * i], acc[2 * i + 1]);
    }
  } else {
    asm volatile("setmaxnreg.dec.sync.aligned.u32 56;");
    if (warp == 8) {
      cluster_wait();
      cluster_arrive();
      LOOPSTAMP(3, tid == 256, 15);
#pragma unroll 1
      for (int it = 1; it < 4; it++) if (elect()) load_stage(it);
      LOOPSTAMP(3, tid == 256, 16);
      __syncwarp();
      cluster_wait();
    } else {
      if (elect()) {
#pragma unroll 1
        for (int g = warp - 9; g < 8; g += 3)
          for (int i = 0; i < 8; i++) mbar_init(bar(8 * g + i), 1u << ((BAR_LOG2 >> (4 * g)) & 7));
        if (warp == 11) for (int i = 0; i < 6; i++) mbar_expect(bar(B_H_FULL + i), i < 2 ? 12288 : i < 5 ? 8192 : 16);
        asm volatile("fence.mbarrier_init.release.cluster;" ::: "memory");
      }
      LOOPSTAMP(3, tid == 288, 14);
      __syncwarp();
      cluster_wait();
      cluster_arrive();
#pragma unroll
      for (int i = 0; i < 3; i++) asm volatile("st.shared.v4.b32 [%0], {%1,%1,%1,%1};" :: "r"(sb + SM_F1 + i * 1536 + (tid - 288) * 16), "r"(0xffffffffu) : "memory");
      fence_async_smem();
      asm volatile("bar.arrive 5, 128;" ::: "memory");
      if ((sb & 0xffffff) != SM_BASE) __trap();
      cluster_wait();
    }
    auto chunk = [&](int ks) { const int c = ks >= 9, t = ks - 2 - 7 * c; return ks < 2 ? 2 * j + ks : 2 * (t + (t >= j)) + c; };
    auto load_q = [&](int n) {
      mbar_expect(bar(B_Q_FULL + (n & 3)), 4096);
      tma2d(sb + SM_Q + (n & 3) * 4096, &P.q, cl * 16, rho * 1024 + n * 128, bar(B_Q_FULL + (n & 3)));
    };
    auto load_wo = [&](uint32_t dst, int c, uint32_t bytes, uint32_t fb) {
      mbar_expect(fb, bytes);
      tma2d_mc(dst + rho * 8192, &P.wo, 128 * j + 64 * rho, c * 64, fb);
    };
    uint8_t* const xch = g_xch[r * 8 + j];
    if (warp == 8) {
      int ck = 0, cw = 0, cph = 1;
      const CUtensorMap* kvmap = rho ? &P.v : &P.k;
#pragma unroll 1
      for (int it = 4 - XPF; it < 32 || (ck < 16 && it < kSpinLimit); ++it) {
        if (it >= 4 && it < 32) {
          mbar_wait(bar(B_QKV_EMPTY + (it & 3)), ((it >> 2) - 1) & 1);
          if (elect()) load_stage(it);
          LOOPSTAMP(3, lane == 0 && it < 12, 15 + it);
        }
        if (it < 32 - XPF) {
          if (((it + XPF) & 7) == rp && elect()) {
            l2_prefetch2d(&P.wk, 1024 + 128 * j + 64 * rho, 32 * (it + XPF));
            l2_prefetch3d(&P.w, 0, 32 * (it + XPF), 32 * rho + 2 * j);
          }
          if (((it + XPF) & 7) == j && elect()) l2_prefetch2d(&P.x, 32 * (it + XPF), 128 * r);
        }
        const int n = it - HSTART;
        if (n >= 0 && n < 8) {
          if (elect()) bulk_load(sb + SM_SIG + n * 8192 + 4096, P.ssm_k + (size_t)(cta * 8 + n) * 2048, 4096, bar(B_H_FULL + (n >= 3) + (n >= 6)));
        } else if (n >= 8 && n < 19) {
          if (n == 8) bar_sync(5, 128);
          if (elect()) bulk_store(xch + (n - 8) * 4096, sb + SM_F1, 4096);
        } else if (it >= PF0 && it < PF0 + 6) {
          if (elect()) l2_prefetch(it < PF0 + 2 ? P.wo_ptr + cta * 8192 + (it - PF0) * 4096 : P.q_ptr + cta * 16384 + (it - PF0 - 2) * 4096, 8192);
        }
        if (ck < 16 && it >= PSTART && __all_sync(0xffffffffu, mbar_test(bar(B_PREP_EMPTY + cw), cph))) {
          if (elect()) {
            mbar_expect(bar(B_PREP_FULL + cw), 8704);
            tma3d_mc(sb + SM_STG + cw * 8704 + rho * 4608, kvmap, cl * 16, ck * 8 - 1 + rho, 0, bar(B_PREP_FULL + cw));
          }
          ++ck;
          if (++cw == 3) { cw = 0; cph ^= 1; }
        }
      }
      if (elect()) {
        bulk_commit();
        bulk_wait_read();
        mbar_wait(bar(B_STG_FREE), 0);
        mbar_expect(bar(B_SIG_READY), 10240);
        bulk_load(sb + SM_TW, g_tables, 10240, bar(B_SIG_READY));
        flag_add(&g_ready);
        prefetch_map(&P.wo); prefetch_map(&P.outa); prefetch_map(&P.q);
        flag_wait(&g_ready, kCtas * (load_epoch(cta) + 1));
        mbar_arrive(bar(B_ZEROED));
        TSTAMP(true, 27);
      }
      __syncwarp();
      mbar_wait(bar(B_QKV_DONE), 0);
#pragma unroll 1
      for (int ks = 0; ks < NB0; ++ks) if (elect()) load_wo(sb + (4 + ks) * SLOT, chunk(ks), ks < 2 ? SLOT : 2 * SLOT, bar(B_OUT_FULL + ks));
    } else {
      const int at = tid - 288, aw = warp - 9, ch0 = cta * 8;
      {
        const uint32_t stg = sb + SM_STG + aw * 8704, pf = bar(B_PREP_FULL + aw), pe = bar(B_PREP_EMPTY + aw);
        const uint4 wv = __ldg(reinterpret_cast<const uint4*>(P.shift_k + (ch0 + 2 * (lane & 3)) * 4));
        const float skip = __bfloat162float(P.ssm_d[ch0 + (lane & 7)]);
        const uint32_t w0 = __byte_perm(wv.x, wv.z, 0x5410), w1 = __byte_perm(wv.x, wv.z, 0x7632);
        const uint32_t w2 = __byte_perm(wv.y, wv.w, 0x5410), w3 = __byte_perm(wv.y, wv.w, 0x7632);
        auto swz32 = [](uint32_t a) { return a ^ ((a >> 3) & 16); };
        const uint32_t kl = (lane >> 3) * 288 + (lane & 7) * 32 + rho * 16;
        const uint32_t ka = stg + swz32(kl + 32), kh = stg + swz32(kl + 12 * 288), va = stg + 4608 + swz32(lane * 32 + rho * 16);
        const uint32_t ua = sb + SM_SIG + (lane & 7) * 8192 + (((lane >> 3) ^ (lane & 7)) << 4);
        uint32_t eh = 0;
#pragma unroll 1
        for (int ck = aw, rd = 0; rd < 9; ck += 3, ++rd) {
          if (rd == 6) {
            bar_sync(4, 96);
            if (at == 64) mbar_arrive(bar(B_STG_FREE));
          }
          const int c = rd < 6 ? ck : ck - 18;
          if (c < 8) {
            uint32_t x[32], dst = sb + SM_SIG + c * 8192;
            if (rd < 6) {
              mbar_wait(bar(B_H_FULL + rd), 0);
#pragma unroll
              for (int i = 0; i < 8; i++) ldsm4(x + 4 * i, dst + 4096 + i * 512 + lane * 16);
              const float d = __shfl_sync(0xffffffffu, skip, c);
              if (lane == 0) x[0] = pack_bf16(bf_lo(x[0]) + d, bf_hi(x[0]));
              dst += 4096 + (lane >> 1) * 128 + ((((lane & 1) * 4) ^ ((lane >> 1) & 7)) << 4);
            } else {
#pragma unroll
              for (int i = 0; i < 8; i++) ldsm4_t(x + 4 * i, dst + i * 512 + ((lane ^ c) << 4));
              dst += (lane >> 4) * 1024 + (lane & 7) * 128 + ((((lane >> 1) & 4) ^ (lane & 7)) << 4);
            }
            const uint32_t e = normalize(x, dst);
            if (rd < 6) {
              eh |= e << (8 * rd);
            } else {
              const int f = min(max((int)(e + (eh & 255)) - 125, 0), 254);
              eh >>= 8;
              if (lane == 0) asm volatile("st.shared.b16 [%0], %1;" :: "r"(sb + SM_SC + rho * 16 + 2 * c), "h"((uint16_t)(f << 7)) : "memory");
            }
          }
          if (ck < 16) {
            mbar_wait(pf, rd & 1);
            uint32_t k[20], v[16];
            ldsm4(k, kh);
#pragma unroll
            for (int m = 0; m < 4; m++) { ldsm4(k + 4 + 4 * m, (ka ^ ((m & 1) << 4)) + m * 1152); ldsm4(v + 4 * m, va + m * 1024); }
            arrive_both(pe + ((k[3] | k[4] | k[8] | k[12] | k[16] | v[0] | v[4] | v[8] | v[12]) & P.zero), lane, ck < 13);
#pragma unroll
            for (int m = 0; m < 4; m++) {
              uint32_t u[4];
#pragma unroll
              for (int n = 0; n < 4; n++) {
                const uint32_t* kk = k + 4 + 4 * m + n;
                u[n] = bmul2(bfma2(kk[0], w0, bfma2(kk[-1], w1, bfma2(kk[-2], w2, bmul2(kk[-3], w3)))), v[4 * m + n]);
              }
              stsm4_t((ua ^ (m << 6)) + ck * 256, u[0], u[1], u[2], u[3]);
            }
          }
        }
        fence_async_smem();
        __syncwarp();
        if (lane == 0) mbar_arrive(bar(B_SIG_READY));
        bar_sync(4, 96);
        if (at == 32) {
          const uint4 s = lds128(sb + SM_SC + rho * 16);
          asm volatile("st.async.weak.shared::cluster.mbarrier::complete_tx::bytes.v4.b32 [%0], {%1,%2,%3,%4}, [%5];"
                       :: "r"(peer_addr(sb + SM_SC + rho * 16, rho ^ 1)), "r"(s.x), "r"(s.y), "r"(s.z), "r"(s.w), "r"(peer_addr(bar(B_RDY0), rho ^ 1)) : "memory");
        }
        TSTAMP(at == 0, 20); LOOPSTAMP(4, at == 0, 22);
      }
    }
    __syncwarp();
    const unsigned epoch = load_epoch(cta);
    mbar_wait(bar(B_KVP), 0);
    {
      const int a4 = warp - 8;
      uint32_t v[20];
      int n = 0;
      do {
#pragma unroll
        for (int i = 0; i < 4; i++) ld_relaxed4(v + 4 * i, xch + 2 * SLOT + ((lane >> 3) * 4 + i) * KV_SLICE + (a4 * 8 + (lane & 7)) * 16);
        v[16] = ld_relaxed(xch + 2 * SLOT + (lane & 15) * KV_SLICE + 512 + (a4 * 2 + (lane >> 4)) * 4);
      } while (!all_arrived<17>(v) && ++n < kSpinLimit);
      TSTAMP(tid == 288, 21);
      float lo[4], hi[4], z = __uint_as_float(v[16]);
#pragma unroll
      for (int b = 0; b < 4; b++) {
        lo[b] = (bf_lo(v[b]) + bf_lo(v[4 + b])) + (bf_lo(v[8 + b]) + bf_lo(v[12 + b]));
        hi[b] = (bf_hi(v[b]) + bf_hi(v[4 + b])) + (bf_hi(v[8 + b]) + bf_hi(v[12 + b]));
      }
      const bool u16 = lane & 16, u8 = lane & 8;
#pragma unroll
      for (int b = 0; b < 2; b++) {
        lo[b] = (u16 ? lo[b + 2] : lo[b]) + __shfl_xor_sync(0xffffffffu, u16 ? lo[b] : lo[b + 2], 16);
        hi[b] = (u16 ? hi[b + 2] : hi[b]) + __shfl_xor_sync(0xffffffffu, u16 ? hi[b] : hi[b + 2], 16);
      }
      const float l = (u8 ? lo[1] : lo[0]) + __shfl_xor_sync(0xffffffffu, u8 ? lo[0] : lo[1], 8);
      const float h = (u8 ? hi[1] : hi[0]) + __shfl_xor_sync(0xffffffffu, u8 ? hi[0] : hi[1], 8);
      uint8_t* red = xch + 2 * SLOT + 16 * KV_SLICE;
      st_relaxed(red + (a4 * 8 + (lane & 7)) * 16 + (lane >> 3) * 4, pack_bf16(l, h));
#pragma unroll
      for (int o = 8; o; o >>= 1) z += __shfl_xor_sync(0xffffffffu, z, o);
      if ((lane & 15) == 0) st_relaxed(red + 512 + (a4 * 2 + (lane >> 4)) * 4, pack_bf16(z, z));
      TSTAMP(tid == 288, 22);
      n = 0;
      do {
#pragma unroll
        for (int i = 0; i < 4; i++) {
          const uint8_t* src = g_xch[(a4 * 4 + i) * 8 + j] + 2 * SLOT + 16 * KV_SLICE;
          ld_relaxed4(v + 4 * i, src + lane * 16);
          v[16 + i] = ld_relaxed(src + 512 + (lane & 28));
        }
      } while (!all_arrived<20>(v) && ++n < kSpinLimit);
#pragma unroll
      for (int i = 0; i < 4; i++) {
        const uint32_t dst = sb + SM_KV + (a4 * 4 + i) * 640;
        stsm4(dst + lane * 16, v[4 * i], v[4 * i + 1], v[4 * i + 2], v[4 * i + 3]);
        asm volatile("st.shared.b32 [%0], %1;" :: "r"(dst + 512 + lane * 4), "r"(v[16 + i]) : "memory");
      }
      fence_async_smem();
      __syncwarp();
      if (lane == 0) mbar_arrive(bar(B_KV_READY));
      TSTAMP(tid == 288, 23);
    }
    if (warp != 10) cluster_arrive();
    if (warp == 8) {
#pragma unroll 1
      for (int ks = NB0; ks < 4; ++ks) if (elect()) load_wo(sb + (4 + ks) * SLOT, chunk(ks), ks < 2 ? SLOT : 2 * SLOT, bar(B_OUT_FULL + ks));
#pragma unroll 1
      for (int n = 0; n < 4; ++n) if (elect()) load_q(n);
      int s = 4;
      uint32_t ph = 1;
#pragma unroll 1
      for (int ks = 4; ks < 16; ++ks) {
        uint32_t fb = bar(B_OUT_FULL + s), dst = sb + ((B_SLOTS >> (4 * s)) & 15) * SLOT;
        int c = chunk(ks);
        keep(fb); keep(dst); keep(c);
        mbar_wait(bar(ks == 4 ? B_CONV_DONE : B_OUT_EMPTY + s), ks == 4 ? 0 : ph);
        if (elect()) load_wo(dst, c, 2 * SLOT, fb);
        if (++s == 5) { s = 0; ph ^= 1; }
      }
    } else {
      auto wait_chunks = [&](unsigned mask) {
        unsigned ready;
        int n = 0;
        do {
          const unsigned f = ld_relaxed(&g_oflag[(r * 8 + ((lane >> 1) & 7)) * 32]);
          ready = __ballot_sync(0xffffffffu, (int)(f - (2 * epoch + 1 + (lane & 1))) >= 0);
        } while ((~ready & mask) && ++n < kSpinLimit);
        return ready;
      };
      if (warp == 9) {
        if (elect()) {
#pragma unroll 1
          for (int c = 0; c < 2; c++) {
            mbar_wait(bar(B_O_WRITTEN + c), 0);
            TSTAMP(c == 0, 19);
            if (RFENCE) fence_async_smem();
            bulk_store(xch + c * SLOT, sb + c * SLOT, SLOT);
            bulk_commit();
            bulk_wait_read();
            mbar_arrive(bar(B_OT_FREE + c));
            delay(FDELAY);
            st_relaxed(&g_oflag[(r * 8 + j) * 32], 2 * epoch + 1 + c);
            TSTAMP(c == 0, 29); TSTAMP(c == 1, 25);
          }
          g_epoch[cta] = epoch + 1;
        }
        __syncwarp();
        wait_chunks(0xaaaa);
        if (lane == 0) mbar_arrive(bar(B_FLAGS1));
      } else if (warp == 10) {
        mbar_wait(bar(B_RDY0), 0);
#pragma unroll 1
        for (int n = 0; n < 4; n++) {
          const int w = n & 1;
          mbar_wait(bar(B_SEG + n), 0);
          if (RFENCE) fence_async_smem();
          if (elect()) bulk_to_peer(sb + (n < 2 ? SM_Y0 : SM_SIG) + w * 8192 + 4096, sb + SM_YT + w * 4096, 4096, bar(B_YIN + (n >> 1)), rho ^ 1);
          if (w) {
            mbar_wait(bar(B_YIN + (n >> 1)), 0);
            if (lane == 0) asm volatile("mbarrier.arrive.shared::cluster.b64 _, [%0];" :: "r"(n < 2 ? peer_addr(bar(B_RDY1), rho ^ 1) : bar(B_Y_READY)) : "memory");
          }
        }
        __syncwarp();
        cluster_arrive();
        TSTAMP(lane == 0, 26);
      } else {
        mbar_wait(bar(B_O_WRITTEN + 1), 0);
        unsigned ready = 0;
        int s = 2;
        uint32_t ph = 1;
#pragma unroll 1
        for (int ks = 2; ks < 16; ++ks) {
          const int c = chunk(ks);
          uint32_t fb = bar(B_OUT_FULL + s), dst = sb + ((A_SLOTS >> (4 * s)) & 15) * SLOT;
          uint8_t* src = g_xch[r * 8 + (c >> 1)] + (c & 1) * SLOT;
          keep(fb); keep(dst); keep(src);
          if (ks < 5 || ks == 9) {
            const unsigned need = ks < 4 ? 1u << c : 0x5555u;
            if (ks == 9) mbar_wait(bar(B_FLAGS1), 0);
            else if (~ready & need) ready = wait_chunks(need);
          }
          if (ks == 5 || ks == 6) mbar_wait(bar(B_OT_FREE + s), 0);
          if (ks >= 4) mbar_wait(bar(ks == 4 ? B_CONV_DONE : B_OUT_EMPTY + s), ks == 4 ? 0 : ph);
          if (elect()) bulk_load(dst, src, SLOT, fb);
          TSTAMP(ks == 2 && lane == 0, 18); LOOPSTAMP(2, lane == 0, 11 + ks);
          if (++s == 5) { s = 0; ph ^= 1; }
        }
      }
      if (warp < 11) {
        const int yc = (lane & 1) + ((lane >> 2) & 2) + (lane & 2) * 2, ysrc = (lane >> 2) & 1;
        const uint32_t ya = sb + (yc & 4 ? SM_SIG : SM_Y0) + (yc & 1) * 8192 + (yc & 2) * 1024 + (ysrc ^ rho) * 4096 +
                            (lane >> 4) * 128 + ((yc ^ (2 * ysrc)) << 4);
        uint32_t s0, s1;
        mbar_wait(bar(B_Y_READY), 0);
        asm volatile("ld.shared.v2.b32 {%0,%1}, [%2];" : "=r"(s0), "=r"(s1) : "r"(sb + SM_SC + (lane & 3) * 8) : "memory");
#pragma unroll 1
        for (int n = warp - 9; n < 8; n += 2) {
          __nv_bfloat16* op = P.out_ptr + (rho * 1024 + n * 128 + (lane >> 2)) * 2048 + 1024 + cl * 16 + (lane & 3) * 4;
          const uint32_t qa = sb + SM_Q + (n & 3) * 4096 + lane * 8;
          mbar_wait(bar(B_Q_FULL + (n & 3)), n >> 2);
#pragma unroll 1
          for (int u0 = 0; u0 < 8; u0 += 2) {
            const uint32_t t0 = clock32();
            uint32_t y[2][4], q[2][4];
#pragma unroll
            for (int u = 0; u < 2; u++) {
              ldsm4_t(y[u], (ya ^ ((u0 + u) << 4)) + n * 256);
#pragma unroll
              for (int m = 0; m < 2; m++)
                asm volatile("ld.shared.v2.b32 {%0,%1}, [%2];" : "=r"(q[u][2 * m]), "=r"(q[u][2 * m + 1]) : "r"(qa + (u0 + u) * 512 + m * 256) : "memory");
            }
#pragma unroll
            for (int u = 0; u < 2; u++)
#pragma unroll
              for (int m = 0; m < 2; m++)
                asm volatile("st.global.v2.b32 [%0], {%1,%2};" :: "l"(op + (u0 * 16 + u * 16 + m * 8) * 2048),
                             "r"(bmul2(q[u][2 * m], bmul2(y[u][2 * m], s0))), "r"(bmul2(q[u][2 * m + 1], bmul2(y[u][2 * m + 1], s1))) : "memory");
            while (clock32() - t0 < PPACE) { }
          }
          __syncwarp();
          if (n < 4 && elect()) load_q(n + 4);
        }
        TSTAMP(tid == 320, 24);
      }
    }
    __syncwarp();
    cluster_wait();
  }
}

typedef CUresult (*EncodeFn)(CUtensorMap*, CUtensorMapDataType, cuuint32_t, void*, const cuuint64_t*, const cuuint64_t*,
                             const cuuint32_t*, const cuuint32_t*, CUtensorMapInterleave, CUtensorMapSwizzle,
                             CUtensorMapL2promotion, CUtensorMapFloatOOBfill);

void encode(EncodeFn fn, CUtensorMap* m, const void* p, int rank, const cuuint64_t* dims, const cuuint64_t* strides,
            const cuuint32_t* box, CUtensorMapSwizzle sw) {
  const cuuint32_t es[3] = {1, 1, 1};
  fn(m, CU_TENSOR_MAP_DATA_TYPE_BFLOAT16, rank, const_cast<void*>(p), dims, strides, box, es, CU_TENSOR_MAP_INTERLEAVE_NONE, sw,
     CU_TENSOR_MAP_L2_PROMOTION_NONE, CU_TENSOR_MAP_FLOAT_OOB_FILL_NONE);
}
void encode2d(EncodeFn fn, CUtensorMap* m, const void* p, uint64_t cols, uint64_t rows, uint32_t bc, uint32_t br, CUtensorMapSwizzle sw) {
  const cuuint64_t dims[2] = {cols, rows}, strides[1] = {cols * 2};
  const cuuint32_t box[2] = {bc, br};
  encode(fn, m, p, 2, dims, strides, box, sw);
}
void encode3d(EncodeFn fn, CUtensorMap* m, const void* p, uint32_t nblk) {
  const cuuint64_t dims[3] = {1024, 128, 16}, strides[2] = {2048 * 16, 2048};
  const cuuint32_t box[3] = {16, nblk, 16};
  encode(fn, m, p, 3, dims, strides, box, CU_TENSOR_MAP_SWIZZLE_32B);
}

}

extern "C" void kernel_launch(void* const* d_in, const int* in_sizes, int n_in, void* d_out, int out_size) {
  static EncodeFn fn = nullptr;
  if (!fn) {
    cudaDriverEntryPointQueryResult qr;
    cudaGetDriverEntryPoint("cuTensorMapEncodeTiled", (void**)&fn, cudaEnableDefault, &qr);
    cudaFuncSetAttribute(fused_kernel, cudaFuncAttributeMaxDynamicSharedMemorySize, SM_TOTAL);
  }
  Params P;
  encode2d(fn, &P.x, d_in[0], 1024, 2048, 32, 128, CU_TENSOR_MAP_SWIZZLE_64B);
  {
    const cuuint64_t dims[3] = {64, 1024, 48}, strides[2] = {6144, 128};
    const cuuint32_t box[3] = {64, 32, 2};
    encode(fn, &P.w, d_in[1], 3, dims, strides, box, CU_TENSOR_MAP_SWIZZLE_128B);
  }
  encode2d(fn, &P.wk, d_in[1], 3072, 1024, 64, 32, CU_TENSOR_MAP_SWIZZLE_128B);
  encode2d(fn, &P.wo, d_in[2], 1024, 1024, 64, 64, CU_TENSOR_MAP_SWIZZLE_128B);
  encode2d(fn, &P.outa, d_out, 2048, 2048, 64, 16, CU_TENSOR_MAP_SWIZZLE_128B);
  encode3d(fn, &P.k, d_in[4], 9);
  encode3d(fn, &P.v, d_in[5], 8);
  encode2d(fn, &P.q, d_in[3], 1024, 2048, 16, 128, CU_TENSOR_MAP_SWIZZLE_NONE);
  P.shift_k = (const __nv_bfloat16*)d_in[6];
  P.ssm_k = (const __nv_bfloat16*)d_in[7];
  P.ssm_d = (const __nv_bfloat16*)d_in[8];
  P.zero = 0;
  P.q_ptr = (const __nv_bfloat16*)d_in[3];
  P.out_ptr = (__nv_bfloat16*)d_out;
  P.wo_ptr = (const __nv_bfloat16*)d_in[2];
  fused_kernel<<<kCtas, kThreads, SM_TOTAL>>>(P);
}
```

```cpp
#include <cuda.h>
#include <cuda_runtime.h>
#include <cuda_bf16.h>
#include <stdint.h>

#define DEVI __device__ __forceinline__

namespace {

DEVI void mma_nt(float* d, uint64_t da, uint64_t db, int sd) {
  asm volatile("{\n.reg .pred p;\nsetp.ne.b32 p, %66, 0;\nwgmma.mma_async.sync.aligned.m64n128k16.f32.bf16.bf16 {%0, %1, %2, %3, %4, %5, %6, %7, %8, %9, %10, %11, %12, %13, %14, %15, %16, %17, %18, %19, %20, %21, %22, %23, %24, %25, %26, %27, %28, %29, %30, %31, %32, %33, %34, %35, %36, %37, %38, %39, %40, %41, %42, %43, %44, %45, %46, %47, %48, %49, %50, %51, %52, %53, %54, %55, %56, %57, %58, %59, %60, %61, %62, %63}, %64, %65, p, 1, 1, 0, 1;\n}\n"
    : "+f"(d[0]), "+f"(d[1]), "+f"(d[2]), "+f"(d[3]), "+f"(d[4]), "+f"(d[5]), "+f"(d[6]), "+f"(d[7]), "+f"(d[8]), "+f"(d[9]), "+f"(d[10]), "+f"(d[11]), "+f"(d[12]), "+f"(d[13]), "+f"(d[14]), "+f"(d[15]), "+f"(d[16]), "+f"(d[17]), "+f"(d[18]), "+f"(d[19]), "+f"(d[20]), "+f"(d[21]), "+f"(d[22]), "+f"(d[23]), "+f"(d[24]), "+f"(d[25]), "+f"(d[26]), "+f"(d[27]), "+f"(d[28]), "+f"(d[29]), "+f"(d[30]), "+f"(d[31]), "+f"(d[32]), "+f"(d[33]), "+f"(d[34]), "+f"(d[35]), "+f"(d[36]), "+f"(d[37]), "+f"(d[38]), "+f"(d[39]), "+f"(d[40]), "+f"(d[41]), "+f"(d[42]), "+f"(d[43]), "+f"(d[44]), "+f"(d[45]), "+f"(d[46]), "+f"(d[47]), "+f"(d[48]), "+f"(d[49]), "+f"(d[50]), "+f"(d[51]), "+f"(d[52]), "+f"(d[53]), "+f"(d[54]), "+f"(d[55]), "+f"(d[56]), "+f"(d[57]), "+f"(d[58]), "+f"(d[59]), "+f"(d[60]), "+f"(d[61]), "+f"(d[62]), "+f"(d[63])
    : "l"(da), "l"(db), "r"(sd));
}
DEVI void mma_tn(float* d, uint64_t da, uint64_t db, int sd) {
  asm volatile("{\n.reg .pred p;\nsetp.ne.b32 p, %66, 0;\nwgmma.mma_async.sync.aligned.m64n128k16.f32.bf16.bf16 {%0, %1, %2, %3, %4, %5, %6, %7, %8, %9, %10, %11, %12, %13, %14, %15, %16, %17, %18, %19, %20, %21, %22, %23, %24, %25, %26, %27, %28, %29, %30, %31, %32, %33, %34, %35, %36, %37, %38, %39, %40, %41, %42, %43, %44, %45, %46, %47, %48, %49, %50, %51, %52, %53, %54, %55, %56, %57, %58, %59, %60, %61, %62, %63}, %64, %65, p, 1, 1, 1, 0;\n}\n"
    : "+f"(d[0]), "+f"(d[1]), "+f"(d[2]), "+f"(d[3]), "+f"(d[4]), "+f"(d[5]), "+f"(d[6]), "+f"(d[7]), "+f"(d[8]), "+f"(d[9]), "+f"(d[10]), "+f"(d[11]), "+f"(d[12]), "+f"(d[13]), "+f"(d[14]), "+f"(d[15]), "+f"(d[16]), "+f"(d[17]), "+f"(d[18]), "+f"(d[19]), "+f"(d[20]), "+f"(d[21]), "+f"(d[22]), "+f"(d[23]), "+f"(d[24]), "+f"(d[25]), "+f"(d[26]), "+f"(d[27]), "+f"(d[28]), "+f"(d[29]), "+f"(d[30]), "+f"(d[31]), "+f"(d[32]), "+f"(d[33]), "+f"(d[34]), "+f"(d[35]), "+f"(d[36]), "+f"(d[37]), "+f"(d[38]), "+f"(d[39]), "+f"(d[40]), "+f"(d[41]), "+f"(d[42]), "+f"(d[43]), "+f"(d[44]), "+f"(d[45]), "+f"(d[46]), "+f"(d[47]), "+f"(d[48]), "+f"(d[49]), "+f"(d[50]), "+f"(d[51]), "+f"(d[52]), "+f"(d[53]), "+f"(d[54]), "+f"(d[55]), "+f"(d[56]), "+f"(d[57]), "+f"(d[58]), "+f"(d[59]), "+f"(d[60]), "+f"(d[61]), "+f"(d[62]), "+f"(d[63])
    : "l"(da), "l"(db), "r"(sd));
}
DEVI void mma_nt256(float* d, uint64_t da, uint64_t db, int sd) {
  asm volatile("{\n.reg .pred p;\nsetp.ne.b32 p, %130, 0;\nwgmma.mma_async.sync.aligned.m64n256k16.f32.bf16.bf16 {%0, %1, %2, %3, %4, %5, %6, %7, %8, %9, %10, %11, %12, %13, %14, %15, %16, %17, %18, %19, %20, %21, %22, %23, %24, %25, %26, %27, %28, %29, %30, %31, %32, %33, %34, %35, %36, %37, %38, %39, %40, %41, %42, %43, %44, %45, %46, %47, %48, %49, %50, %51, %52, %53, %54, %55, %56, %57, %58, %59, %60, %61, %62, %63, %64, %65, %66, %67, %68, %69, %70, %71, %72, %73, %74, %75, %76, %77, %78, %79, %80, %81, %82, %83, %84, %85, %86, %87, %88, %89, %90, %91, %92, %93, %94, %95, %96, %97, %98, %99, %100, %101, %102, %103, %104, %105, %106, %107, %108, %109, %110, %111, %112, %113, %114, %115, %116, %117, %118, %119, %120, %121, %122, %123, %124, %125, %126, %127}, %128, %129, p, 1, 1, 0, 1;\n}\n"
    : "+f"(d[0]), "+f"(d[1]), "+f"(d[2]), "+f"(d[3]), "+f"(d[4]), "+f"(d[5]), "+f"(d[6]), "+f"(d[7]), "+f"(d[8]), "+f"(d[9]), "+f"(d[10]), "+f"(d[11]), "+f"(d[12]), "+f"(d[13]), "+f"(d[14]), "+f"(d[15]), "+f"(d[16]), "+f"(d[17]), "+f"(d[18]), "+f"(d[19]), "+f"(d[20]), "+f"(d[21]), "+f"(d[22]), "+f"(d[23]), "+f"(d[24]), "+f"(d[25]), "+f"(d[26]), "+f"(d[27]), "+f"(d[28]), "+f"(d[29]), "+f"(d[30]), "+f"(d[31]), "+f"(d[32]), "+f"(d[33]), "+f"(d[34]), "+f"(d[35]), "+f"(d[36]), "+f"(d[37]), "+f"(d[38]), "+f"(d[39]), "+f"(d[40]), "+f"(d[41]), "+f"(d[42]), "+f"(d[43]), "+f"(d[44]), "+f"(d[45]), "+f"(d[46]), "+f"(d[47]), "+f"(d[48]), "+f"(d[49]), "+f"(d[50]), "+f"(d[51]), "+f"(d[52]), "+f"(d[53]), "+f"(d[54]), "+f"(d[55]), "+f"(d[56]), "+f"(d[57]), "+f"(d[58]), "+f"(d[59]), "+f"(d[60]), "+f"(d[61]), "+f"(d[62]), "+f"(d[63]), "+f"(d[64]), "+f"(d[65]), "+f"(d[66]), "+f"(d[67]), "+f"(d[68]), "+f"(d[69]), "+f"(d[70]), "+f"(d[71]), "+f"(d[72]), "+f"(d[73]), "+f"(d[74]), "+f"(d[75]), "+f"(d[76]), "+f"(d[77]), "+f"(d[78]), "+f"(d[79]), "+f"(d[80]), "+f"(d[81]), "+f"(d[82]), "+f"(d[83]), "+f"(d[84]), "+f"(d[85]), "+f"(d[86]), "+f"(d[87]), "+f"(d[88]), "+f"(d[89]), "+f"(d[90]), "+f"(d[91]), "+f"(d[92]), "+f"(d[93]), "+f"(d[94]), "+f"(d[95]), "+f"(d[96]), "+f"(d[97]), "+f"(d[98]), "+f"(d[99]), "+f"(d[100]), "+f"(d[101]), "+f"(d[102]), "+f"(d[103]), "+f"(d[104]), "+f"(d[105]), "+f"(d[106]), "+f"(d[107]), "+f"(d[108]), "+f"(d[109]), "+f"(d[110]), "+f"(d[111]), "+f"(d[112]), "+f"(d[113]), "+f"(d[114]), "+f"(d[115]), "+f"(d[116]), "+f"(d[117]), "+f"(d[118]), "+f"(d[119]), "+f"(d[120]), "+f"(d[121]), "+f"(d[122]), "+f"(d[123]), "+f"(d[124]), "+f"(d[125]), "+f"(d[126]), "+f"(d[127])
    : "l"(da), "l"(db), "r"(sd));
}
DEVI void mma_kv_init(float* d, uint32_t a0, uint32_t a1, uint32_t a2, uint32_t a3, uint64_t db) {
  asm volatile("wgmma.mma_async.sync.aligned.m64n72k16.f32.bf16.bf16 {%0, %1, %2, %3, %4, %5, %6, %7, %8, %9, %10, %11, %12, %13, %14, %15, %16, %17, %18, %19, %20, %21, %22, %23, %24, %25, %26, %27, %28, %29, %30, %31, %32, %33, %34, %35}, {%36,%37,%38,%39}, %40, 0, 1, 1, 1;\n"
    : "=f"(d[0]), "=f"(d[1]), "=f"(d[2]), "=f"(d[3]), "=f"(d[4]), "=f"(d[5]), "=f"(d[6]), "=f"(d[7]), "=f"(d[8]), "=f"(d[9]), "=f"(d[10]), "=f"(d[11]), "=f"(d[12]), "=f"(d[13]), "=f"(d[14]), "=f"(d[15]), "=f"(d[16]), "=f"(d[17]), "=f"(d[18]), "=f"(d[19]), "=f"(d[20]), "=f"(d[21]), "=f"(d[22]), "=f"(d[23]), "=f"(d[24]), "=f"(d[25]), "=f"(d[26]), "=f"(d[27]), "=f"(d[28]), "=f"(d[29]), "=f"(d[30]), "=f"(d[31]), "=f"(d[32]), "=f"(d[33]), "=f"(d[34]), "=f"(d[35])
    : "r"(a0), "r"(a1), "r"(a2), "r"(a3), "l"(db));
}
DEVI void mma_kv_acc(float* d, uint32_t a0, uint32_t a1, uint32_t a2, uint32_t a3, uint64_t db) {
  asm volatile("wgmma.mma_async.sync.aligned.m64n72k16.f32.bf16.bf16 {%0, %1, %2, %3, %4, %5, %6, %7, %8, %9, %10, %11, %12, %13, %14, %15, %16, %17, %18, %19, %20, %21, %22, %23, %24, %25, %26, %27, %28, %29, %30, %31, %32, %33, %34, %35}, {%36,%37,%38,%39}, %40, 1, 1, 1, 1;\n"
    : "+f"(d[0]), "+f"(d[1]), "+f"(d[2]), "+f"(d[3]), "+f"(d[4]), "+f"(d[5]), "+f"(d[6]), "+f"(d[7]), "+f"(d[8]), "+f"(d[9]), "+f"(d[10]), "+f"(d[11]), "+f"(d[12]), "+f"(d[13]), "+f"(d[14]), "+f"(d[15]), "+f"(d[16]), "+f"(d[17]), "+f"(d[18]), "+f"(d[19]), "+f"(d[20]), "+f"(d[21]), "+f"(d[22]), "+f"(d[23]), "+f"(d[24]), "+f"(d[25]), "+f"(d[26]), "+f"(d[27]), "+f"(d[28]), "+f"(d[29]), "+f"(d[30]), "+f"(d[31]), "+f"(d[32]), "+f"(d[33]), "+f"(d[34]), "+f"(d[35])
    : "r"(a0), "r"(a1), "r"(a2), "r"(a3), "l"(db));
}
DEVI void mma_o_init(float* d, uint32_t a0, uint32_t a1, uint32_t a2, uint32_t a3, uint64_t db) {
  asm volatile("wgmma.mma_async.sync.aligned.m64n40k16.f32.bf16.bf16 {%0, %1, %2, %3, %4, %5, %6, %7, %8, %9, %10, %11, %12, %13, %14, %15, %16, %17, %18, %19}, {%20,%21,%22,%23}, %24, 0, 1, 1, 1;\n"
    : "=f"(d[0]), "=f"(d[1]), "=f"(d[2]), "=f"(d[3]), "=f"(d[4]), "=f"(d[5]), "=f"(d[6]), "=f"(d[7]), "=f"(d[8]), "=f"(d[9]), "=f"(d[10]), "=f"(d[11]), "=f"(d[12]), "=f"(d[13]), "=f"(d[14]), "=f"(d[15]), "=f"(d[16]), "=f"(d[17]), "=f"(d[18]), "=f"(d[19])
    : "r"(a0), "r"(a1), "r"(a2), "r"(a3), "l"(db));
}
DEVI void mma_o_acc(float* d, uint32_t a0, uint32_t a1, uint32_t a2, uint32_t a3, uint64_t db) {
  asm volatile("wgmma.mma_async.sync.aligned.m64n40k16.f32.bf16.bf16 {%0, %1, %2, %3, %4, %5, %6, %7, %8, %9, %10, %11, %12, %13, %14, %15, %16, %17, %18, %19}, {%20,%21,%22,%23}, %24, 1, 1, 1, 1;\n"
    : "+f"(d[0]), "+f"(d[1]), "+f"(d[2]), "+f"(d[3]), "+f"(d[4]), "+f"(d[5]), "+f"(d[6]), "+f"(d[7]), "+f"(d[8]), "+f"(d[9]), "+f"(d[10]), "+f"(d[11]), "+f"(d[12]), "+f"(d[13]), "+f"(d[14]), "+f"(d[15]), "+f"(d[16]), "+f"(d[17]), "+f"(d[18]), "+f"(d[19])
    : "r"(a0), "r"(a1), "r"(a2), "r"(a3), "l"(db));
}
DEVI void fft1_init(uint32_t* d, uint32_t a0, uint32_t a1, uint32_t a2, uint32_t a3, uint64_t db) {
  asm volatile("wgmma.mma_async.sync.aligned.m64n128k16.f16.f16.f16 {%0, %1, %2, %3, %4, %5, %6, %7, %8, %9, %10, %11, %12, %13, %14, %15, %16, %17, %18, %19, %20, %21, %22, %23, %24, %25, %26, %27, %28, %29, %30, %31}, {%32,%33,%34,%35}, %36, 0, 1, 1, 1;\n"
    : "=r"(d[0]), "=r"(d[1]), "=r"(d[2]), "=r"(d[3]), "=r"(d[4]), "=r"(d[5]), "=r"(d[6]), "=r"(d[7]), "=r"(d[8]), "=r"(d[9]), "=r"(d[10]), "=r"(d[11]), "=r"(d[12]), "=r"(d[13]), "=r"(d[14]), "=r"(d[15]), "=r"(d[16]), "=r"(d[17]), "=r"(d[18]), "=r"(d[19]), "=r"(d[20]), "=r"(d[21]), "=r"(d[22]), "=r"(d[23]), "=r"(d[24]), "=r"(d[25]), "=r"(d[26]), "=r"(d[27]), "=r"(d[28]), "=r"(d[29]), "=r"(d[30]), "=r"(d[31])
    : "r"(a0), "r"(a1), "r"(a2), "r"(a3), "l"(db));
}
DEVI void fft1_acc(uint32_t* d, uint32_t a0, uint32_t a1, uint32_t a2, uint32_t a3, uint64_t db) {
  asm volatile("wgmma.mma_async.sync.aligned.m64n128k16.f16.f16.f16 {%0, %1, %2, %3, %4, %5, %6, %7, %8, %9, %10, %11, %12, %13, %14, %15, %16, %17, %18, %19, %20, %21, %22, %23, %24, %25, %26, %27, %28, %29, %30, %31}, {%32,%33,%34,%35}, %36, 1, 1, 1, 1;\n"
    : "+r"(d[0]), "+r"(d[1]), "+r"(d[2]), "+r"(d[3]), "+r"(d[4]), "+r"(d[5]), "+r"(d[6]), "+r"(d[7]), "+r"(d[8]), "+r"(d[9]), "+r"(d[10]), "+r"(d[11]), "+r"(d[12]), "+r"(d[13]), "+r"(d[14]), "+r"(d[15]), "+r"(d[16]), "+r"(d[17]), "+r"(d[18]), "+r"(d[19]), "+r"(d[20]), "+r"(d[21]), "+r"(d[22]), "+r"(d[23]), "+r"(d[24]), "+r"(d[25]), "+r"(d[26]), "+r"(d[27]), "+r"(d[28]), "+r"(d[29]), "+r"(d[30]), "+r"(d[31])
    : "r"(a0), "r"(a1), "r"(a2), "r"(a3), "l"(db));
}
DEVI void fft2_init(uint32_t* d, uint32_t a0, uint32_t a1, uint32_t a2, uint32_t a3, uint64_t db) {
  asm volatile("wgmma.mma_async.sync.aligned.m64n32k16.f16.f16.f16 {%0, %1, %2, %3, %4, %5, %6, %7}, {%8,%9,%10,%11}, %12, 0, 1, 1, 0;\n"
    : "=r"(d[0]), "=r"(d[1]), "=r"(d[2]), "=r"(d[3]), "=r"(d[4]), "=r"(d[5]), "=r"(d[6]), "=r"(d[7])
    : "r"(a0), "r"(a1), "r"(a2), "r"(a3), "l"(db));
}
DEVI void fft2_acc(uint32_t* d, uint32_t a0, uint32_t a1, uint32_t a2, uint32_t a3, uint64_t db) {
  asm volatile("wgmma.mma_async.sync.aligned.m64n32k16.f16.f16.f16 {%0, %1, %2, %3, %4, %5, %6, %7}, {%8,%9,%10,%11}, %12, 1, 1, 1, 0;\n"
    : "+r"(d[0]), "+r"(d[1]), "+r"(d[2]), "+r"(d[3]), "+r"(d[4]), "+r"(d[5]), "+r"(d[6]), "+r"(d[7])
    : "r"(a0), "r"(a1), "r"(a2), "r"(a3), "l"(db));
}
DEVI void fft3r_init(float* d, uint32_t a0, uint32_t a1, uint32_t a2, uint32_t a3, uint64_t db) {
  asm volatile("wgmma.mma_async.sync.aligned.m64n32k16.f32.f16.f16 {%0, %1, %2, %3, %4, %5, %6, %7, %8, %9, %10, %11, %12, %13, %14, %15}, {%16,%17,%18,%19}, %20, 0, 1, 1, 0;\n"
    : "=f"(d[0]), "=f"(d[1]), "=f"(d[2]), "=f"(d[3]), "=f"(d[4]), "=f"(d[5]), "=f"(d[6]), "=f"(d[7]), "=f"(d[8]), "=f"(d[9]), "=f"(d[10]), "=f"(d[11]), "=f"(d[12]), "=f"(d[13]), "=f"(d[14]), "=f"(d[15])
    : "r"(a0), "r"(a1), "r"(a2), "r"(a3), "l"(db));
}
DEVI void fft3r_acc(float* d, uint32_t a0, uint32_t a1, uint32_t a2, uint32_t a3, uint64_t db) {
  asm volatile("wgmma.mma_async.sync.aligned.m64n32k16.f32.f16.f16 {%0, %1, %2, %3, %4, %5, %6, %7, %8, %9, %10, %11, %12, %13, %14, %15}, {%16,%17,%18,%19}, %20, 1, 1, 1, 0;\n"
    : "+f"(d[0]), "+f"(d[1]), "+f"(d[2]), "+f"(d[3]), "+f"(d[4]), "+f"(d[5]), "+f"(d[6]), "+f"(d[7]), "+f"(d[8]), "+f"(d[9]), "+f"(d[10]), "+f"(d[11]), "+f"(d[12]), "+f"(d[13]), "+f"(d[14]), "+f"(d[15])
    : "r"(a0), "r"(a1), "r"(a2), "r"(a3), "l"(db));
}
DEVI void fft3_init(float* d, uint64_t da, uint64_t db) {
  asm volatile("wgmma.mma_async.sync.aligned.m64n32k16.f32.f16.f16 {%0, %1, %2, %3, %4, %5, %6, %7, %8, %9, %10, %11, %12, %13, %14, %15}, %16, %17, 0, 1, 1, 1, 0;\n"
    : "=f"(d[0]), "=f"(d[1]), "=f"(d[2]), "=f"(d[3]), "=f"(d[4]), "=f"(d[5]), "=f"(d[6]), "=f"(d[7]), "=f"(d[8]), "=f"(d[9]), "=f"(d[10]), "=f"(d[11]), "=f"(d[12]), "=f"(d[13]), "=f"(d[14]), "=f"(d[15])
    : "l"(da), "l"(db));
}
DEVI void fft3_acc(float* d, uint64_t da, uint64_t db) {
  asm volatile("wgmma.mma_async.sync.aligned.m64n32k16.f32.f16.f16 {%0, %1, %2, %3, %4, %5, %6, %7, %8, %9, %10, %11, %12, %13, %14, %15}, %16, %17, 1, 1, 1, 1, 0;\n"
    : "+f"(d[0]), "+f"(d[1]), "+f"(d[2]), "+f"(d[3]), "+f"(d[4]), "+f"(d[5]), "+f"(d[6]), "+f"(d[7]), "+f"(d[8]), "+f"(d[9]), "+f"(d[10]), "+f"(d[11]), "+f"(d[12]), "+f"(d[13]), "+f"(d[14]), "+f"(d[15])
    : "l"(da), "l"(db));
}

__device__ __align__(128) const uint32_t g_tables[2560] = {
0xa11ba1e4,0xa51ba5e4,0x18b61248,0x1cb61648,0x9f12a052,0xa311a452,0x1d7f1bdb,0x217f1fdb,0x9bdb9d7f,0x9fdba17f,0x20521f12,0x24522311,
0x924898b6,0x96489cb6,0x21e4211b,0x25e4251b,0xaa63ab5f,0xae5faf59,0x21e41bdb,0x25e41fdb,0xa86ba967,0xac6aad65,0x26e024e9,0x2ade28e8,
0xa4e9a6e0,0xa8e8aade,0x2967286b,0x2d652c6a,0x9bdba1e4,0x9fdba5e4,0x2b5f2a63,0x2f592e5f,0xadc2aea7,0xb1b6b294,0x254d1f12,0x294d2311,
0xabf6acde,0xafefb0d7,0x2a31286b,0x2e2d2c6a,0xa86baa31,0xac6aae2d,0x2cde2bf6,0x30d72fef,0x9f12a54d,0xa311a94d,0x2ea72dc2,0x329431b6,
0xb02cb0d2,0xb41ab4b7,0x27a9211b,0x2ba7251b,0xadc2af0c,0xb1b6b2f7,0x2c792a63,0x30742e5f,0xaa63ac79,0xae5fb074,0x2f0c2dc2,0x32f731b6,
0xa11ba7a9,0xa51baba7,0x30d2302c,0x34b7341a,0xb17ab257,0xb552b61a,0x290222ad,0x2d0026ad,0xaf8cb09f,0xb371b487,0x2ddc2c2e,0x31cf3029,
0xac2eaddc,0xb029b1cf,0x309f2f8c,0x34873371,0xa2ada902,0xa6adad00,0x3257317a,0x361a3552,0xb2cdb3e3,0xb682b76f,0x2a312420,0x2e2d281f,
0xb0acb1bb,0xb493b58d,0x2f3f2d2a,0x33283122,0xad2aaf3f,0xb122b328,0x31bb30ac,0x358d3493,0xa420aa31,0xa81fae2d,0x33e332cd,0x376f3682,
0xb413b4bc,0xb7a6b85a,0x2b5f24e9,0x2f5928e8,0xb194b2da,0xb56ab68d,0x30522e28,0x343e3219,0xae28b052,0xb219b43e,0x32da3194,0x368d356a,
0xa4e9ab5f,0xa8e8af59,0x34bc3413,0x385a37a6,0xb4c3b58c,0xb85fb8f3,0x2c4725b2,0x304229b1,0xb27eb3fd,0xb63cb785,0x31062f26,0x34e7330f,
0xaf26b106,0xb30fb4e7,0x33fd327e,0x3785363c,0xa5b2ac47,0xa9b1b042,0x358c34c3,0x38f3385f,0xb577b662,0xb8e5b982,0x2cde267b,0x30d72a7a,
0xb36bb493,0xb70ab83a,0x31bb3012,0x358d3402,0xb012b1bb,0xb402b58d,0x3493336b,0x383a370a,0xa67bacde,0xaa7ab0d7,0x36623577,0x398238e5,
0xb630b741,0xb962ba04,0x2d762744,0x316c2b43,0xb42eb52a,0xb7d2b8ad,0x32713092,0x3631347b,0xb092b271,0xb47bb631,0x352a342e,0x38ad37d2,
0xa744ad76,0xab43b16c,0x37413630,0x3a043962,0xb6eeb815,0xb9d6ba7a,0x2e0e2807,0x32012c06,0xb4a7b5c4,0xb84ab91b,0x33293113,0x36d234f3,
0xb113b329,0xb4f3b6d2,0x35c434a7,0x391b384a,0xa807ae0e,0xac06b201,0x381536ee,0x3a7a39d6,0xb7b4b88e,0xba41bae1,0x2ea7286b,0x32942c6a,
0xb523b662,0xb8a8b982,0x33e33194,0x376f356a,0xb194b3e3,0xb56ab76f,0x36623523,0x398238a8,0xa86baea7,0xac6ab294,0x388e37b4,0x3ae13a41,
0xb841b90f,0xbaa2bb3a,0x2f3f28d0,0x33282cce,0xb5a1b705,0xb902b9e3,0x344f3216,0x380535df,0xb216b44f,0xb5dfb805,0x370535a1,0x39e33902,
0xa8d0af3f,0xacceb328,0x390f3841,0x3b3a3aa2,0xb8acb997,0xbaf7bb83,0x2fd82935,0x33ba2d33,0xb621b7ac,0xb958ba3d,0x34ae3298,0x38503654,
0xb298b4ae,0xb654b850,0x37ac3621,0x3a3d3958,0xa935afd8,0xad33b3ba,0x399738ac,0x3b833af7,0xb91cba28,0xbb42bbbc,0x30392999,0x34262d97,
0xb6a4b82d,0xb9aaba90,0x350e331c,0x389936c6,0xb31cb50e,0xb6c6b899,0x382d36a4,0x3a9039aa,0xa999b039,0xad97b426,0x3a28391c,0x3bbc3b42,
0xb992bac3,0xbb81bbe3,0x308529fe,0x346f2dfb,0xb72ab886,0xb9f8badb,0x357033a0,0x38e03737,0xb3a0b570,0xb737b8e0,0x3886372a,0x3adb39f8,
0xa9feb085,0xadfbb46f,0x3ac33992,0x3be33b81,0x39cf3b16,0x3b9c3bf1,0xb0acaa31,0xb493ae2d,0x376f38b4,0x3a1d3afe,0xb5a1b3e3,0xb902b76f,
0x33e335a1,0x376f3902,0xb8b4b76f,0xbafeba1d,0x2a3130ac,0x2e2d3493,0xbb16b9cf,0xbbf1bb9c,0x39563a74,0x3b633bd2,0xb05fa9cc,0xb44badc9,
0x36e73859,0x39d23ab6,0xb53fb35e,0xb8bcb6ff,0x335e353f,0x36ff38bc,0xb859b6e7,0xbab6b9d2,0x29cc305f,0x2dc9344b,0xba74b956,0xbbd2bb63,
0x38e339de,0x3b1e3ba1,0xb012a967,0xb402ad65,0x36623801,0x39823a67,0xb4deb2da,0xb874b68d,0x32da34de,0x368d3874,0xb801b662,0xba67b982,
0x29673012,0x2d653402,0xb9deb8e3,0xbba1bb1e,0x38763952,0x3ace3b60,0xaf8ca902,0xb371ad00,0x35e13758,0x392e3a11,0xb47eb257,0xb82ab61a,
0x3257347e,0x361a382a,0xb758b5e1,0xba11b92e,0x29022f8c,0x2d003371,0xb952b876,0xbb60bace,0x380d38ce,0x3a733b10,0xaef3a89e,0xb2deac9c,
0x356236b3,0x38d639b3,0xb420b1d5,0xb7bdb5a5,0x31d53420,0x35a537bd,0xb6b3b562,0xb9b3b8d6,0x289e2ef3,0x2c9c32de,0xb8ceb80d,0xbb10ba73,
0x37503851,0x3a0d3ab0,0xae5aa839,0xb24bac38,0x34e53613,0x387a394f,0xb386b153,0xb721b52f,0x31533386,0x352f3721,0xb613b4e5,0xb94fb87a,
0x28392e5a,0x2c38324b,0xb851b750,0xbab0ba0d,0x368e37b4,0x399d3a41,0xadc2a7a9,0xb1b6aba7,0x346a3577,0x381a38e5,0xb2cdb0d2,0xb682b4b7,
0x30d232cd,0x34b73682,0xb577b46a,0xb8e5b81a,0x27a92dc2,0x2ba731b6,0xb7b4b68e,0xba41b99d,0x35d236d1,0x392439c5,0xad2aa6e0,0xb122aade,
0x33e334de,0x376f3874,0xb216b052,0xb5dfb43e,0x30523216,0x343e35df,0xb4deb3e3,0xb874b76f,0x26e02d2a,0x2ade3122,0xb6d1b5d2,0xb9c5b924,
0x351c35f6,0x38a3393c,0xac93a617,0xb08daa16,0x32f43448,0x36a437fe,0xb160afa5,0xb53ab389,0x2fa53160,0x3389353a,0xb448b2f4,0xb7feb6a4,
0x26172c93,0x2a16308d,0xb5f6b51c,0xb93cb8a3,0x346a3523,0x381a38a8,0xabf6a54d,0xafefa94d,0x3209336b,0x35d4370a,0xb0acaea7,0xb493b294,
0x2ea730ac,0x32943493,0xb36bb209,0xb70ab5d4,0x254d2bf6,0x294d2fef,0xb523b46a,0xb8a8b81a,0x33783456,0x3715380a,0xaac8a484,0xaec3a884,
0x3120324a,0x34ff360e,0xaff2ada9,0xb3d3b19e,0x2da92ff2,0x319e33d3,0xb24ab120,0xb60eb4ff,0x24842ac8,0x28842ec3,0xb456b378,0xb80ab715,
0x3223331c,0x35eb36c6,0xa999a376,0xad97a776,0x3039312d,0x3426350b,0xae8dacac,0xb27cb0a6,0x2cac2e8d,0x30a6327c,0xb12db039,0xb50bb426,
0x23762999,0x27762d97,0xb31cb223,0xb6c6b5eb,0x30d23194,0x34b7356a,0xa86ba1e4,0xac6aa5e4,0x2ea73012,0x32943402,0xad2aab5f,0xb122af59,
0x2b5f2d2a,0x2f593122,0xb012aea7,0xb402b294,0x21e4286b,0x25e42c6a,0xb194b0d2,0xb56ab4b7,0x2f0c3012,0x32f73402,0xa67ba052,0xaa7aa452,
0x2cde2df5,0x30d731e8,0xab91a967,0xaf8bad65,0x29672b91,0x2d652f8b,0xadf5acde,0xb1e8b0d7,0x2052267b,0x24522a7a,0xb012af0c,0xb402b2f7,
0x2c792d2a,0x30743122,0xa4209d7f,0xa81fa17f,0x2a312b91,0x2e2d2f8b,0xa8d0a6e0,0xacceaade,0x26e028d0,0x2ade2cce,0xab91aa31,0xaf8bae2d,
0x1d7f2420,0x217f281f,0xad2aac79,0xb122b074,0x27a9286b,0x2ba72c6a,0x9f1298b6,0xa3119cb6,0x254d267b,0x294d2a7a,0xa420a1e4,0xa81fa5e4,
0x21e42420,0x25e4281f,0xa67ba54d,0xaa7aa94d,0x18b61f12,0x1cb62311,0xa86ba7a9,0xac6aaba7,0x3f803f80,0x3f803f80,0x3f803f80,0x3f803f80,
0x3f803f80,0x3f803f80,0x3f803f80,0x3f803f80,0x3f803f80,0x3f803f80,0x3f803f80,0x3f803f80,0x3f803f80,0x3f803f80,0x3f803f80,0x3f803f80,
0x3f803f80,0x3f803f80,0x3f803f80,0x3f803f80,0x3f803f80,0x3f803f80,0x3f803f80,0x3f803f80,0x3f803f80,0x3f803f80,0x3f803f80,0x3f803f80,
0x3f803f80,0x3f803f80,0x3f803f80,0x3f803f80,0x3f803f80,0x3f803f80,0x3f803f80,0x3f803f80,0x3f803f80,0x3f803f80,0x3f803f80,0x3f803f80,
0x3f803f80,0x3f803f80,0x3f803f80,0x3f803f80,0x3f803f80,0x3f803f80,0x3f803f80,0x3f803f80,0x3f803f80,0x3f803f80,0x3f803f80,0x3f803f80,
0x3f803f80,0x3f803f80,0x3f803f80,0x3f803f80,0x3f803f80,0x3f803f80,0x3f803f80,0x3f803f80,0x3f803f80,0x3f803f80,0x3f803f80,0x3f803f80,
0x3f803f80,0x3f803f80,0x3f803f80,0x3f803f80,0x3f803f80,0x3f803f80,0x3f803f80,0x3f803f80,0x3f803f80,0x3f803f80,0x3f803f80,0x3f803f80,
0x3f803f80,0x3f803f80,0x3f803f80,0x3f803f80,0x3f803f80,0x3f803f80,0x3f803f80,0x3f803f80,0x3f803f80,0x3f803f80,0x3f803f80,0x3f803f80,
0x3f803f80,0x3f803f80,0x3f803f80,0x3f803f80,0x3f803f80,0x3f803f80,0x3f803f80,0x3f803f80,0x3f803f80,0x3f803f80,0x3f803f80,0x3f803f80,
0x3f803f80,0x3f803f80,0x3f803f80,0x3f803f80,0x3f803f80,0x3f803f80,0x3f803f80,0x3f803f80,0x3f803f80,0x3f803f80,0x3f803f80,0x3f803f80,
0x3f803f80,0x3f803f80,0x3f803f80,0x3f803f80,0x3f803f80,0x3f803f80,0x3f803f80,0x3f803f80,0x3f803f80,0x3f803f80,0x3f803f80,0x3f803f80,
0x3f803f80,0x3f803f80,0x3f803f80,0x3f803f80,0x3f803f80,0x3f803f80,0x3f803f80,0x3f803f80,0x3f803f80,0x3f803f80,0x3f803f80,0x3f803f80,
0x3f803f80,0x3f803f80,0x3f803f80,0x3f803f80,0x3f803f80,0x3f803f80,0x3f803f80,0x3f803f80,0x3f803f80,0x3f803f80,0x3f803f80,0x3f803f80,
0x3f803f80,0x3f803f80,0x3f803f80,0x3f803f80,0x3f803f80,0x3f803f80,0x3f803f80,0x3f803f80,0x3f803f80,0x3f803f80,0x3f803f80,0x3f803f80,
0x3f803f80,0x3f803f80,0x3f803f80,0x3f803f80,0x3f803f80,0x3f803f80,0x3f803f80,0x3f803f80,0x3f803f80,0x3f803f80,0x3f803f80,0x3f803f80,
0x3f803f80,0x3f803f80,0x3f803f80,0x3f803f80,0x3f803f80,0x3f803f80,0x3f803f80,0x3f803f80,0x3f803f80,0x3f803f80,0x3f803f80,0x3f803f80,
0x3f803f80,0x3f803f80,0x3f803f80,0x3f803f80,0x3f803f80,0x3f803f80,0x3f803f80,0x3f803f80,0x3f803f80,0x3f803f80,0x3f803f80,0x3f803f80,
0x3f803f80,0x3f803f80,0x3f803f80,0x3f803f80,0x3f803f80,0x3f803f80,0x3f803f80,0x3f803f80,0x3f803f80,0x3f803f80,0x3f803f80,0x3f803f80,
0x3f803f80,0x3f803f80,0x3f803f80,0x3f803f80,0x3f803f80,0x3f803f80,0x3f803f80,0x3f803f80,0x3f803f80,0x3f803f80,0x3f803f80,0x3f803f80,
0x3f803f80,0x3f803f80,0x3f803f80,0x3f803f80,0x3f803f80,0x3f803f80,0x3f803f80,0x3f803f80,0x3f803f80,0x3f803f80,0x3f803f80,0x3f803f80,
0x3f803f80,0x3f803f80,0x3f803f80,0x3f803f80,0x3f803f80,0x3f803f80,0x3f803f80,0x3f803f80,0x3f803f80,0x3f803f80,0x3f803f80,0x3f803f80,
0x3f803f80,0x3f803f80,0x3f803f80,0x3f803f80,0x3f803f80,0x3f803f80,0x3f803f80,0x3f803f80,0x3f803f80,0x3f803f80,0x3f803f80,0x3f803f80,
0x3f803f80,0x3f803f80,0x3f803f80,0x3f803f80,0x3f803f80,0x3f803f80,0x3f803f80,0x3f803f80,0x3f803f80,0x3f803f80,0x3f803f80,0x3f803f80,
0x3f803f80,0x3f803f80,0x3f803f80,0x3f803f80,0x3f803f80,0x3f803f80,0x3f803f80,0x3f803f80,0x3f803f80,0x3f803f80,0x3f803f80,0x3f803f80,
0x3f803f80,0x3f803f80,0x3f803f80,0x3f803f80,0x3f803f80,0x3f803f80,0x3f803f80,0x3f803f80,0x3f803f80,0x3f803f80,0x3f803f80,0x3f803f80,
0x3f803f80,0x3f803f80,0x3f803f80,0x3f803f80,0x3f803f80,0x3f803f80,0x3f803f80,0x3f803f80,0x3f803f80,0x3f803f80,0x3f803f80,0x3f803f80,
0x3f803f80,0x3f803f80,0x3f803f80,0x3f803f80,0x3f803f80,0x3f803f80,0x3f803f80,0x3f803f80,0x3f803f80,0x3f803f80,0x3f803f80,0x3f803f80,
0x3f803f80,0x3f803f80,0x3f803f80,0x3f803f80,0x3f803f80,0x3f803f80,0x3f803f80,0x3f803f80,0x3f803f80,0x3f803f80,0x3f803f80,0x3f803f80,
0x3f803f80,0x3f803f80,0x3f803f80,0x3f803f80,0x3f803f80,0x3f803f80,0x3f803f80,0x3f803f80,0x3f803f80,0x3f803f80,0x3f803f80,0x3f803f80,
0x3f803f80,0x3f803f80,0x3f803f80,0x3f803f80,0x3f803f80,0x3f803f80,0x3f803f80,0x3f803f80,0x3f803f80,0x3f803f80,0x3f803f80,0x3f803f80,
0x3f803f80,0x3f803f80,0x3f803f80,0x3f803f80,0x3f803f80,0x3f803f80,0x3f803f80,0x3f803f80,0x3f803f80,0x3f803f80,0x3f803f80,0x3f803f80,
0x3f803f80,0x3f803f80,0x3f803f80,0x3f803f80,0x3f803f80,0x3f803f80,0x3f803f80,0x3f803f80,0x3f803f80,0x3f803f80,0x3f803f80,0x3f803f80,
0x3f803f80,0x3f803f80,0x3f803f80,0x3f803f80,0x3f803f80,0x3f803f80,0x3f803f80,0x3f803f80,0x3f803f80,0x3f803f80,0x3f803f80,0x3f803f80,
0x3f803f80,0x3f803f80,0x3f803f80,0x3f803f80,0x3f803f80,0x3f803f80,0x3f803f80,0x3f803f80,0x3f803f80,0x3f803f80,0x3f803f80,0x3f803f80,
0x3f803f80,0x3f803f80,0x3f803f80,0x3f803f80,0x3f803f80,0x3f803f80,0x3f803f80,0x3f803f80,0x3f803f80,0x3f803f80,0x3f803f80,0x3f803f80,
0x3f803f80,0x3f803f80,0x3f803f80,0x3f803f80,0x3f803f80,0x3f803f80,0x3f803f80,0x3f803f80,0x3f803f80,0x3f803f80,0x3f803f80,0x3f803f80,
0x3f803f80,0x3f803f80,0x3f803f80,0x3f803f80,0x3f803f80,0x3f803f80,0x3f803f80,0x3f803f80,0x3f803f80,0x3f803f80,0x3f803f80,0x3f803f80,
0x3f803f80,0x3f803f80,0x3f803f80,0x3f803f80,0x3f803f80,0x3f803f80,0x3f803f80,0x3f803f80,0x3f803f80,0x3f803f80,0x3f803f80,0x3f803f80,
0x3f803f80,0x3f803f80,0x3f803f80,0x3f803f80,0x3f803f80,0x3f803f80,0x3f803f80,0x3f803f80,0x3f803f80,0x3f803f80,0x3f803f80,0x3f803f80,
0x3f803f80,0x3f803f80,0x3f803f80,0x3f803f80,0x3f803f80,0x3f803f80,0x3f803f80,0x3f803f80,0x3f803f80,0x3f803f80,0x3f803f80,0x3f803f80,
0x3f803f80,0x3f803f80,0x3f803f80,0x3f803f80,0x3f803f80,0x3f803f80,0x3f803f80,0x3f803f80,0x3f803f80,0x3f803f80,0x3f803f80,0x3f803f80,
0x3f803f80,0x3f803f80,0x3f803f80,0x3f803f80,0x3f803f80,0x3f803f80,0x3f803f80,0x3f803f80,0x3f803f80,0x3f803f80,0x3f803f80,0x3f803f80,
0x3f803f80,0x3f803f80,0x3f803f80,0x3f803f80,0x3f803f80,0x3f803f80,0x3f803f80,0x3f803f80,0x3f803f80,0x3f803f80,0x3f803f80,0x3f803f80,
0x3f803f80,0x3f803f80,0x3f803f80,0x3f803f80,0x3bf23bff,0x3ba53bd4,0x3b163b65,0x3a493ab6,0x3b7c3bfb,0x38bc3a60,0x2b43356a,0xb7f3b359,
0x3a933bf1,0x9cb63764,0xba9eb785,0xbb73bbf3,0x39463be2,0xb8cc28e8,0xbb42bbc2,0x3328b70a,0x374e3bcf,0xbbabb648,0xaec3baa9,0x3bfa3994,
0x33403bb7,0xbb85b9fc,0x3a64b0be,0x2c6a3b47,0xa4523b9a,0xb86abbae,0x3b6a3911,0xbbd0ad65,0xb4263b78,0x2adebbe6,0x30f03bfd,0xb5b1bbbc,
0x2f5925e4,0x34b73294,0x376f361a,0x38f3385a,0x35a52c9c,0x3a7338d6,0x3bfd3b87,0x3af13bc9,0x388e2fbd,0x3c003b18,0x387f3b10,0xb5d42f27,
0x3a04316c,0x3a673bfe,0xb6bb33d3,0xbbccbb2f,0x3b1e32f7,0x34933b5c,0xbbf5b86f,0x2d00b9bc,0x3bcb343e,0xb576394f,0xb8d1bbe9,0x3bfb36a4,
0x3c0034ff,0xbaac347b,0x3602ba31,0x32de3bf9,0x3bba35bc,0xbbfdb109,0x3be7aa7a,0xbb7a341a,0x394639cd,0x381538b2,0x358136dd,0x3153341a,
0xbb1eb9c9,0xbbf5bbdd,0xba39bb65,0xb4f3b889,0xb340b93c,0x3966340e,0x3bec3b87,0x37213a7e,0x3c003a4d,0x32193a21,0xbb5eb785,0xb894bbb0,
0xb426389e,0xbb37bb45,0x38b7b3d3,0x397d3bfc,0xbafebac1,0x3b13217f,0xadc93aa9,0xba49bb59,0x3979b7e8,0xb0d73b32,0xb6f4bbe9,0x3af139da,
0x38553b24,0xb9a1ba3d,0x3ab03911,0xbb73b759,0x3a043982,0x3ae13a7a,0x3b833b3a,0x3be33bbc,0x374e3986,0xae9131e8,0xb907b61a,0xbb9cba97,
0xbbcbba0d,0xb9e7bbbd,0x3074b56a,0x3b2a38ad,0x2452b8ee,0x3bda3924,0x363c3b10,0xba90b46f,0x3bba3a89,0xb6e836af,0xba76bbc2,0x39d2ac06,
0xb7c8384a,0xb77abc00,0x3bf8386f,0xb8f33654,0xb9d6baf4,0x3be836ff,0xbb3530be,0x37f3b974,0x3abab737,0xb9af3902,0x3865ba31,0xb5d43b1b,
0x32c62fbd,0x363134cf,0x38653785,0x398b38fd,0xb715b16c,0xbae1b970,0xbbfebbc2,0xba85bb92,0x392e32f7,0x3bf53b6c,0x37a63aa9,0xb7422311,
0xba81b43e,0xb9e7bbfc,0x380fb0be,0x3b963b7f,0x3b7134ff,0x32193b04,0xbc00b911,0x319eb929,0xbbefb5bc,0x36e8b8b2,0x382a3bfd,0xbbffb805,
0x3bf23676,0xbb1331e8,0x376fb9aa,0x2f8b3bde,0xbb7cb72c,0x3be8340e,0xbbfdaa16,0x3bb8b122,0xbbd2bbf1,0xbb60bba1,0xbab0bb10,0xb9c5ba41,
0x3b2c3be2,0x381539df,0xa94d33d3,0xb8a3b52f,0xba19bbcf,0x2e91b5f7,0x3b07386f,0x3b213c00,0x38a83bb7,0xb966aba7,0xbae5bbe9,0x3517b599,
0xb5dfbb9a,0x3bda37b2,0x1fdb3a31,0xbbe0ba1d,0x30293b78,0xbb37ba7a,0x3ad5aa7a,0xa7763aeb,0x2f59bb52,0x377a3bdd,0xbb16b9a6,0x3bf231cf,
0xb5a53b27,0x30d7bbbd,0x2b433bfe,0xb432bbe5,0x3a813a0d,0x3b3f3ae8,0x3bbf3b87,0x3bfb3be5,0xb5dfb8ee,0x3263ad97,0x399d3785,0x3bd03b01,
0xbbefba89,0xb958bb81,0x3389b3d3,0x3b7a394a,0xaf59384a,0xbbf7b9b8,0xb4c3baa9,0x3afb35eb,0x3b7c3af4,0xb825353a,0xb9f8bbe9,0x3a542884,
0x388eb737,0x360e3bf4,0xbbdcb911,0x398bb4db,0xb946bb4f,0x3bc03830,0xbb832a7a,0x38a3b8db,0xbb1e35c8,0x3a35b85f,0xb90739aa,0x3742bab6,
0xb8a8b93c,0xb6c6b80a,0xb402b56a,0xac6ab122,0xbb71ba4d,0xbbd7bbf8,0xb9b3bb10,0xb2deb7bd,0x3029389e,0xb9f4b58d,0xbbc6bbc2,0xb5b1ba00,
0x3bf23ac1,0x2dfb3999,0xbba3b86f,0xb7d2bb6f,0x35a5b7e8,0x3ad83b90,0xb95430be,0xb8e5bbff,0xba93bb24,0x3b682ef5,0xb2013a31,0xb9c5bb9f,
0xba043682,0x33ebbad1,0x35813bfd,0xba85ba5c,0x374e3b76,0xb90cbab3,0x3a3939a6,0xbb21b85a,0xb7c83b52,0x391bba9b,0xba2539aa,0x3afbb889,
0xb9793b27,0x3bc5b80a,0xbb8eaa16,0x38e538ad,0xbaba3af7,0x3b60ad97,0xb27cba2d,0xb98b3bb0,0xbb943ac4,0x3815358d,0x39e3bbea,0xba852c06,
0xbbf93a8c,0xae9139b8,0x3bacb874,0x3742bb59,0xbbe43a50,0xb9663b90,0x340233ba,0x3b96b974,0xbb573a11,0xbbda3bf4,0xb99d3b0d,0xb19e3759,
0xba5839cd,0xbb373ad1,0xbbc63b89,0xbbff3bee,0x3afe3676,0xba29b884,0x391f39a6,0xb7d2ba97,0x39d6372c,0xb3a2bae8,0xb5463bfe,0x3a54ba7e,
0x385537dd,0x3631bbf8,0xbbd63916,0x39c5346f,0x35233845,0x3ae1bb81,0xb96bb0a6,0xb8a33bfc,0x2d333899,0x3bf5b999,0x3487baa5,0xbb213654,
0xb13b38ea,0x39e7b53a,0x3bbfbbc3,0x3517b9da,0xb65f3937,0x32192ef5,0x39b3b790,0x3be0bb1b,0xb8e03982,0xb6e83830,0xb389355e,0xa7763042,
0xbb943682,0x3bebb371,0xbbfe2a7a,0x3bcc3042,0xad33bb76,0xb79b3bd4,0x3b07b9aa,0xbbfa32ad,0x3be4b50b,0xb6c6b8d6,0xb80f3bfe,0x3bfbb835,
0xb65f3bb5,0x3bd7b764,0x9fdbba2d,0xbbd03a41,0xba58330f,0xb9f43bfe,0x382a30a6,0x3b7abb92,0x3a45bbe1,0xadfbb648,0xbb163874,0xbafb3c00,
0x3699afef,0x3ad8b94f,0x3bfdbbc3,0x3a54bb7f,0xbbdf3bfa,0xbb683bae,0xba9e3b0d,0xb98b3a1d,0x35233b4f,0xb08dbbc8,0xa94d3bfd,0x3328bbee,
0xbbf935c8,0x3b0a3294,0xb7a6b9a6,0xad003bd3,0x313bbb98,0xbb3f3a60,0x3ae52a16,0xac6abace,0x3b57b44b,0x3263bb18,0xbc003916,0x32de38fd,
0xb8e03bce,0x3958a8e8,0x3ad5bbea,0xb5b1b52f,0xb8f83185,0xbbf73b5c,0xb76f3aa5,0x37d2a311,0x3b4abbf0,0x3825b9fc,0xab43b3ba,0xb8e53599,
0x31b6acce,0x360eb47b,0x387fb790,0x39c5b929,0x3a9337dd,0xb9a1b924,0x387f3a2d,0xb66bbb01,0xb946b845,0x308d3b45,0x36bbbbea,0xbac73a00,
0x374e3899,0x379bbc00,0xbbf53874,0x393335eb,0xb340b8ea,0xbb3f3b32,0x38d133ba,0x3941bbff,0xa4523937,0x3bd7b902,0x3602bb0d,0xbabd34db,
0x3426b982,0xb9583371,0xbbe73b89,0xb68d3a5c,0xb7c839c9,0x2dfb3294,0x391fb625,0x3bb3bab6,0x3979ba0d,0x3825b8d6,0x3546b6d2,0x3010b359,
0x388ebaf7,0xb9af3a21,0x3a9eb916,0xbb5437bd,0xba043ac4,0x3bebb6af,0xbb42b0a6,0x3840394a,0x3b1eba8c,0xbb0aa17f,0x2ec33aa5,0x3a15bb6f,
0xbbcb3a50,0x36c636ff,0x3a64bbc3,0xba09a884,0x3c00ba11,0x3263ba3d,0xbb6a3790,0xb8503b9f,0xbbba39cd,0xb9f43bc8,0x30f0355e,0x3b4cb8db,
0x3afeb986,0x3bf7bbd4,0x3a25bb63,0x3457b85a,0xb9d6393c,0xbad83a60,0xbb8e3b3d,0xbbef3bc9,0x33403b98,0xa9b1bbed,0xb0743bfe,0x3517bbc9,
0x3c00b44b,0xbaa2b4cf,0x363c3a2d,0x319ebbf3,0x3426bbce,0xbb8b39df,0x3a7630a6,0x2776bb2f,0xbafe3185,0xb4b73b6c,0x3bf8b874,0xaf8bb994,
0xb9793bf0,0x38bc2ba7,0x3b35bbc3,0xb432b6a4,0x3855acce,0x3c00bb04,0x3865bb0d,0xb66bad65,0x3b94bbff,0x38ccba7a,0x294db55e,0xb840341a,
0xad33a5e4,0xb49331e8,0xb7a63625,0xb9333889,0x3bcbb50b,0xbbfe305b,0x3bec2a16,0xbb96b359,0x2452bbb5,0xb87a3ba1,0x3b5eb916,0xbbe02f27,
0xbbba330f,0x35523970,0x38b7bbea,0xbbff370a,0xb7c83be1,0x3ba5b5f7,0x2dc9baa5,0xbbf239bc,0x39d6afef,0x3a73bbfc,0xb6f4b3ba,0xbbb83b47,
0x3ababbfa,0x1cb6b7b2,0xbab03790,0xbb543bf9,0xb52326ad,0xba6738b2,0xbbfe3b89,0xbac73bbc,0xbbf93bff,0xbbab3bdd,0xbb073b63,0xba153a97,
0xb8f83986,0xb77a385f,0xb4c33625,0xaf8b32ad,0xb699393c,0x30d7305b,0x3954b6d2,0x3bb8bace,0xb1b638ee,0x39afb4cf,0x3bdcbba7,0x366bba41,
0x2c38389e,0x3bebb970,0x3581bade,0xbac7352f,0x34e7384a,0x3b0abb6c,0xb907b24b,0xb9333c00,0x383a37e8,0x36c6bbfc,0xbbec38c1,0x39413599,
0x39c03737,0xb263bb04,0xb63c3bf6,0x3abdba1d,0x3aee3682,0xb9f4b8b2,0x38b739f0,0xb68dbaeb,0xba4539c9,0xbb133ab3,0xbba33b63,0xbbf23bd3,
0xbb4a3a0d,0xbbe83bed,0xb9f83b3d,0xb4323835,0xbbdf3a4d,0xb9a13ba1,0x320134ab,0x3b54b8fd,0xbbfc3a89,0xb08d39df,0x3b83b81a,0x3840bb92,
0xbb9e3ac1,0x379b35f7,0x3a39bbd8,0xba15a311,0xbacb3af4,0x3b3faba7,0xb074ba6f,0xba093b7f,0xb9903b24,0x3bd7b7b2,0xbb5eae5f,0x38503929,
0xb7fe3b4f,0x3958ba7a,0xba76395d,0x3b4cb805,0x2c3826ad,0x33ebb109,0x36bbb55e,0x38a3b805,0x3b9ebbff,0x390cba9b,0x2ec3b625,0xb74231cf,
0xb83a2c9c,0xbbfe3ae8,0xb8d13b3d,0x35173122,0xb9903bf1,0x387a2d97,0x3b6abba7,0xb19eb7bd,0x3aeeb16c,0x3552bb81,0xbbe7381a,0x27763a00,
0x3463bbcf,0xbba539b8,0x3a25324b,0x2f8bbb6f,0xbbff343e,0x3a73353a,0xb546ba6f,0xb4323bff,0x32c63b9a,0x9cb6bbf4,0xb27c3bf6,0x366bbb9f,
0xbbfc3bff,0xbbc03be6,0xbb423b89,0xba853aeb,0x34e7a5e4,0x3a35b884,0x3bf5bb63,0x3b21bbde,0x3acbbbfb,0x29b1b80a,0xba6436d2,0xbb963be5,
0xb9c02fbd,0xbaa23bf8,0x360234ab,0x3be0bb01,0xb7fe3be2,0x3b8bb58d,0x30f0bade,0xbbff394a,0x3bb2b2f7,0xb4b7b999,0xb91f3bd8,0x3bf2b5eb,
0x281fbbb7,0xb8bc3b90,0x3b8eb8c1,0xbbb82884,0xbbd234ff,0x3c00aef5,0xbbd6ae5f,0x3b5434db,0xbaba3a4d,0xbb683b18,0xbbd63ba7,0xbc003bf3,
0x3b94ba89,0x3bc0bbfe,0x396bbade,0x3153b70a,0xbbf93ac1,0xb90c3b5c,0x3487324b,0x3b9cb994,0x3be4baf4,0x29b1b94f,0xbbbf38c1,0xb7213b47,
0xbb573b24,0x387a347b,0x39b3bbf6,0xba902d65,0x3a58bb4f,0xbb8b3109,0x338939f0,0x397dbbbc,0xb8f83b76,0x3ba5b884,0xbba39648,0x38f33889,
0x3699bb98,0xb8bc3ae8,0x39f8b9eb,0xbaf138ad,0x3855b8ee,0x360eb764,0x327cb4ab,0x251baf27,0xb523389e,0x33eb28e8,0x39e3b81a,0x3be3bb2f,
0x2d33b84a,0xba353648,0xbbac3bd8,0xb4f339bc,0x313b37e8,0x3bfeb9fc,0x3402ba6f,0xbb2a36a4,0xb65fb737,0xbaa23bae,0x399d2e5f,0x3894bbf9,
0x38e03682,0x3552bbe6,0xbbc6395d,0x39d2341a,0xba45b5c8,0x34b73a9b,0x34c3bc00,0xba493a97,0x3b4a350b,0xba73b80a,0x39543962,0xb7f3ba7e,
0xbbe43bfb,0xbb853bbd,0xbae53b3d,0xba093a7e,0xb65f2fbd,0xbaac3924,0xbc003ba7,0xbabd3bb0,0x3a58bbe2,0xaadeb6af,0xbad5381a,0xbb4c3bfc,
0x3a45b2f7,0x3a29bc00,0xb76fb24b,0xbbb33b59,0xb6993bb7,0x3bc5b6ff,0x2b43ba6f,0xbbef39da,0xbbdf34ff,0x36313902,0x387fbbf6,0xbc003759,
0xac38bb78,0xb8153bc8,0x3b42b95d,0xbbe33042,0x3b9eb676,0xbbf53294,0x3bf51648,0xbb9cb2ad,0xb13b2c9c,0xb576340e,0xb80f36d2,0xb94138ad,
0x3b57bbf1,0x386aba21,0x1fdbb4ab,0xb850346f,0x38e0b16c,0x3bfdbb45,0x382abade,0xb68dac06,0xb8f83bcf,0x391ba17f,0x3b16bbd8,0xb457b654,
0xbb4a343e,0xb3a23b32,0x3bfdb8c1,0xb010b974,0x31b6bb9a,0xbb603a3d,0x3a9e2e5f,0x251bbb1b,0x3bfcb5bc,0xbae1b371,0x36bb39f0,0x3153bbee,
0x34e73b52,0xae91bbd4,0xaec33c00,0x34f3bbd3,0x3bb235c8,0xbbf7b1e8,0x3bf81648,0xbbb331cf,0x3bff350b,0xbad8340e,0x36f4b9eb,0x30103be5,
0x3bd2344b,0xb60e3924,0xb865bbf6,0x3c0037bd,0x3b2c330f,0x33eb3b45,0xbbfeb8c7,0x3153b94a,0x3a193185,0x3a353c00,0xb7a63232,0xbb9cbb6f,
0x38a82fef,0x3bfe3b32,0x380f3adb,0xb7212884,0x35df2cce,0x3aa23902,0x3c003ba9,0x3a903b9f,0x302926ad,0x35523371,0x382a36dd,0x397d38db,
0xb4633b76,0x2dfbbbdd,0x2dc93c00,0xb457bbde,0xa81f3b98,0xb825bbbd,0x3b353962,0xbbefb122,0x32c63bb5,0xbb68ba21,0x3ab0ae2d,0xa51b3b01,
0x37153bce,0xbbc0b6af,0xa94dba6b,0x3be33a00,0x392e3be1,0xb90c217f,0xbb07bbd9,0x34f3b5eb,0x3a813bf0,0xa9b136ff,0xbae5b820,0xbb2abbff,
0x3b713bfa,0x387a3a3d,0x9fdb349f,0xb894b4db,0x3bef3bff,0x3b8b3bc8,0x3ad53b3a,0x39d23a5c,0x3b2cb5bc,0xba673830,0x396bb95d,0xb8403a5c,
0xb92ebb52,0x3bab385f,0xbbac9648,0x3933b85a,0xb8a8372c,0xb576bbed,0x3bbf3962,0xba093359,0x3b713af7,0xb86a34cf,0xb99dbbf6,0x3abd2f27,
0x3029b845,0x3bfd39df,0x33893a6b,0xbb4cb70a,0xbbf2ba8c,0xb91bbb6c,0x34c3b232,0x3bb339bc,0x35a538ea,0xb3a22ba7,0xb9f8b820,0xbbefbb47,
0x3a933a11,0x3b603b04,0x3bdc3ba9,0x3c003bf9,0x37153b78,0xb8ccbad1,0x39e339f0,0xbac7b8db,0x3a19b676,0xb4933ab3,0xb487bc00,0x3a153ab6,
0xba81bb27,0x3b85305b,0xb40239eb,0xb941bbc9,0xb5df37dd,0xbaacbba1,0x39b3ae2d,0x38503bf3,0x3bef3ac4,0x2ade3970,0xbbc6b8c7,0xb68dbb2f,
0xaf59b899,0x3a2935f7,0x3ba33bd9,0x34573994,0xbb7cba50,0xbbc5bbfc,0xb954badb,0xb010b6a4,0x388e3937,0x363137b2,0x3201349f,0xa51b2d65,
0xb1b63bb5,0x9cb6bbf8,0x32013bf6,0xb5d4bbb0,0xac38bbce,0x38cc3b81,0xbb83b8c7,0x3bcc2c06,0x34e73be1,0xbbabb999,0x3a39b232,0x2d003b59,
0xb83abbf0,0x3b85353a,0x30743adb,0xbbfbb974,0x39c03bfa,0xb86a2ef5,0xbb5ebba9,0x32deb759,0xbaeebbff,0xaadeb830,0x3a7636dd,0x3b7a3bee,
0x3bb23bff,0x391b3ab3,0x2dc9361a,0xb7d2b2ad,0xbbffbbfb,0xbbc5bbed,0xbb35bb87,0xba54bace,0xbbdfb44b,0x3c002d97,0xbbdc2e2d,0x3b73b46f,
0x3bfc330f,0xba67358d,0x3581ba6b,0x33283bfc,0xbb9eb185,0x3493b9b8,0x39073bd9,0xbbfab654,0x3acb2fef,0x35763b90,0xbbecb820,0x2c6ab9da,
0xb990acce,0xbaacbbf4,0x363cb49f,0x3bd03b1b,0x37fe26ad,0x3bfd3ad1,0x38b73b3a,0xb5b13042,0xb46325e4,0xba29b85f,0xbbf8bb65,0xbafbbbd3,
0x281fac9c,0x33a2305b,0x36f4356a,0x38e53835,0x383a3b27,0xb966ba60,0x3a643962,0xbb2ab835,0xb99037dd,0x3219bb18,0x36023bf6,0xba90ba41,
0xbaeebac4,0x3b3728e8,0xb0f03a6b,0xb9d2bb92,0x3463b899,0x3b133b5c,0xb91f3232,0xb8f3bc00,0x3bff3a50,0x30d739fc,0xbb8eb820,0xb7f3bb7f,
0x32c63937,0xb9a1b47b,0xbbd6bba9,0xb5d4ba1d,0xbb2cb9cd,0xbbebbbe6,0xb9e3bb3a,0xb328b805,0xb92eb9c9,0xb79bb884,0xb487b61a,0xad00b1cf,
0xbacb372c,0x39e7b8d6,0xb8d139eb,0x3721bace,0xb9c0baf7,0x3bda3764,0xbb6a2e2d,0x3894b8fd,0x37feb845,0x36e83bfe,0xbbe7b8c7,0x397db52f,
0x3bb23a8c,0xb77a3648,0xba25bbd9,0x3a492311,0xa81f38ea,0xbbe8b94f,0xb546badb,0x3af13599,0xbbd2ba11,0xb9afbbae,0x327cb49f,0x3b733929,
0xb715b982,0x308db109,0x396b36dd,0x3bcc3aeb,0x3a193986,0x3b0a3a9b,0x3bac3b65,0x3bfa3bde,0x30003000,0x30003000,0x30003000,0x30003000,
0x2f643000,0x2a1f2da8,0xaa1f0000,0xaf64ada8,0x2da83000,0xada80000,0xada8b000,0x2da88000,0x2a1f3000,0xaf64ada8,0x2f648000,0xaa1f2da8,
0x00003000,0x8000b000,0x00003000,0x8000b000,0xaa1f3000,0x2f64ada8,0xaf640000,0x2a1f2da8,0xada83000,0x2da88000,0x2da8b000,0xada80000,
0xaf643000,0xaa1f2da8,0x2a1f8000,0x2f64ada8,0x30003000,0x30003000,0x30003000,0x30003000,0xaf64b000,0xaa1fada8,0x2a1f8000,0x2f642da8,
0x2da83000,0xada80000,0xada8b000,0x2da88000,0xaa1fb000,0x2f642da8,0xaf640000,0x2a1fada8,0x00003000,0x8000b000,0x00003000,0x8000b000,
0x2a1fb000,0xaf642da8,0x2f648000,0xaa1fada8,0xada83000,0x2da88000,0x2da8b000,0xada80000,0x2f64b000,0x2a1fada8,0xaa1f0000,0xaf642da8,
0x80008000,0x80008000,0x80008000,0x80008000,0xaa1f8000,0xaf64ada8,0xaf64b000,0xaa1fada8,0xada88000,0xada8b000,0x2da88000,0x2da83000,
0xaf648000,0x2a1fada8,0x2a1f3000,0xaf64ada8,0xb0008000,0x30008000,0xb0008000,0x30008000,0xaf648000,0x2a1f2da8,0x2a1fb000,0xaf642da8,
0xada88000,0xada83000,0x2da88000,0x2da8b000,0xaa1f8000,0xaf642da8,0xaf643000,0xaa1f2da8,0x80008000,0x80008000,0x80008000,0x80008000,
0x2a1f8000,0x2f642da8,0x2f643000,0x2a1f2da8,0xada88000,0xada8b000,0x2da88000,0x2da83000,0x2f648000,0xaa1f2da8,0xaa1fb000,0x2f642da8,
0xb0008000,0x30008000,0xb0008000,0x30008000,0x2f648000,0xaa1fada8,0xaa1f3000,0x2f64ada8,0xada88000,0xada83000,0x2da88000,0x2da8b000,
0x2a1f8000,0x2f64ada8,0x2f64b000,0x2a1fada8,0xb0003000,0xb0003000,0xb0003000,0xb0003000,0xaf643000,0xaa1f2da8,0x2a1f0000,0x2f64ada8,
0xada83000,0x2da80000,0x2da8b000,0xada88000,0xaa1f3000,0x2f64ada8,0xaf648000,0x2a1f2da8,0x80003000,0x0000b000,0x80003000,0x0000b000,
0x2a1f3000,0xaf64ada8,0x2f640000,0xaa1f2da8,0x2da83000,0xada88000,0xada8b000,0x2da80000,0x2f643000,0x2a1f2da8,0xaa1f8000,0xaf64ada8,
0xb0003000,0xb0003000,0xb0003000,0xb0003000,0x2f64b000,0x2a1fada8,0xaa1f8000,0xaf642da8,0xada83000,0x2da80000,0x2da8b000,0xada88000,
0x2a1fb000,0xaf642da8,0x2f640000,0xaa1fada8,0x80003000,0x0000b000,0x80003000,0x0000b000,0xaa1fb000,0x2f642da8,0xaf648000,0x2a1fada8,
0x2da83000,0xada88000,0xada8b000,0x2da80000,0xaf64b000,0xaa1fada8,0x2a1f0000,0x2f642da8,0x80008000,0x80008000,0x80008000,0x80008000,
0x2a1f8000,0x2f64ada8,0x2f64b000,0x2a1fada8,0x2da88000,0x2da8b000,0xada88000,0xada83000,0x2f648000,0xaa1fada8,0xaa1f3000,0x2f64ada8,
0x30008000,0xb0008000,0x30008000,0xb0008000,0x2f648000,0xaa1f2da8,0xaa1fb000,0x2f642da8,0x2da88000,0x2da83000,0xada88000,0xada8b000,
0x2a1f8000,0x2f642da8,0x2f643000,0x2a1f2da8,0x80008000,0x80008000,0x80008000,0x80008000,0xaa1f8000,0xaf642da8,0xaf643000,0xaa1f2da8,
0x2da88000,0x2da8b000,0xada88000,0xada83000,0xaf648000,0x2a1f2da8,0x2a1fb000,0xaf642da8,0x30008000,0xb0008000,0x30008000,0xb0008000,
0xaf648000,0x2a1fada8,0x2a1f3000,0xaf64ada8,0x2da88000,0x2da83000,0xada88000,0xada8b000,0xaa1f8000,0xaf64ada8,0xaf64b000,0xaa1fada8,
0x00000000,0x00000000,0x00000000,0x00000000,0x2a1f0000,0x2f642da8,0x2f643000,0x2a1f2da8,0x2da80000,0x2da83000,0xada80000,0xada8b000,
0x2f640000,0xaa1f2da8,0xaa1fb000,0x2f642da8,0x30000000,0xb0000000,0x30000000,0xb0000000,0x2f640000,0xaa1fada8,0xaa1f3000,0x2f64ada8,
0x2da80000,0x2da8b000,0xada80000,0xada83000,0x2a1f0000,0x2f64ada8,0x2f64b000,0x2a1fada8,0x00000000,0x00000000,0x00000000,0x00000000,
0xaa1f0000,0xaf64ada8,0xaf64b000,0xaa1fada8,0x2da80000,0x2da83000,0xada80000,0xada8b000,0xaf640000,0x2a1fada8,0x2a1f3000,0xaf64ada8,
0x30000000,0xb0000000,0x30000000,0xb0000000,0xaf640000,0x2a1f2da8,0x2a1fb000,0xaf642da8,0x2da80000,0x2da8b000,0xada80000,0xada83000,
0xaa1f0000,0xaf642da8,0xaf643000,0xaa1f2da8,0x30003000,0x30003000,0x30003000,0x30003000,0x2f643000,0x2a1f2da8,0xaa1f0000,0xaf64ada8,
0x2da83000,0xada80000,0xada8b000,0x2da88000,0x2a1f3000,0xaf64ada8,0x2f648000,0xaa1f2da8,0x00003000,0x8000b000,0x00003000,0x8000b000,
0xaa1f3000,0x2f64ada8,0xaf640000,0x2a1f2da8,0xada83000,0x2da88000,0x2da8b000,0xada80000,0xaf643000,0xaa1f2da8,0x2a1f8000,0x2f64ada8,
0x30003000,0x30003000,0x30003000,0x30003000,0xaf64b000,0xaa1fada8,0x2a1f8000,0x2f642da8,0x2da83000,0xada80000,0xada8b000,0x2da88000,
0xaa1fb000,0x2f642da8,0xaf640000,0x2a1fada8,0x00003000,0x8000b000,0x00003000,0x8000b000,0x2a1fb000,0xaf642da8,0x2f648000,0xaa1fada8,
0xada83000,0x2da88000,0x2da8b000,0xada80000,0x2f64b000,0x2a1fada8,0xaa1f0000,0xaf642da8,0x00000000,0x00000000,0x00000000,0x00000000,
0xaa1f0000,0xaf642da8,0xaf643000,0xaa1f2da8,0xada80000,0xada83000,0x2da80000,0x2da8b000,0xaf640000,0x2a1f2da8,0x2a1fb000,0xaf642da8,
0xb0000000,0x30000000,0xb0000000,0x30000000,0xaf640000,0x2a1fada8,0x2a1f3000,0xaf64ada8,0xada80000,0xada8b000,0x2da80000,0x2da83000,
0xaa1f0000,0xaf64ada8,0xaf64b000,0xaa1fada8,0x00000000,0x00000000,0x00000000,0x00000000,0x2a1f0000,0x2f64ada8,0x2f64b000,0x2a1fada8,
0xada80000,0xada83000,0x2da80000,0x2da8b000,0x2f640000,0xaa1fada8,0xaa1f3000,0x2f64ada8,0xb0000000,0x30000000,0xb0000000,0x30000000,
0x2f640000,0xaa1f2da8,0xaa1fb000,0x2f642da8,0xada80000,0xada8b000,0x2da80000,0x2da83000,0x2a1f0000,0x2f642da8,0x2f643000,0x2a1f2da8,
0xb0003000,0xb0003000,0xb0003000,0xb0003000,0xaf643000,0xaa1f2da8,0x2a1f0000,0x2f64ada8,0xada83000,0x2da80000,0x2da8b000,0xada88000,
0xaa1f3000,0x2f64ada8,0xaf648000,0x2a1f2da8,0x80003000,0x0000b000,0x80003000,0x0000b000,0x2a1f3000,0xaf64ada8,0x2f640000,0xaa1f2da8,
0x2da83000,0xada88000,0xada8b000,0x2da80000,0x2f643000,0x2a1f2da8,0xaa1f8000,0xaf64ada8,0xb0003000,0xb0003000,0xb0003000,0xb0003000,
0x2f64b000,0x2a1fada8,0xaa1f8000,0xaf642da8,0xada83000,0x2da80000,0x2da8b000,0xada88000,0x2a1fb000,0xaf642da8,0x2f640000,0xaa1fada8,
0x80003000,0x0000b000,0x80003000,0x0000b000,0xaa1fb000,0x2f642da8,0xaf648000,0x2a1fada8,0x2da83000,0xada88000,0xada8b000,0x2da80000,
0xaf64b000,0xaa1fada8,0x2a1f0000,0x2f642da8};

constexpr int kThreads = 384;
constexpr int kCtas = 128;

constexpr uint32_t SM_BASE = 1024;
constexpr uint32_t QKV_STAGE = 32768;
constexpr uint32_t SLOT = 16384;
constexpr uint32_t SM_KV = 2 * SLOT;
constexpr uint32_t SM_SIG = 131072;
constexpr uint32_t SM_STG = 196608;
constexpr uint32_t SM_Q = SM_STG;
constexpr uint32_t SM_Y0 = 3 * SLOT;
constexpr uint32_t SM_YT = SM_STG + 16384;
constexpr uint32_t SM_TW = SM_STG + 24576, SM_ONES = SM_TW + 2048, SM_F1 = SM_ONES + 2048, SM_F2 = SM_F1 + 4096;
constexpr uint32_t SM_BAR = SM_F2 + 2048;
constexpr uint32_t SM_SC = SM_BAR + 640;
constexpr uint32_t SM_TOTAL = 232448;
constexpr uint32_t A_SLOTS = 0xB2910, B_SLOTS = 0xA7654;

enum Bar { B_QKV_EMPTY = 0, B_QKV_DONE = 4, B_CONV_DONE = 5,
           B_OUT_EMPTY = 8,
           B_H_FULL = 16, B_YIN = 19, B_RDY0 = 21, B_RDY1 = 22, B_ZEROED = 23,
           B_OUT_FULL = 24, B_PREP_FULL = 29,
           B_Q_FULL = 32, B_OT_FREE = 36, B_Y_READY = 38, B_FLAGS1 = 39,
           B_SEG = 40, B_SIG_READY = 44, B_KV_READY = 45,
           B_KVP = 48, B_O_WRITTEN = 49,
           B_PREP_EMPTY = 56,
           B_QKV_FULL = 64, B_STG_FREE = 68 };
constexpr uint32_t BAR_LOG2 = 0x13200044;

constexpr int KV_SLICE = 640;
constexpr int XCH_FLAG = 2 * SLOT + 17 * KV_SLICE;
constexpr int XCH_BYTES = 11 * 4096;

struct Params {
  CUtensorMap x, w, wk, wo, outa, k, v, q;
  const __nv_bfloat16* shift_k;
  const __nv_bfloat16* ssm_k;
  const __nv_bfloat16* ssm_d;
  const __nv_bfloat16* q_ptr;
  __nv_bfloat16* out_ptr;
  const __nv_bfloat16* wo_ptr;
  int zero;
};

__device__ __align__(128) uint8_t g_xch[kCtas][XCH_BYTES];
__device__ unsigned g_ready, g_epoch[kCtas];

#define TSTAMP(cond, i) do { } while (0)
#define GSTAMP(cond, i) do { } while (0)
#define LOOPSTAMP(id, cond, i) do { } while (0)

constexpr int kSpinLimit = 1 << 17;

DEVI void mbar_init(uint32_t a, uint32_t c) { asm volatile("mbarrier.init.shared::cta.b64 [%0], %1;" :: "r"(a), "r"(c) : "memory"); }
DEVI void mbar_expect(uint32_t a, uint32_t b) { asm volatile("mbarrier.arrive.expect_tx.shared::cta.b64 _, [%0], %1;" :: "r"(a), "r"(b) : "memory"); }
DEVI void mbar_arrive(uint32_t a) { asm volatile("mbarrier.arrive.shared::cta.b64 _, [%0];" :: "r"(a) : "memory"); }
DEVI void mbar_arrive_if(uint32_t a, bool pred) {
  asm volatile("{\n.reg .pred p;\nsetp.ne.b32 p, %1, 0;\n@p mbarrier.arrive.shared::cta.b64 _, [%0];\n}" :: "r"(a), "r"((int)pred) : "memory");
}
DEVI void mbar_wait(uint32_t a, uint32_t parity) {
  asm volatile("{\n.reg .pred p;\n.reg .u32 n;\nmov.u32 n, 0;\nW_LOOP:\n"
               "mbarrier.try_wait.parity.shared::cta.b64 p, [%0], %1;\nadd.u32 n, n, 1;\n"
               "setp.lt.and.u32 p, n, %2, !p;\n@p bra W_LOOP;\n}"
               :: "r"(a), "r"(parity), "n"(kSpinLimit) : "memory");
}
DEVI bool mbar_test(uint32_t a, uint32_t parity) {
  uint32_t ok;
  asm volatile("{\n.reg .pred p;\nmbarrier.test_wait.parity.shared::cta.b64 p, [%1], %2;\nselp.u32 %0, 1, 0, p;\n}" : "=r"(ok) : "r"(a), "r"(parity) : "memory");
  return ok;
}
DEVI bool elect() {
  uint32_t ok;
  asm volatile("{\n.reg .pred p;\nelect.sync _|p, 0xffffffff;\nselp.u32 %0, 1, 0, p;\n}" : "=r"(ok));
  return ok;
}
DEVI void flag_wait(const unsigned* p, unsigned target) {
  int n = 0; unsigned v;
  do {
    asm volatile("ld.acquire.gpu.global.u32 %0, [%1];" : "=r"(v) : "l"(p) : "memory");
  } while ((int)(v - target) < 0 && ++n < kSpinLimit);
}
DEVI void st_relaxed(void* p, uint32_t v) { asm volatile("st.relaxed.gpu.global.b32 [%0], %1;" :: "l"(p), "r"(v) : "memory"); }
DEVI uint32_t ld_relaxed(const void* p) { uint32_t v; asm volatile("ld.relaxed.gpu.global.b32 %0, [%1];" : "=r"(v) : "l"(p) : "memory"); return v; }
DEVI void ld_relaxed4(uint32_t* v, const void* p) {
  asm volatile("ld.relaxed.gpu.global.v4.b32 {%0,%1,%2,%3}, [%4];" : "=r"(v[0]), "=r"(v[1]), "=r"(v[2]), "=r"(v[3]) : "l"(p) : "memory");
}
template <int N> DEVI bool all_arrived(const uint32_t* v) {
  uint32_t m = v[0];
#pragma unroll
  for (int i = 1; i + 1 < N; i += 2) m = __vimax3_u32(m, v[i], v[i + 1]);
  if (N % 2 == 0) m = max(m, v[N - 1]);
  return __all_sync(0xffffffffu, m != 0xffffffffu);
}
DEVI void flag_add(unsigned* p) {
  asm volatile("fence.release.gpu;\nred.relaxed.gpu.global.add.u32 [%0], 1;" :: "l"(p) : "memory");
}
DEVI void fence_async_smem() { asm volatile("fence.proxy.async.shared::cta;" ::: "memory"); }
DEVI void bar_sync(int id, int n) { asm volatile("bar.sync %0, %1;" :: "r"(id), "r"(n) : "memory"); }
DEVI void cluster_arrive() { asm volatile("barrier.cluster.arrive.relaxed.aligned;" ::: "memory"); }
DEVI void cluster_wait() { asm volatile("barrier.cluster.wait.aligned;" ::: "memory"); }
DEVI void wg_fence() { asm volatile("wgmma.fence.sync.aligned;" ::: "memory"); }
DEVI void wg_commit() { asm volatile("wgmma.commit_group.sync.aligned;" ::: "memory"); }
template <int N> DEVI void wg_wait() { asm volatile("wgmma.wait_group.sync.aligned %0;" :: "n"(N) : "memory"); }
template <int N> DEVI void pin(uint32_t* r) {
#pragma unroll
  for (int i = 0; i < N; i++) asm volatile("" : "+r"(r[i]) :: "memory");
}
template <int N> DEVI void pin(float* r) {
#pragma unroll
  for (int i = 0; i < N; i++) asm volatile("" : "+f"(r[i]) :: "memory");
}

DEVI void sched_fence(int zero, int id) { asm volatile("{\n.reg .pred p;\nsetp.eq.b32 p, %0, %1;\nS_LOOP:\n@p st.volatile.shared.b32 [%0], %0;\n@p bra S_LOOP;\n}" :: "r"(zero), "r"(id + 1) : "memory"); }
DEVI void pin_range(float* r, int i0, int i1) {
#pragma unroll
  for (int i = i0; i < i1; i++) asm volatile("" : "+f"(r[i]) :: "memory");
}
DEVI void keep(uint32_t& x) { asm volatile("" : "+r"(x) :: "memory"); }
DEVI void keep(int& x) { asm volatile("" : "+r"(x) :: "memory"); }
template <class T> DEVI void keep(T*& x) { asm volatile("" : "+l"(x) :: "memory"); }

DEVI void tma2d(uint32_t dst, const CUtensorMap* m, int c0, int c1, uint32_t bar) {
  asm volatile("cp.async.bulk.tensor.2d.shared::cluster.global.mbarrier::complete_tx::bytes [%0], [%1, {%3, %4}], [%2];"
               :: "r"(dst), "l"(m), "r"(bar), "r"(c0), "r"(c1) : "memory");
}
DEVI void tma2d_mc(uint32_t dst, const CUtensorMap* m, int c0, int c1, uint32_t bar) {
  asm volatile("cp.async.bulk.tensor.2d.shared::cluster.global.mbarrier::complete_tx::bytes.multicast::cluster [%0], [%1, {%3, %4}], [%2], %5;"
               :: "r"(dst), "l"(m), "r"(bar), "r"(c0), "r"(c1), "h"((uint16_t)3) : "memory");
}
DEVI void tma3d(uint32_t dst, const CUtensorMap* m, int c0, int c1, int c2, uint32_t bar) {
  asm volatile("cp.async.bulk.tensor.3d.shared::cluster.global.mbarrier::complete_tx::bytes [%0], [%1, {%3, %4, %5}], [%2];"
               :: "r"(dst), "l"(m), "r"(bar), "r"(c0), "r"(c1), "r"(c2) : "memory");
}
DEVI void tma3d_mc(uint32_t dst, const CUtensorMap* m, int c0, int c1, int c2, uint32_t bar) {
  asm volatile("cp.async.bulk.tensor.3d.shared::cluster.global.mbarrier::complete_tx::bytes.multicast::cluster [%0], [%1, {%3, %4, %5}], [%2], %6;"
               :: "r"(dst), "l"(m), "r"(bar), "r"(c0), "r"(c1), "r"(c2), "h"((uint16_t)3) : "memory");
}
DEVI void tma2d_store(const CUtensorMap* m, uint32_t src, int c0, int c1) {
  asm volatile("cp.async.bulk.tensor.2d.global.shared::cta.bulk_group [%0, {%2, %3}], [%1];" :: "l"(m), "r"(src), "r"(c0), "r"(c1) : "memory");
}
DEVI void bulk_load(uint32_t dst, const void* src, uint32_t bytes, uint32_t bar) {
  asm volatile("cp.async.bulk.shared::cluster.global.mbarrier::complete_tx::bytes [%0], [%1], %2, [%3];" :: "r"(dst), "l"(src), "r"(bytes), "r"(bar) : "memory");
}
DEVI void bulk_store(void* dst, uint32_t src, uint32_t bytes) {
  asm volatile("cp.async.bulk.global.shared::cta.bulk_group [%0], [%1], %2;" :: "l"(dst), "r"(src), "r"(bytes) : "memory");
}
DEVI uint32_t peer_addr(uint32_t a, int rank) { uint32_t r; asm("mapa.shared::cluster.u32 %0, %1, %2;" : "=r"(r) : "r"(a), "r"(rank)); return r; }
DEVI void bulk_to_peer(uint32_t dst, uint32_t src, uint32_t bytes, uint32_t bar, int rank) {
  asm volatile("cp.async.bulk.shared::cluster.shared::cta.mbarrier::complete_tx::bytes [%0], [%1], %2, [%3];"
               :: "r"(peer_addr(dst, rank)), "r"(src), "r"(bytes), "r"(peer_addr(bar, rank)) : "memory");
}
DEVI void l2_prefetch(const void* p, uint32_t bytes) {
  asm volatile("cp.async.bulk.prefetch.L2.global [%0], %1;" :: "l"(p), "r"(bytes) : "memory");
}
DEVI void l2_prefetch2d(const CUtensorMap* m, int c0, int c1) {
  asm volatile("cp.async.bulk.prefetch.tensor.2d.L2.global [%0, {%1, %2}];" :: "l"(m), "r"(c0), "r"(c1) : "memory");
}
DEVI void l2_prefetch3d(const CUtensorMap* m, int c0, int c1, int c2) {
  asm volatile("cp.async.bulk.prefetch.tensor.3d.L2.global [%0, {%1, %2, %3}];" :: "l"(m), "r"(c0), "r"(c1), "r"(c2) : "memory");
}
DEVI uint32_t clock32() { uint32_t t; asm volatile("mov.u32 %0, %%clock;" : "=r"(t) :: "memory"); return t; }
DEVI void delay(uint32_t cycles) { const uint32_t t = clock32(); while (clock32() - t < cycles) { } }
DEVI void bulk_commit() { asm volatile("cp.async.bulk.commit_group;" ::: "memory"); }
DEVI void bulk_wait_all() { asm volatile("cp.async.bulk.wait_group 0;" ::: "memory"); }
DEVI void bulk_wait_read() { asm volatile("cp.async.bulk.wait_group.read 0;" ::: "memory"); }
DEVI void prefetch_map(const CUtensorMap* m) { asm volatile("prefetch.tensormap [%0];" :: "l"(m) : "memory"); }
DEVI void arrive_both(uint32_t bar, int lane, bool pred = true) {
  asm volatile("{\n.reg .pred p;\n.reg .b32 r;\nsetp.ne.b32 p, %2, 0;\nmapa.shared::cluster.u32 r, %0, %1;\n@p mbarrier.arrive.shared::cluster.b64 _, [r];\n}"
               :: "r"(bar), "r"(lane & 1), "r"((int)(pred && lane < 2)) : "memory");
}

DEVI uint64_t make_desc(uint32_t off, uint32_t lbo, uint32_t sbo, uint32_t mode) {
  const uint32_t lo = (off >> 4) + (SM_BASE >> 4) + ((lbo >> 4) << 16), hi = (sbo >> 4) | (mode << 30);
  return ((uint64_t)hi << 32) | lo;
}
DEVI uint32_t pack_bf16(float lo, float hi) { uint32_t r; asm("cvt.rn.bf16x2.f32 %0, %1, %2;" : "=r"(r) : "f"(hi), "f"(lo)); return r; }
DEVI uint32_t pack_f16(float lo, float hi) { uint32_t r; asm("cvt.rn.f16x2.f32 %0, %1, %2;" : "=r"(r) : "f"(hi), "f"(lo)); return r; }
DEVI void stsm4(uint32_t addr, uint32_t r0, uint32_t r1, uint32_t r2, uint32_t r3) {
  asm volatile("stmatrix.sync.aligned.m8n8.x4.shared.b16 [%0], {%1,%2,%3,%4};" :: "r"(addr), "r"(r0), "r"(r1), "r"(r2), "r"(r3) : "memory");
}
DEVI void stsm2(uint32_t addr, uint32_t r0, uint32_t r1) {
  asm volatile("stmatrix.sync.aligned.m8n8.x2.shared.b16 [%0], {%1,%2};" :: "r"(addr), "r"(r0), "r"(r1) : "memory");
}
DEVI void stsm4_t(uint32_t addr, uint32_t r0, uint32_t r1, uint32_t r2, uint32_t r3) {
  asm volatile("stmatrix.sync.aligned.m8n8.x4.trans.shared.b16 [%0], {%1,%2,%3,%4};" :: "r"(addr), "r"(r0), "r"(r1), "r"(r2), "r"(r3) : "memory");
}
DEVI void ldsm4(uint32_t* r, uint32_t addr) {
  asm volatile("ldmatrix.sync.aligned.m8n8.x4.shared.b16 {%0,%1,%2,%3}, [%4];" : "=r"(r[0]), "=r"(r[1]), "=r"(r[2]), "=r"(r[3]) : "r"(addr) : "memory");
}
DEVI void ldsm4_t(uint32_t* r, uint32_t addr) {
  asm volatile("ldmatrix.sync.aligned.m8n8.x4.trans.shared.b16 {%0,%1,%2,%3}, [%4];" : "=r"(r[0]), "=r"(r[1]), "=r"(r[2]), "=r"(r[3]) : "r"(addr) : "memory");
}
DEVI uint32_t lds32(uint32_t a) { uint32_t v; asm volatile("ld.shared.b32 %0, [%1];" : "=r"(v) : "r"(a) : "memory"); return v; }
DEVI uint4 lds128(uint32_t a) {
  uint4 v; asm volatile("ld.shared.v4.b32 {%0,%1,%2,%3}, [%4];" : "=r"(v.x), "=r"(v.y), "=r"(v.z), "=r"(v.w) : "r"(a) : "memory"); return v;
}
DEVI uint32_t bmul2(uint32_t a, uint32_t b) { uint32_t r; asm("mul.rn.bf16x2 %0, %1, %2;" : "=r"(r) : "r"(a), "r"(b)); return r; }
DEVI uint32_t bfma2(uint32_t a, uint32_t b, uint32_t c) { uint32_t r; asm("fma.rn.bf16x2 %0, %1, %2, %3;" : "=r"(r) : "r"(a), "r"(b), "r"(c)); return r; }
DEVI float bf_lo(uint32_t w) { return __uint_as_float(w << 16); }
DEVI float bf_hi(uint32_t w) { return __uint_as_float(w & 0xffff0000u); }
DEVI uint32_t elu1(float a0, float a1) {
  constexpr float L = 1.4426950408889634f;
  float e0, e1;
  asm("ex2.approx.ftz.f32 %0, %1;" : "=f"(e0) : "f"(-fabsf(fmaf(a0, L, -L))));
  asm("ex2.approx.ftz.f32 %0, %1;" : "=f"(e1) : "f"(-fabsf(fmaf(a1, L, -L))));
  return pack_bf16(fmaxf(e0, a0), fmaxf(e1, a1));
}
DEVI float rcp(float x) { float r; asm("rcp.approx.ftz.f32 %0, %1;" : "=f"(r) : "f"(x)); return r; }
DEVI uint32_t add_eps(uint32_t x) { uint32_t r; asm("add.rn.bf16x2 %0, %1, %2;" : "=r"(r) : "r"(x), "r"(0x35863586u)); return r; }

#define FIN 0
DEVI uint32_t hmul(uint32_t a, uint32_t b) { uint32_t r; asm("mul.rn.f16x2 %0, %1, %2;" : "=r"(r) : "r"(a), "r"(b)); return r; }
DEVI uint32_t hfma(uint32_t a, uint32_t b, uint32_t c) { uint32_t r; asm("fma.rn.f16x2 %0, %1, %2, %3;" : "=r"(r) : "r"(a), "r"(b), "r"(c)); return r; }
DEVI uint32_t hneg(uint32_t a) { uint32_t r; asm("neg.f16x2 %0, %1;" : "=r"(r) : "r"(a)); return r; }
DEVI uint32_t hadd(uint32_t a, uint32_t b) { uint32_t r; asm("add.rn.f16x2 %0, %1, %2;" : "=r"(r) : "r"(a), "r"(b)); return r; }
DEVI uint32_t hsub(uint32_t a, uint32_t b) { uint32_t r; asm("sub.rn.f16x2 %0, %1, %2;" : "=r"(r) : "r"(a), "r"(b)); return r; }
struct Cx { uint32_t re, im; };
DEVI Cx cmul(Cx a, Cx b) { return {hfma(a.re, b.re, hneg(hmul(a.im, b.im))), hfma(a.re, b.im, hmul(a.im, b.re))}; }
DEVI Cx cfma(Cx a, Cx b, Cx c) { return {hfma(a.re, b.re, hfma(hneg(a.im), b.im, c.re)), hfma(a.re, b.im, hfma(a.im, b.re, c.im))}; }
DEVI Cx rot(Cx a, Cx t) {
  const uint32_t x = hfma(hneg(t.re), a.im, a.re), y = hfma(t.im, x, a.im);
  return {hfma(hneg(t.re), y, x), y};
}
struct Fft {
  uint32_t fa[8];
  Cx tw[2];
  uint32_t vld;
  uint64_t dF2a, dF2b;
  uint32_t vst;
  DEVI void stage1(uint32_t* d1, uint32_t slot) const {
    wg_fence();
    fft1_init(d1, fa[0], fa[1], fa[2], fa[3], make_desc(slot, 4096, 1024, 1));
    fft1_acc(d1, fa[4], fa[5], fa[6], fa[7], make_desc(slot + 2048, 4096, 1024, 1));
    wg_commit();
  }
  DEVI void stage2(uint32_t* d, const Cx* t) const {
    wg_fence();
    fft2_init(d, t[0].re, t[1].re, t[2].re, t[3].re, dF2a);
    fft2_acc(d, t[0].im, t[1].im, t[2].im, t[3].im, dF2b);
    wg_commit();
  }
  template <int PR> DEVI void fwd(const uint32_t* d1, uint32_t* d2) const {
    Cx t[4];
#pragma unroll
    for (int e = 0; e < 4; e++) {
      const int j = 8 * (PR & 1) + 4 * (e >> 1) + 2 * (PR >> 1) + (e & 1);
      t[e] = rot({d1[2 * j], d1[2 * j + 1]}, tw[e >> 1]);
    }
    stage2(d2 + 8 * PR, t);
  }
  static DEVI Cx U(const uint32_t* d2, int p, int hi) { return {d2[16 * (p >> 1) + 2 * hi + (p & 1)], d2[16 * (p >> 1) + 4 + 2 * hi + (p & 1)]}; }
  static DEVI Cx H(const uint32_t* d2, int p, int hi) { return U(d2 + 8, p, hi); }
  DEVI void prod01(const uint32_t* d2, Cx* p1, uint32_t* d3) const {
    Cx z[4];
#pragma unroll
    for (int hi = 0; hi < 2; hi++) {
      const Cx p0 = cmul(H(d2, 0, hi), U(d2, 0, hi));
      p1[hi] = cfma(H(d2, 1, hi), U(d2, 0, hi), cmul(H(d2, 0, hi), U(d2, 1, hi)));
      z[2 * hi] = {p0.im, p0.re};
      z[2 * hi + 1] = {hsub(p1[hi].im, p0.re), hadd(p1[hi].re, p0.im)};
    }
    stage2(d3, z);
  }
  DEVI void prod23(const uint32_t* d2, const Cx* p1, uint32_t* d3) const {
    Cx z[4];
#pragma unroll
    for (int hi = 0; hi < 2; hi++) {
      const Cx p2 = cfma(H(d2, 2, hi), U(d2, 0, hi), cfma(H(d2, 0, hi), U(d2, 2, hi), cmul(H(d2, 1, hi), U(d2, 1, hi))));
      const Cx z3 = cfma(H(d2, 3, hi), U(d2, 0, hi), cfma(H(d2, 2, hi), U(d2, 1, hi),
                    cfma(H(d2, 1, hi), U(d2, 2, hi), cfma(H(d2, 0, hi), U(d2, 3, hi), {p2.im, hneg(p2.re)}))));
      z[2 * hi] = {hsub(p2.im, p1[hi].re), hadd(p2.re, p1[hi].im)};
      z[2 * hi + 1] = {z3.im, z3.re};
    }
    stage2(d3 + 8, z);
  }
  template <int PB> DEVI void inv(const uint32_t* d3, uint32_t slot) const {
    Cx v[4];
#pragma unroll
    for (int e = 0; e < 4; e++) {
      const int r = 8 * PB + 2 * (e & 1) + (e >> 1);
      v[e] = rot({d3[r], d3[r + 4]}, tw[e & 1]);
    }
    stsm4(slot + (vst ^ (PB * 64)), v[0].im, v[1].im, v[2].im, v[3].im);
    stsm4(slot + 1024 + (vst ^ (PB * 64)), v[0].re, v[1].re, v[2].re, v[3].re);
  }
  DEVI void last(float* dy, uint32_t slot, int wg, bool fenced = false) const {
    if (!fenced) fence_async_smem();
    bar_sync(2 + wg, 128);
    wg_fence();
    fft3_init(dy, make_desc(slot, 4096, 1024, 1), make_desc(SM_F1, 128, 1024, 0));
#pragma unroll
    for (int ks = 1; ks < 4; ks++) fft3_acc(dy, make_desc(slot + ks * 2048, 4096, 1024, 1), make_desc(SM_F1 + ks * 256, 128, 1024, 0));
    wg_commit();
  }
  static DEVI void store_y(const float* dy, uint32_t a) {
    stsm4_t(a, pack_bf16(dy[0], dy[1]), pack_bf16(dy[2], dy[3]), pack_bf16(dy[4], dy[5]), pack_bf16(dy[6], dy[7]));
    stsm4_t(a + 512, pack_bf16(dy[8], dy[9]), pack_bf16(dy[10], dy[11]), pack_bf16(dy[12], dy[13]), pack_bf16(dy[14], dy[15]));
  }
};
DEVI uint32_t normalize(uint32_t* x, uint32_t dst) {
  uint32_t m = x[0];
#pragma unroll
  for (int i = 1; i < 32; i++) asm("max.xorsign.abs.bf16x2 %0, %0, %1;" : "+r"(m) : "r"(x[i]));
  const uint32_t e = min(__reduce_max_sync(0xffffffffu, max(m & 0x7fffu, (m >> 16) & 0x7fffu)) >> 7, 252u);
  if (e > 140) {
#pragma unroll
    for (int i = 0; i < 32; i++) x[i] = bmul2(x[i], 15u * 0x00800080u);
  }
  const uint32_t sc = (e > 140 ? 253u - e : 141u - e) * 0x00800080u;
#pragma unroll
  for (int i = 0; i < 8; i++) {
    uint32_t y[4];
#pragma unroll
    for (int n = 0; n < 4; n++) {
      const uint32_t w = bmul2(x[4 * i + n], sc);
      y[n] = (w & 0x7fff7fffu) * 7u + w;
    }
    stsm4((dst ^ ((i >> 1) << 4)) + (i & 1) * 2048, y[0], y[1], y[2], y[3]);
  }
  return e;
}
#define RFENCE 1
#define EFENCE 0
#define UDESC 1
#define QF 0
#define KF 1
#define LATE 0
#define PPACE2 PPACE
#define PPACE3 (LATE ? 1 : PPACE)
#define C1DELAY 1
#define SAMP 128
#define PD1 600
#define PD2 500
#define TAIL 3
#define DBG 0
#define XPF 3
#define PSTART 5
#define HSTART 3
#define PF0 28
#define PPACE 300
#define FDELAY 150
#define PH0 2
#define QA 4
#define QB 2
#define QC 4
#define S1POS 1

__global__ void __cluster_dims__(2, 1, 1) __launch_bounds__(kThreads, 1)
fused_kernel(const __grid_constant__ Params P) {
  extern __shared__ __align__(1024) uint8_t smem[];
  if (threadIdx.x == 0) { prefetch_map(&P.x); prefetch_map(&P.w); prefetch_map(&P.wk); prefetch_map(blockIdx.x & 1 ? &P.v : &P.k); }
  const uint32_t sb = __shfl_sync(0xffffffffu, (uint32_t)__cvta_generic_to_shared(smem), 0);
  const int tid = threadIdx.x, lane = tid & 31;
  const int warp = __shfl_sync(0xffffffffu, tid >> 5, 0);
  const int bc = blockIdx.x >> 1, late = ((bc - 36) * 37) >> 8;
  const int rp = bc < 4 ? 0 : bc < 36 ? (bc - 4) & 7 : bc - 35 - 7 * late, j = bc < 4 ? 4 + bc : bc < 36 ? (bc - 4) >> 3 : 4 + late;
  const int rho = blockIdx.x & 1, cl = 8 * rp + j, cta = 2 * cl + rho, r = rp * 2 + rho;
  auto bar = [&](int i) { return sb + SM_BAR + 8u * i; };
  TSTAMP(tid == 0, 0); GSTAMP(tid == 0, 30);
  auto load_stage = [&](int it) {
    const uint32_t st = sb + (it & 3) * QKV_STAGE, fb = bar(B_QKV_FULL + (it & 3));
    mbar_expect(fb, QKV_STAGE);
    tma2d_mc(st + 24576 + rho * 4096, &P.wk, 1024 + 128 * j + 64 * rho, 32 * it, fb);
    tma3d_mc(st + 8192 + rho * 8192, &P.w, 0, 32 * it, 32 * rho + 2 * j, fb);
    tma2d(st, &P.x, 32 * it, 128 * r, fb);
  };
  if (warp == 8 && elect()) {
    mbar_init(bar(B_QKV_FULL), 1);
    mbar_expect(bar(B_QKV_FULL), QKV_STAGE);
    tma2d(sb, &P.x, 0, 128 * r, bar(B_QKV_FULL));
    tma3d(sb + 24576, &P.w, 0, 0, 16 + 2 * j, bar(B_QKV_FULL));
    tma3d(sb + 8192, &P.w, 0, 0, 2 * j, bar(B_QKV_FULL));
    tma3d(sb + 16384, &P.w, 0, 0, 32 + 2 * j, bar(B_QKV_FULL));
    for (int i = 1; i < 5; i++) mbar_init(bar(B_QKV_FULL + i), 1);
    asm volatile("fence.mbarrier_init.release.cluster;" ::: "memory");
  }
  LOOPSTAMP(3, tid == 256, 13);
  __syncwarp();
  cluster_arrive();

  if (warp < 8) {
    cluster_wait();
    cluster_arrive();
    asm volatile("setmaxnreg.inc.sync.aligned.u32 224;");
    const int wg = warp >> 2, wq = warp & 3;
    const int never = __shfl_sync(0xffffffffu, P.zero, 0);
    const uint32_t orow = wq * 2048 + (lane & 15) * 128, ox = ((lane >> 4) ^ (lane & 7)) << 4;
    float aq[64];
    Fft F;
    uint32_t a1[32];
    {
      float ak[64], avq[128];
      auto k_step = [&](uint32_t st, int kk, int acc) {
        mma_tn(ak, make_desc(st + 24576 + wg * 4096 + kk * 2048, 4096, 1024, 1), make_desc(st + kk * 32, 16, 512, 2), acc);
      };
      auto vq_step = [&](uint32_t st, int kk, int acc) {
        mma_nt256(avq, make_desc(st + wg * 4096 + kk * 32, 16, 512, 2), make_desc(st + 8192 + kk * 2048, 4096, 1024, 1), acc);
      };
#pragma unroll
      for (int i = 0; i < 64; i++) { ak[i] = 1.f; avq[i] = 1.f; avq[64 + i] = 0.f; }
      pin<64>(ak); pin<128>(avq);
      cluster_wait();
      LOOPSTAMP(3, tid == 0, 17);
#pragma unroll 1
      for (int it = 0; it < 29; ++it) {
        mbar_wait(bar(B_QKV_FULL + (it & 3)), (it >> 2) & 1);
        TSTAMP(tid == 0 && it == 0, 1); LOOPSTAMP(1, tid == 0 && it < 27, 1 + it); LOOPSTAMP(3, tid == 0 && it < 12, 1 + it);
        const uint32_t st = (it & 3) * QKV_STAGE;
        wg_fence();
        k_step(st, 0, 1);
        wg_commit();
        wg_wait<1>();
        arrive_both(bar(B_QKV_EMPTY + ((it - 1) & 3)), lane, it > 0);
        wg_fence();
        vq_step(st, 0, 1);
        k_step(st, 1, 1);
        vq_step(st, 1, 1);
        wg_commit();
      }
#pragma unroll 1
      for (int s = 1; s < 4; ++s) {
        mbar_wait(bar(B_QKV_FULL + s), 1);
        wg_fence();
        k_step(s * QKV_STAGE, 0, 1);
        k_step(s * QKV_STAGE, 1, 1);
        wg_commit();
      }
      uint32_t pk[32];
      auto phi_k = [&](int i0, int i1) {
#pragma unroll
        for (int i = i0; i < i1; i++) { pk[i] = elu1(ak[2 * i], ak[2 * i + 1]); asm volatile("" : "+r"(pk[i]) :: "memory"); }
        if (KF) sched_fence(never, i0);
      };
#pragma unroll
      for (int n = 0; n < 6; n++) {
        wg_fence();
        vq_step((1 + (n >> 1)) * QKV_STAGE, n & 1, 1);
        wg_commit();
        if (n == 0) {
          wg_wait<1>();
          pin<64>(ak);
          TSTAMP(tid == 0, 2);
          bar_sync(1, 256);
        }
        phi_k(n ? PH0 + (32 - PH0) * (n - 1) / 5 : 0, PH0 + (32 - PH0) * n / 5);
      }
      mbar_wait(bar(B_SIG_READY), 0);
      ldsm4_t(F.fa, sb + SM_F1 + (lane >> 4) * 1024 + wq * 256 + (lane & 15) * 16);
      ldsm4_t(F.fa + 4, sb + SM_F1 + 2048 + (lane >> 4) * 1024 + wq * 256 + (lane & 15) * 16);
      const uint4 tw = lds128(sb + SM_TW + (tid & 127) * 16);
      F.tw[0] = {tw.x, tw.y}; F.tw[1] = {tw.z, tw.w};
      F.vld = sb + ((lane >> 4) * 8 + (lane & 7)) * 128 + (((2 * wq + ((lane >> 3) & 1)) ^ (lane & 7)) << 4);
      F.dF2a = make_desc(SM_F2, 128, 512, 0) + (UDESC ? (uint64_t)never * 0x100000001ull : 0); F.dF2b = F.dF2a + 16;
      F.vst = sb + (16 * wq + (lane & 7)) * 128 + (((lane >> 3) ^ (lane & 7)) << 4);
      wg_wait<0>();
      pin<128>(avq);
      if (S1POS == 0) F.stage1(a1, SM_SIG + wg * 8192);
      arrive_both(bar(B_QKV_DONE), lane);
      TSTAMP(tid == 0, 3);
#pragma unroll
      for (int t = 0; t < 8; t++) {
        const float* b = avq + 64 + 8 * t;
        stsm4(sb + (t >> 2) * SLOT + wg * 8192 + orow + (ox ^ ((t & 3) << 5)), pack_bf16(b[0], b[1]), pack_bf16(b[2], b[3]), pack_bf16(b[4], b[5]), pack_bf16(b[6], b[7]));
      }
#pragma unroll
      for (int i = 0; i < 64; i++) aq[i] = avq[i];
      fence_async_smem();
      bar_sync(1, 256);
      float dkv[36];
#pragma unroll
      for (int ks = 0; ks < 8; ks++) {
        const uint32_t va = wg * SLOT + ks * 2048;
        const uint64_t db = make_desc(va, SM_ONES - va, 1024, 1);
        uint32_t a[4];
        pin<4>(pk + 4 * ks);
#pragma unroll
        for (int i = 0; i < 4; i++) a[i] = add_eps(pk[4 * ks + i]);
        wg_fence();
        if (ks == 0) mma_kv_init(dkv, a[0], a[1], a[2], a[3], db);
        else mma_kv_acc(dkv, a[0], a[1], a[2], a[3], db);
      }
      wg_commit();
      uint8_t* box = g_xch[warp * 16 + j] + 2 * SLOT + r * KV_SLICE + lane * 16;
      uint8_t* zbox = box + (lane & 1) * 8 * XCH_BYTES + 512 + (lane & 28) - lane * 16;
      keep(box); keep(zbox);
      if (S1POS == 1) F.stage1(a1, SM_SIG + wg * 8192);
      mbar_wait(bar(B_ZEROED), 0);
      wg_wait<S1POS == 1>();
      pin<36>(dkv);
      if (S1POS == 2) F.stage1(a1, SM_SIG + wg * 8192);
      TSTAMP(tid == 0, 4);
      auto put = [&](const float* d) {
#pragma unroll
        for (int m = 0; m < 2; m++)
          asm volatile("st.relaxed.gpu.global.v4.b32 [%0], {%1,%2,%3,%4};" :: "l"(box + m * 8 * XCH_BYTES), "r"(pack_bf16(d[2 * m], d[2 * m + 1])),
                       "r"(pack_bf16(d[2 * m + 4], d[2 * m + 5])), "r"(pack_bf16(d[2 * m + 8], d[2 * m + 9])), "r"(pack_bf16(d[2 * m + 12], d[2 * m + 13])) : "memory");
      };
      if (wq < 2) put(dkv); else put(dkv + 16);
      asm volatile("{\n.reg .pred p;\nsetp.eq.b32 p, %2, 0;\n@p st.relaxed.gpu.global.b32 [%0], %1;\n}" :: "l"(zbox), "f"(lane & 1 ? dkv[34] : dkv[32]), "r"(lane & 2) : "memory");
      __syncwarp();
      mbar_arrive_if(bar(B_KVP), lane == 0);
      TSTAMP(tid == 0, 5);
    }

    uint32_t pq[32];
    auto phi_q = [&](int i0, int i1) {
      pin_range(aq, 2 * i0, 2 * i1);
#pragma unroll
      for (int i = i0; i < i1; i++) { pq[i] = add_eps(elu1(aq[2 * i], aq[2 * i + 1])); keep(pq[i]); }
      if (QF && i1 > i0) sched_fence(never, 40 + i0);
    };
    uint32_t a2[32];
    float by[16];
    auto conv_pair = [&](uint32_t sa, uint32_t ya, uint32_t first) {
      const uint32_t sc = sa + SLOT;
      uint32_t b1[32], b2[32], a3[16], b3[16];
      float ay[16];
      Cx pa[2], pb[2];
      sched_fence(never, 80);
      F.stage1(b1, sc);
      F.prod01(a2, pa, a3);
      F.prod23(a2, pa, a3);
      wg_wait<1>(); pin<32>(b1); pin<8>(a3);
      F.inv<0>(a3, sa);
      F.fwd<0>(b1, b2);
      wg_wait<1>(); pin<8>(a3 + 8);
      F.inv<1>(a3, sa);
      F.fwd<1>(b1, b2);
      if (EFENCE == 1 && !FIN) fence_async_smem();
      F.fwd<2>(b1, b2);
      if (EFENCE == 2 && !FIN) fence_async_smem();
      F.fwd<3>(b1, b2);
      F.last(ay, sa, wg, EFENCE);
      wg_wait<3>(); pin<16>(b2);
      F.prod01(b2, pb, b3);
      wg_wait<2>(); pin<16>(b2 + 16);
      F.prod23(b2, pb, b3);
      mbar_wait(bar(B_RDY1), first);
      wg_wait<1>(); pin<8>(b3); pin<16>(ay);
      F.inv<0>(b3, sc);
      Fft::store_y(ay, ya);
      wg_wait<0>(); pin<8>(b3 + 8);
      F.inv<1>(b3, sc);
    };
    const bool ylocal = (wq >> 1) == rho;
    const uint32_t yoff = sb + (wq & 1) * 1024 + ((lane ^ wg ^ (2 * rho)) << 4);
    const uint32_t ya0 = yoff + (ylocal ? SM_Y0 + wg * 8192 : SM_YT + wg * 4096), ya1 = (yoff ^ 64) + (ylocal ? SM_SIG + wg * 8192 : SM_YT + wg * 4096);
    auto pair_done = [&](uint32_t ya, int seg) {
      pin<16>(by);
      Fft::store_y(by, (ya ^ 32) + 2048);
      if (!RFENCE) fence_async_smem();
      __syncwarp();
      mbar_arrive_if(bar(B_SEG + 2 * seg + wg), lane == 0);
    };
    const uint32_t s0 = SM_SIG + wg * 8192, s1 = s0 + 2 * SLOT;
    phi_q(0, QA);
    wg_wait<0>(); pin<32>(a1);
    bar_sync(2 + wg, 128);
    F.fwd<0>(a1, a2); phi_q(QA, QA + QB);
    F.fwd<1>(a1, a2); phi_q(QA + QB, QA + 2 * QB);
    F.fwd<2>(a1, a2); phi_q(QA + 2 * QB, QA + 3 * QB);
    F.fwd<3>(a1, a2);
    phi_q(QA + 3 * QB, QA + 3 * QB + QC);
    wg_wait<0>(); pin<32>(a2);
#pragma unroll 1
    for (uint32_t sa = s0;; sa += 2 * SLOT + P.zero) {
    conv_pair(sa, sa == s1 ? ya1 : ya0, sa != s1);
    if (sa == s1) break;
    F.last(by, s0 + SLOT, wg);
    F.stage1(a1, s1);
    phi_q(QA + 3 * QB + QC, 32);
    wg_wait<1>();
    pair_done(ya0, 0);
    TSTAMP(tid == 0, 7); TSTAMP(tid == 128, 10);
    {
      float dn[4][20];
      wg_wait<0>(); pin<32>(a1);
      bar_sync(2 + wg, 128);
      F.fwd<0>(a1, a2); F.fwd<1>(a1, a2); F.fwd<2>(a1, a2); F.fwd<3>(a1, a2);
      mbar_wait(bar(B_KV_READY), 0);
      TSTAMP(tid == 0, 8);
      auto head_mma = [&](int h) {
        wg_fence();
        const uint64_t db = make_desc(SM_KV + h * 2560, 640, 128, 0);
        const uint32_t* a = pq + 8 * h;
        mma_o_init(dn[h], a[0], a[1], a[2], a[3], db);
        mma_o_acc(dn[h], a[4], a[5], a[6], a[7], db + (1280 >> 4));
        wg_commit();
      };
      auto head_store = [&](int h) {
        pin<20>(dn[h]);
        const float i0 = rcp(dn[h][16] + 1e-6f), i1 = rcp(dn[h][18] + 1e-6f);
        const uint32_t p0 = pack_bf16(i0, i0), p1 = pack_bf16(i1, i1);
#pragma unroll
        for (int hf = 0; hf < 2; hf++) {
          const float* a = dn[h] + 8 * hf;
          const uint32_t dst = sb + (h >> 1) * SLOT + wg * 8192 + orow + (ox ^ (((h & 1) * 2 + hf) << 5));
          stsm4(dst, bmul2(pack_bf16(a[0], a[1]), p0), bmul2(pack_bf16(a[2], a[3]), p1), bmul2(pack_bf16(a[4], a[5]), p0), bmul2(pack_bf16(a[6], a[7]), p1));
        }
        if (h & 1) { if (!RFENCE) fence_async_smem(); __syncwarp(); mbar_arrive_if(bar(B_O_WRITTEN + (h >> 1)), lane == 0); }
      };
      head_mma(0); head_mma(1);
      wg_wait<1>(); head_store(0);
      head_mma(2);
      wg_wait<1>(); head_store(1);
      head_mma(3);
      wg_wait<1>(); head_store(2);
      wg_wait<0>(); head_store(3);
      TSTAMP(tid == 0, 9);
      pin<32>(a2);
    }
    }
    if (FIN && RFENCE) mbar_wait(bar(B_OT_FREE), 0);
    F.last(by, s1 + SLOT, wg);

    float acc[64];
    auto stage_mma = [&](int s, int kk, int accumulate) {
      mma_nt(acc, make_desc(((A_SLOTS >> (4 * s)) & 15) * SLOT + wg * 8192 + kk * 32, 16, 1024, 1),
             make_desc(((B_SLOTS >> (4 * s)) & 15) * SLOT + kk * 2048, 8192, 1024, 1), accumulate);
    };
    {
      mbar_wait(bar(B_OUT_FULL), 0);
      wg_fence();
#pragma unroll
      for (int kk = 0; kk < 2; kk++) stage_mma(0, kk, kk);
      wg_commit();
      wg_wait<1>();
      arrive_both(bar(B_CONV_DONE), lane);
      cluster_arrive();
      wg_fence();
#pragma unroll
      for (int kk = 2; kk < 4; kk++) stage_mma(0, kk, 1);
      wg_commit();
      pair_done(ya1, 1);
      TSTAMP(tid == 0, 11); TSTAMP(tid == 128, 12);
      int s = 1, sprev = 0;
      uint32_t ph = 0;
#pragma unroll 1
      for (int ks = 1; ks < 12; ++ks) {
        mbar_wait(bar(B_OUT_FULL + s), ph);
        LOOPSTAMP(2, tid == 0, 1 + ks);
        TSTAMP(tid == 0 && ks == 2, 13); TSTAMP(tid == 0 && ks == 9, 14);
        wg_fence();
        stage_mma(s, 0, 1);
        wg_commit();
        wg_wait<1>();
        arrive_both(bar(B_OUT_EMPTY + sprev), lane);
        wg_fence();
#pragma unroll
        for (int kk = 1; kk < 4; kk++) stage_mma(s, kk, 1);
        wg_commit();
        sprev = s;
        if (++s == 5) { s = 0; ph ^= 1; }
      }
#pragma unroll 1
      for (int ks = 12; ks < 16; ++ks) {
        asm volatile("{\n.reg .pred p;\nsetp.ne.b32 p, %0, 0;\n@p bar.sync 1, 256;\n}" :: "r"((int)(ks == 16 - TAIL && wg)) : "memory");
        mbar_wait(bar(B_OUT_FULL + s), ks == 15);
        wg_fence();
#pragma unroll
        for (int kk = 0; kk < 4; kk++) stage_mma(s, kk, 1);
        wg_commit();
        if (++s == 5) s = 0;
      }
    }
    asm volatile("{\n.reg .pred p;\nsetp.eq.b32 p, %0, 0;\n@p bar.arrive 1, 256;\n}" :: "r"(wg) : "memory");
    wg_wait<0>(); pin<64>(acc);
    TSTAMP(tid == 0, 15); TSTAMP(tid == 128, 16);
#pragma unroll
    for (int hf = 0; hf < 2; hf++) {
      const uint32_t dst = sb + (1 + 8 * hf) * SLOT + wg * 8192;
#pragma unroll
      for (int t = 0; t < 4; t++) {
        const float* a = acc + 32 * hf + 8 * t;
        stsm4(dst + orow + (ox ^ (t << 5)), pack_bf16(a[0], a[1]), pack_bf16(a[2], a[3]), pack_bf16(a[4], a[5]), pack_bf16(a[6], a[7]));
      }
      fence_async_smem();
      __syncwarp();
      if ((!(DBG & 4) || wg) && elect()) { tma2d_store(&P.outa, dst + wq * 2048, 128 * j + 64 * hf, 128 * r + 16 * warp); bulk_commit(); }
    }
    const bool stale = __any_sync(0xffffffffu, acc[0] != acc[0] || acc[2] != acc[2] || (DBG & 256));
    if (elect()) bulk_wait_read();
    TSTAMP(tid == 128, 17);
    __syncwarp();
    cluster_wait();
    TSTAMP(tid == 128, 28); GSTAMP(tid == 128, 31);
    if (stale) {
      __threadfence();
#pragma unroll
      for (int i = 0; i < 64; i++) acc[i] = 0.f;
      const int row = warp * 16 + (lane >> 2);
#pragma unroll 1
      for (int k = 0; k < 1024; k += 2) {
        const uint8_t* src = g_xch[r * 8 + (k >> 7)] + ((k >> 6) & 1) * SLOT + row * 128 + ((((k >> 3) ^ row) & 7) << 4) + (k & 7) * 2;
        uint32_t a[2];
        int n = 0;
        do { a[0] = ld_relaxed(src); a[1] = ld_relaxed(src + 1024); } while (!all_arrived<2>(a) && ++n < kSpinLimit);
#pragma unroll 1
        for (int e = 0; e < 2; e++) {
          const float a0 = e ? bf_hi(a[0]) : bf_lo(a[0]), a1 = e ? bf_hi(a[1]) : bf_lo(a[1]);
          const uint32_t* wrow = reinterpret_cast<const uint32_t*>(P.wo_ptr + (k + e) * 1024 + 128 * j) + (lane & 3);
#pragma unroll
          for (int i = 0; i < 16; i++) {
            const uint32_t w = __ldg(wrow + 4 * i);
            acc[4 * i] += a0 * bf_lo(w); acc[4 * i + 1] += a0 * bf_hi(w);
            acc[4 * i + 2] += a1 * bf_lo(w); acc[4 * i + 3] += a1 * bf_hi(w);
          }
        }
      }
      uint32_t* op = reinterpret_cast<uint32_t*>(P.out_ptr + (128 * r + row) * 2048 + 128 * j) + (lane & 3);
#pragma unroll
      for (int i = 0; i < 32; i++) op[(i & 1) * 8192 + (i >> 1) * 4] = pack_bf16(acc[2 * i], acc[2 * i + 1]);
    }
  } else {
    asm volatile("setmaxnreg.dec.sync.aligned.u32 56;");
    if (warp == 8) {
      cluster_wait();
      cluster_arrive();
      LOOPSTAMP(3, tid == 256, 15);
#pragma unroll 1
      for (int it = 1; it < 4; it++) if (elect()) load_stage(it);
      LOOPSTAMP(3, tid == 256, 16);
      __syncwarp();
      cluster_wait();
    } else {
      if (elect()) {
#pragma unroll 1
        for (int g = warp - 9; g < 8; g += 3)
          for (int i = 0; i < 8; i++) mbar_init(bar(8 * g + i), 1u << ((BAR_LOG2 >> (4 * g)) & 7));
        if (warp == 11) for (int i = 0; i < 6; i++) mbar_expect(bar(B_H_FULL + i), i < 2 ? 12288 : i < 5 ? 8192 : 16);
        asm volatile("fence.mbarrier_init.release.cluster;" ::: "memory");
      }
      LOOPSTAMP(3, tid == 288, 14);
      __syncwarp();
      cluster_wait();
      cluster_arrive();
#pragma unroll
      for (int i = 0; i < 3; i++) asm volatile("st.shared.v4.b32 [%0], {%1,%1,%1,%1};" :: "r"(sb + SM_F1 + i * 1536 + (tid - 288) * 16), "r"(0xffffffffu) : "memory");
      fence_async_smem();
      asm volatile("bar.arrive 5, 128;" ::: "memory");
      if ((sb & 0xffffff) != SM_BASE) __trap();
      cluster_wait();
    }
    auto chunk = [&](int ks) { const int c = ks >= 9, t = ks - 2 - 7 * c; return ks < 2 ? 2 * j + ks : 2 * (t + (t >= j)) + c; };
    auto load_q = [&](int n) {
      mbar_expect(bar(B_Q_FULL + (n & 3)), 4096);
      tma2d(sb + SM_Q + (n & 3) * 4096, &P.q, cl * 16, rho * 1024 + n * 128, bar(B_Q_FULL + (n & 3)));
    };
    auto load_wo = [&](uint32_t dst, int c, uint32_t bytes, uint32_t fb) {
      mbar_expect(fb, bytes);
      tma2d_mc(dst + rho * 8192, &P.wo, 128 * j + 64 * rho, c * 64, fb);
    };
    uint8_t* const xch = g_xch[r * 8 + j];
    if (warp == 8) {
      int ck = 0, cw = 0, cph = 1;
      const CUtensorMap* kvmap = rho ? &P.v : &P.k;
#pragma unroll 1
      for (int it = 4 - XPF; it < 32 || (ck < 20 && it < kSpinLimit); ++it) {
        if (it >= 4 && it < 32) {
          mbar_wait(bar(B_QKV_EMPTY + (it & 3)), ((it >> 2) - 1) & 1);
          if (elect()) load_stage(it);
          LOOPSTAMP(3, lane == 0 && it < 12, 15 + it);
        }
        if (it < 32 - XPF) {
          if (((it + XPF) & 7) == rp && elect()) {
            l2_prefetch2d(&P.wk, 1024 + 128 * j + 64 * rho, 32 * (it + XPF));
            l2_prefetch3d(&P.w, 0, 32 * (it + XPF), 32 * rho + 2 * j);
          }
          if (((it + XPF) & 7) == j && elect()) l2_prefetch2d(&P.x, 32 * (it + XPF), 128 * r);
        }
        const int n = it - HSTART;
        if (n >= 0 && n < 8) {
          if (elect()) bulk_load(sb + SM_SIG + n * 8192 + 4096, P.ssm_k + (size_t)(cta * 8 + n) * 2048, 4096, bar(B_H_FULL + (n >= 3) + (n >= 6)));
        } else if (n >= 8 && n < 19) {
          if (n == 8) bar_sync(5, 128);
          if (elect()) bulk_store(xch + (n - 8) * 4096, sb + SM_F1, 4096);
        } else if (it >= PF0 && it < PF0 + 4) {
          if (elect()) l2_prefetch(it < PF0 + 2 ? P.wo_ptr + cta * 8192 + (it - PF0) * 4096 : P.q_ptr + (512 + (it - PF0 - 2) * 1024 + cta * 4) * 1024, 8192);
        }
        if (ck < 16 && it >= PSTART && __all_sync(0xffffffffu, mbar_test(bar(B_PREP_EMPTY + cw), cph))) {
          if (elect()) {
            mbar_expect(bar(B_PREP_FULL + cw), 8704);
            tma3d_mc(sb + SM_STG + cw * 8704 + rho * 4608, kvmap, cl * 16, ck * 8 - 1 + rho, 0, bar(B_PREP_FULL + cw));
          }
          ++ck;
          if (++cw == 3) { cw = 0; cph ^= 1; }
        } else if (ck >= 16 && ck < 20 && __all_sync(0xffffffffu, mbar_test(bar(B_STG_FREE), 0))) {
          if (elect()) load_q(ck - 16);
          ++ck;
        }
      }
      if (elect()) {
        bulk_commit();
        bulk_wait_read();
        mbar_expect(bar(B_SIG_READY), 10240);
        bulk_load(sb + SM_TW, g_tables, 10240, bar(B_SIG_READY));
        flag_add(&g_ready);
        prefetch_map(&P.wo); prefetch_map(&P.outa); prefetch_map(&P.q);
        const unsigned epoch = ld_relaxed(&g_epoch[cta]) + 1;
        g_epoch[cta] = epoch;
        flag_wait(&g_ready, kCtas * epoch);
        mbar_arrive(bar(B_ZEROED));
      }
      __syncwarp();
      mbar_wait(bar(B_QKV_DONE), 0);
#pragma unroll 1
      for (int ks = 0; ks < 4; ++ks) if (elect()) load_wo(sb + (4 + ks) * SLOT, chunk(ks), ks < 2 ? SLOT : 2 * SLOT, bar(B_OUT_FULL + ks));
    } else {
      const int at = tid - 288, aw = warp - 9, ch0 = cta * 8;
      {
        const uint32_t stg = sb + SM_STG + aw * 8704, pf = bar(B_PREP_FULL + aw), pe = bar(B_PREP_EMPTY + aw);
        const uint4 wv = __ldg(reinterpret_cast<const uint4*>(P.shift_k + (ch0 + 2 * (lane & 3)) * 4));
        const float skip = __bfloat162float(P.ssm_d[ch0 + (lane & 7)]);
        const uint32_t w0 = __byte_perm(wv.x, wv.z, 0x5410), w1 = __byte_perm(wv.x, wv.z, 0x7632);
        const uint32_t w2 = __byte_perm(wv.y, wv.w, 0x5410), w3 = __byte_perm(wv.y, wv.w, 0x7632);
        auto swz32 = [](uint32_t a) { return a ^ ((a >> 3) & 16); };
        const uint32_t kl = (lane >> 3) * 288 + (lane & 7) * 32 + rho * 16;
        const uint32_t ka = stg + swz32(kl + 32), kh = stg + swz32(kl + 12 * 288), va = stg + 4608 + swz32(lane * 32 + rho * 16);
        const uint32_t ua = sb + SM_SIG + (lane & 7) * 8192 + (((lane >> 3) ^ (lane & 7)) << 4);
        uint32_t eh = 0;
#pragma unroll 1
        for (int ck = aw, rd = 0; rd < 9; ck += 3, ++rd) {
          if (rd == 6) {
            bar_sync(4, 96);
            if (at == 64) mbar_arrive(bar(B_STG_FREE));
          }
          const int c = rd < 6 ? ck : ck - 18;
          if (c < 8) {
            uint32_t x[32], dst = sb + SM_SIG + c * 8192;
            if (rd < 6) {
              mbar_wait(bar(B_H_FULL + rd), 0);
#pragma unroll
              for (int i = 0; i < 8; i++) ldsm4(x + 4 * i, dst + 4096 + i * 512 + lane * 16);
              const float d = __shfl_sync(0xffffffffu, skip, c);
              if (lane == 0) x[0] = pack_bf16(bf_lo(x[0]) + d, bf_hi(x[0]));
              dst += 4096 + (lane >> 1) * 128 + ((((lane & 1) * 4) ^ ((lane >> 1) & 7)) << 4);
            } else {
#pragma unroll
              for (int i = 0; i < 8; i++) ldsm4_t(x + 4 * i, dst + i * 512 + ((lane ^ c) << 4));
              dst += (lane >> 4) * 1024 + (lane & 7) * 128 + ((((lane >> 1) & 4) ^ (lane & 7)) << 4);
            }
            const uint32_t e = normalize(x, dst);
            if (rd < 6) {
              eh |= e << (8 * rd);
            } else {
              const int f = min(max((int)(e + (eh & 255)) - 125, 0), 254);
              eh >>= 8;
              if (lane == 0) asm volatile("st.shared.b16 [%0], %1;" :: "r"(sb + SM_SC + rho * 16 + 2 * c), "h"((uint16_t)(f << 7)) : "memory");
            }
          }
          if (ck < 16) {
            mbar_wait(pf, rd & 1);
            uint32_t k[20], v[16];
            ldsm4(k, kh);
#pragma unroll
            for (int m = 0; m < 4; m++) { ldsm4(k + 4 + 4 * m, (ka ^ ((m & 1) << 4)) + m * 1152); ldsm4(v + 4 * m, va + m * 1024); }
            arrive_both(pe + ((k[3] | k[4] | k[8] | k[12] | k[16] | v[0] | v[4] | v[8] | v[12]) & P.zero), lane, ck < 13);
#pragma unroll
            for (int m = 0; m < 4; m++) {
              uint32_t u[4];
#pragma unroll
              for (int n = 0; n < 4; n++) {
                const uint32_t* kk = k + 4 + 4 * m + n;
                u[n] = bmul2(bfma2(kk[0], w0, bfma2(kk[-1], w1, bfma2(kk[-2], w2, bmul2(kk[-3], w3)))), v[4 * m + n]);
              }
              stsm4_t((ua ^ (m << 6)) + ck * 256, u[0], u[1], u[2], u[3]);
            }
          }
        }
        fence_async_smem();
        __syncwarp();
        if (lane == 0) mbar_arrive(bar(B_SIG_READY));
        bar_sync(4, 96);
        if (at == 32) {
          const uint4 s = lds128(sb + SM_SC + rho * 16);
          asm volatile("st.async.weak.shared::cluster.mbarrier::complete_tx::bytes.v4.b32 [%0], {%1,%2,%3,%4}, [%5];"
                       :: "r"(peer_addr(sb + SM_SC + rho * 16, rho ^ 1)), "r"(s.x), "r"(s.y), "r"(s.z), "r"(s.w), "r"(peer_addr(bar(B_RDY0), rho ^ 1)) : "memory");
        }
        TSTAMP(at == 0, 20); LOOPSTAMP(4, at == 0, 22);
      }
    }
    __syncwarp();
    {
      const int a4 = warp - 8;
      const uint8_t* part = xch + 2 * SLOT + (lane >> 3) * 4 * KV_SLICE + (a4 * 8 + (lane & 7)) * 16;
      const uint8_t* zpart = xch + 2 * SLOT + (lane & 15) * KV_SLICE + 512 + (a4 * 2 + (lane >> 4)) * 4;
      uint8_t* red = xch + 2 * SLOT + 16 * KV_SLICE + (a4 * 8 + (lane & 7)) * 16 + (lane >> 3) * 4;
      uint8_t* zred = xch + 2 * SLOT + 16 * KV_SLICE + 512 + (a4 * 2 + (lane >> 4)) * 4;
      const uint8_t* all = g_xch[a4 * 32 + j] + 2 * SLOT + 16 * KV_SLICE + lane * 16;
      const uint8_t* zall = all + 512 + (lane & 28) - lane * 16;
      keep(part); keep(zpart); keep(red); keep(zred); keep(all); keep(zall);
      uint32_t v[20];
      int n = 0;
      mbar_wait(bar(B_KVP), 0);
      if (PD1) delay(PD1);
      do {
#pragma unroll
        for (int i = 0; i < 4; i++) ld_relaxed4(v + 4 * i, part + i * KV_SLICE);
        v[16] = ld_relaxed(zpart);
      } while (!all_arrived<17>(v) && ++n < kSpinLimit);
      TSTAMP(tid == 288, 21);
      float lo[4], hi[4], z = __uint_as_float(v[16]);
#pragma unroll
      for (int b = 0; b < 4; b++) {
        lo[b] = (bf_lo(v[b]) + bf_lo(v[4 + b])) + (bf_lo(v[8 + b]) + bf_lo(v[12 + b]));
        hi[b] = (bf_hi(v[b]) + bf_hi(v[4 + b])) + (bf_hi(v[8 + b]) + bf_hi(v[12 + b]));
      }
      const bool u16 = lane & 16, u8 = lane & 8;
#pragma unroll
      for (int b = 0; b < 2; b++) {
        lo[b] = (u16 ? lo[b + 2] : lo[b]) + __shfl_xor_sync(0xffffffffu, u16 ? lo[b] : lo[b + 2], 16);
        hi[b] = (u16 ? hi[b + 2] : hi[b]) + __shfl_xor_sync(0xffffffffu, u16 ? hi[b] : hi[b + 2], 16);
      }
      const float l = (u8 ? lo[1] : lo[0]) + __shfl_xor_sync(0xffffffffu, u8 ? lo[0] : lo[1], 8);
      const float h = (u8 ? hi[1] : hi[0]) + __shfl_xor_sync(0xffffffffu, u8 ? hi[0] : hi[1], 8);
      st_relaxed(red, pack_bf16(l, h));
#pragma unroll
      for (int o = 8; o; o >>= 1) z += __shfl_xor_sync(0xffffffffu, z, o);
      if ((lane & 15) == 0) st_relaxed(zred, pack_bf16(z, z));
      TSTAMP(tid == 288, 22);
      n = 0;
      if (PD2) delay(PD2);
      do {
#pragma unroll
        for (int i = 0; i < 4; i++) {
          ld_relaxed4(v + 4 * i, all + i * 8 * XCH_BYTES);
          v[16 + i] = ld_relaxed(zall + i * 8 * XCH_BYTES);
        }
      } while (!all_arrived<20>(v) && ++n < kSpinLimit);
#pragma unroll
      for (int i = 0; i < 4; i++) {
        const uint32_t dst = sb + SM_KV + (a4 * 4 + i) * 640;
        stsm4(dst + lane * 16, v[4 * i], v[4 * i + 1], v[4 * i + 2], v[4 * i + 3]);
        asm volatile("st.shared.b32 [%0], %1;" :: "r"(dst + 512 + lane * 4), "r"(v[16 + i]) : "memory");
      }
      fence_async_smem();
      __syncwarp();
      if (lane == 0) mbar_arrive(bar(B_KV_READY));
      TSTAMP(tid == 288, 23);
    }
    if (warp != 10) cluster_arrive();
    if (warp == 8) {
      int s = 4;
      uint32_t ph = 1;
#pragma unroll 1
      for (int ks = 4; ks < 16; ++ks) {
        uint32_t fb = bar(B_OUT_FULL + s), dst = sb + ((B_SLOTS >> (4 * s)) & 15) * SLOT;
        int c = chunk(ks);
        keep(fb); keep(dst); keep(c);
        mbar_wait(bar(ks == 4 ? B_CONV_DONE : B_OUT_EMPTY + s), ks == 4 ? 0 : ph);
        if (elect()) load_wo(dst, c, 2 * SLOT, fb);
        if (++s == 5) { s = 0; ph ^= 1; }
      }
    } else {
      auto wait_chunks = [&](unsigned mask) {
        unsigned ready;
        int n = 0;
        do {
          ready = __ballot_sync(0xffffffffu, ld_relaxed(g_xch[r * 8 + ((lane >> 1) & 7)] + XCH_FLAG) + 1 > (lane & 1));
        } while ((~ready & mask) && ++n < kSpinLimit);
        return ready;
      };
      if (warp == 9) {
        if (elect()) {
#pragma unroll 1
          for (int c = 0; c < 2; c++) {
            mbar_wait(bar(B_O_WRITTEN + c), 0);
            TSTAMP(c == 0, 19);
            fence_async_smem();
            bulk_store(xch + c * SLOT, sb + c * SLOT, SLOT);
            bulk_commit();
            bulk_wait_read();
            if (c) mbar_arrive(bar(B_OT_FREE));
            delay(FDELAY);
            st_relaxed(xch + XCH_FLAG, c);
            if (!c) delay(C1DELAY);
            TSTAMP(c == 1, 25);
          }
        }
        __syncwarp();
        wait_chunks(0xaaaa);
        if (lane == 0) mbar_arrive(bar(B_FLAGS1));
      } else if (warp == 10) {
        mbar_wait(bar(B_RDY0), 0);
        mbar_wait(bar(B_QKV_DONE), 0);
#pragma unroll 1
        for (int n = 0; n < 4; n++) {
          const int w = n & 1;
          if (n == 2) for (int i = 0; i < 4; i++) mbar_wait(bar(B_Q_FULL + i), 0);
          mbar_wait(bar(B_SEG + n), 0);
          if (RFENCE) fence_async_smem();
          if (elect()) bulk_to_peer(sb + (n < 2 ? SM_Y0 : SM_SIG) + w * 8192 + 4096, sb + SM_YT + w * 4096, 4096, bar(B_YIN + (n >> 1)), rho ^ 1);
          if (w) {
            mbar_wait(bar(B_YIN + (n >> 1)), 0);
            if (lane == 0) asm volatile("mbarrier.arrive.shared::cluster.b64 _, [%0];" :: "r"(n < 2 ? peer_addr(bar(B_RDY1), rho ^ 1) : bar(B_Y_READY)) : "memory");
          }
        }
        __syncwarp();
        cluster_arrive();
        TSTAMP(lane == 0, 26);
      } else {
        mbar_wait(bar(B_O_WRITTEN), 0);
        unsigned ready = 0;
        int s = 2;
        uint32_t ph = 1;
#pragma unroll 1
        for (int ks = 2; ks < 16; ++ks) {
          const int c = chunk(ks);
          uint32_t fb = bar(B_OUT_FULL + s), dst = sb + ((A_SLOTS >> (4 * s)) & 15) * SLOT;
          uint8_t* src = g_xch[r * 8 + (c >> 1)] + (c & 1) * SLOT;
          keep(fb); keep(dst); keep(src);
          if (ks < 5 || ks == 9) {
            const unsigned need = ks < 4 ? 1u << c : 0x5555u;
            if (ks == 9) mbar_wait(bar(B_FLAGS1), 0);
            else if (~ready & need) ready = wait_chunks(need);
          }
          if (ks == 3 || ks == 5) mbar_wait(bar(ks == 3 ? B_O_WRITTEN + 1 : B_OT_FREE), 0);
          if (ks >= 4) mbar_wait(bar(ks == 4 ? B_CONV_DONE : B_OUT_EMPTY + s), ks == 4 ? 0 : ph);
          if (elect()) bulk_load(dst, src, SLOT, fb);
          TSTAMP(ks == 2 && lane == 0, 18); LOOPSTAMP(2, lane == 0, 11 + ks);
          if (++s == 5) { s = 0; ph ^= 1; }
        }
      }
    }
    if (LATE || warp == 9 || warp == 10) {
      const int yc = (lane & 1) + ((lane >> 2) & 2) + (lane & 2) * 2, ysrc = (lane >> 2) & 1;
      const uint32_t ya = sb + (yc & 4 ? SM_SIG : SM_Y0) + (yc & 1) * 8192 + (yc & 2) * 1024 + (ysrc ^ rho) * 4096 +
                          (lane >> 4) * 128 + ((yc ^ (2 * ysrc)) << 4);
      uint32_t s0, s1;
      mbar_wait(bar(B_Y_READY), 0);
      asm volatile("ld.shared.v2.b32 {%0,%1}, [%2];" : "=r"(s0), "=r"(s1) : "r"(sb + SM_SC + (lane & 3) * 8) : "memory");
#pragma unroll 1
      for (int n = warp == 8 ? 6 : warp == 11 ? 7 : warp - 9; n < 8; n += LATE && n >= 4 ? 8 : 2) {
        __nv_bfloat16* op = P.out_ptr + (rho * 1024 + n * 128 + (lane >> 2)) * 2048 + 1024 + cl * 16 + (lane & 3) * 4;
        const uint32_t qa = sb + SM_Q + (n & 3) * 4096 + lane * 8;
        if (n >= 4 && !(DBG & 1)) mbar_wait(bar(B_Q_FULL + (n & 3)), 1);
#pragma unroll 1
        for (int u0 = 0; u0 < (DBG & 2 ? 0 : 8); u0 += 2) {
          const uint32_t t0 = clock32();
          uint32_t y[2][4], q[2][4];
#pragma unroll
          for (int u = 0; u < 2; u++) {
            ldsm4_t(y[u], (ya ^ ((u0 + u) << 4)) + n * 256);
#pragma unroll
            for (int m = 0; m < 2; m++)
              asm volatile("ld.shared.v2.b32 {%0,%1}, [%2];" : "=r"(q[u][2 * m]), "=r"(q[u][2 * m + 1]) : "r"(qa + (u0 + u) * 512 + m * 256) : "memory");
          }
#pragma unroll
          for (int u = 0; u < 2; u++)
#pragma unroll
            for (int m = 0; m < 2; m++)
              asm volatile("st.global.v2.b32 [%0], {%1,%2};" :: "l"(op + (u0 * 16 + u * 16 + m * 8) * 2048),
                           "r"(bmul2(q[u][2 * m], bmul2(y[u][2 * m], s0))), "r"(bmul2(q[u][2 * m + 1], bmul2(y[u][2 * m + 1], s1))) : "memory");
          while (clock32() - t0 < (n < 4 ? PPACE : n < 6 ? PPACE2 : PPACE3)) { }
        }
        __syncwarp();
        if (n < 4 && !(DBG & 1) && elect()) load_q(n + 4);
      }
      TSTAMP(tid == 320, 24); TSTAMP(tid == 352, 27);
    }
    __syncwarp();
    cluster_wait();
  }
}

typedef CUresult (*EncodeFn)(CUtensorMap*, CUtensorMapDataType, cuuint32_t, void*, const cuuint64_t*, const cuuint64_t*,
                             const cuuint32_t*, const cuuint32_t*, CUtensorMapInterleave, CUtensorMapSwizzle,
                             CUtensorMapL2promotion, CUtensorMapFloatOOBfill);

void encode(EncodeFn fn, CUtensorMap* m, const void* p, int rank, const cuuint64_t* dims, const cuuint64_t* strides,
            const cuuint32_t* box, CUtensorMapSwizzle sw) {
  const cuuint32_t es[3] = {1, 1, 1};
  fn(m, CU_TENSOR_MAP_DATA_TYPE_BFLOAT16, rank, const_cast<void*>(p), dims, strides, box, es, CU_TENSOR_MAP_INTERLEAVE_NONE, sw,
     CU_TENSOR_MAP_L2_PROMOTION_NONE, CU_TENSOR_MAP_FLOAT_OOB_FILL_NONE);
}
void encode2d(EncodeFn fn, CUtensorMap* m, const void* p, uint64_t cols, uint64_t rows, uint32_t bc, uint32_t br, CUtensorMapSwizzle sw) {
  const cuuint64_t dims[2] = {cols, rows}, strides[1] = {cols * 2};
  const cuuint32_t box[2] = {bc, br};
  encode(fn, m, p, 2, dims, strides, box, sw);
}
void encode3d(EncodeFn fn, CUtensorMap* m, const void* p, uint32_t nblk) {
  const cuuint64_t dims[3] = {1024, 128, 16}, strides[2] = {2048 * 16, 2048};
  const cuuint32_t box[3] = {16, nblk, 16};
  encode(fn, m, p, 3, dims, strides, box, CU_TENSOR_MAP_SWIZZLE_32B);
}

}

extern "C" void kernel_launch(void* const* d_in, const int* in_sizes, int n_in, void* d_out, int out_size) {
  static EncodeFn fn = nullptr;
  if (!fn) {
    cudaDriverEntryPointQueryResult qr;
    cudaGetDriverEntryPoint("cuTensorMapEncodeTiled", (void**)&fn, cudaEnableDefault, &qr);
    cudaFuncSetAttribute(fused_kernel, cudaFuncAttributeMaxDynamicSharedMemorySize, SM_TOTAL);
  }
  Params P;
  encode2d(fn, &P.x, d_in[0], 1024, 2048, 32, 128, CU_TENSOR_MAP_SWIZZLE_64B);
  {
    const cuuint64_t dims[3] = {64, 1024, 48}, strides[2] = {6144, 128};
    const cuuint32_t box[3] = {64, 32, 2};
    encode(fn, &P.w, d_in[1], 3, dims, strides, box, CU_TENSOR_MAP_SWIZZLE_128B);
  }
  encode2d(fn, &P.wk, d_in[1], 3072, 1024, 64, 32, CU_TENSOR_MAP_SWIZZLE_128B);
  encode2d(fn, &P.wo, d_in[2], 1024, 1024, 64, 64, CU_TENSOR_MAP_SWIZZLE_128B);
  encode2d(fn, &P.outa, d_out, 2048, 2048, 64, 16, CU_TENSOR_MAP_SWIZZLE_128B);
  encode3d(fn, &P.k, d_in[4], 9);
  encode3d(fn, &P.v, d_in[5], 8);
  encode2d(fn, &P.q, d_in[3], 1024, 2048, 16, 128, CU_TENSOR_MAP_SWIZZLE_NONE);
  P.shift_k = (const __nv_bfloat16*)d_in[6];
  P.ssm_k = (const __nv_bfloat16*)d_in[7];
  P.ssm_d = (const __nv_bfloat16*)d_in[8];
  P.zero = 0;
  P.q_ptr = (const __nv_bfloat16*)d_in[3];
  P.out_ptr = (__nv_bfloat16*)d_out;
  P.wo_ptr = (const __nv_bfloat16*)d_in[2];
  fused_kernel<<<kCtas, kThreads, SM_TOTAL>>>(P);
}
```

```cpp
#include <cuda.h>
#include <cuda_runtime.h>
#include <cuda_bf16.h>
#include <stdint.h>

#define DEVI __device__ __forceinline__

namespace {

DEVI void mma_nt(float* d, uint64_t da, uint64_t db, int sd) {
  asm volatile("{\n.reg .pred p;\nsetp.ne.b32 p, %66, 0;\nwgmma.mma_async.sync.aligned.m64n128k16.f32.bf16.bf16 {%0, %1, %2, %3, %4, %5, %6, %7, %8, %9, %10, %11, %12, %13, %14, %15, %16, %17, %18, %19, %20, %21, %22, %23, %24, %25, %26, %27, %28, %29, %30, %31, %32, %33, %34, %35, %36, %37, %38, %39, %40, %41, %42, %43, %44, %45, %46, %47, %48, %49, %50, %51, %52, %53, %54, %55, %56, %57, %58, %59, %60, %61, %62, %63}, %64, %65, p, 1, 1, 0, 1;\n}\n"
    : "+f"(d[0]), "+f"(d[1]), "+f"(d[2]), "+f"(d[3]), "+f"(d[4]), "+f"(d[5]), "+f"(d[6]), "+f"(d[7]), "+f"(d[8]), "+f"(d[9]), "+f"(d[10]), "+f"(d[11]), "+f"(d[12]), "+f"(d[13]), "+f"(d[14]), "+f"(d[15]), "+f"(d[16]), "+f"(d[17]), "+f"(d[18]), "+f"(d[19]), "+f"(d[20]), "+f"(d[21]), "+f"(d[22]), "+f"(d[23]), "+f"(d[24]), "+f"(d[25]), "+f"(d[26]), "+f"(d[27]), "+f"(d[28]), "+f"(d[29]), "+f"(d[30]), "+f"(d[31]), "+f"(d[32]), "+f"(d[33]), "+f"(d[34]), "+f"(d[35]), "+f"(d[36]), "+f"(d[37]), "+f"(d[38]), "+f"(d[39]), "+f"(d[40]), "+f"(d[41]), "+f"(d[42]), "+f"(d[43]), "+f"(d[44]), "+f"(d[45]), "+f"(d[46]), "+f"(d[47]), "+f"(d[48]), "+f"(d[49]), "+f"(d[50]), "+f"(d[51]), "+f"(d[52]), "+f"(d[53]), "+f"(d[54]), "+f"(d[55]), "+f"(d[56]), "+f"(d[57]), "+f"(d[58]), "+f"(d[59]), "+f"(d[60]), "+f"(d[61]), "+f"(d[62]), "+f"(d[63])
    : "l"(da), "l"(db), "r"(sd));
}
DEVI void mma_tn(float* d, uint64_t da, uint64_t db, int sd) {
  asm volatile("{\n.reg .pred p;\nsetp.ne.b32 p, %66, 0;\nwgmma.mma_async.sync.aligned.m64n128k16.f32.bf16.bf16 {%0, %1, %2, %3, %4, %5, %6, %7, %8, %9, %10, %11, %12, %13, %14, %15, %16, %17, %18, %19, %20, %21, %22, %23, %24, %25, %26, %27, %28, %29, %30, %31, %32, %33, %34, %35, %36, %37, %38, %39, %40, %41, %42, %43, %44, %45, %46, %47, %48, %49, %50, %51, %52, %53, %54, %55, %56, %57, %58, %59, %60, %61, %62, %63}, %64, %65, p, 1, 1, 1, 0;\n}\n"
    : "+f"(d[0]), "+f"(d[1]), "+f"(d[2]), "+f"(d[3]), "+f"(d[4]), "+f"(d[5]), "+f"(d[6]), "+f"(d[7]), "+f"(d[8]), "+f"(d[9]), "+f"(d[10]), "+f"(d[11]), "+f"(d[12]), "+f"(d[13]), "+f"(d[14]), "+f"(d[15]), "+f"(d[16]), "+f"(d[17]), "+f"(d[18]), "+f"(d[19]), "+f"(d[20]), "+f"(d[21]), "+f"(d[22]), "+f"(d[23]), "+f"(d[24]), "+f"(d[25]), "+f"(d[26]), "+f"(d[27]), "+f"(d[28]), "+f"(d[29]), "+f"(d[30]), "+f"(d[31]), "+f"(d[32]), "+f"(d[33]), "+f"(d[34]), "+f"(d[35]), "+f"(d[36]), "+f"(d[37]), "+f"(d[38]), "+f"(d[39]), "+f"(d[40]), "+f"(d[41]), "+f"(d[42]), "+f"(d[43]), "+f"(d[44]), "+f"(d[45]), "+f"(d[46]), "+f"(d[47]), "+f"(d[48]), "+f"(d[49]), "+f"(d[50]), "+f"(d[51]), "+f"(d[52]), "+f"(d[53]), "+f"(d[54]), "+f"(d[55]), "+f"(d[56]), "+f"(d[57]), "+f"(d[58]), "+f"(d[59]), "+f"(d[60]), "+f"(d[61]), "+f"(d[62]), "+f"(d[63])
    : "l"(da), "l"(db), "r"(sd));
}
DEVI void mma_nt256(float* d, uint64_t da, uint64_t db, int sd) {
  asm volatile("{\n.reg .pred p;\nsetp.ne.b32 p, %130, 0;\nwgmma.mma_async.sync.aligned.m64n256k16.f32.bf16.bf16 {%0, %1, %2, %3, %4, %5, %6, %7, %8, %9, %10, %11, %12, %13, %14, %15, %16, %17, %18, %19, %20, %21, %22, %23, %24, %25, %26, %27, %28, %29, %30, %31, %32, %33, %34, %35, %36, %37, %38, %39, %40, %41, %42, %43, %44, %45, %46, %47, %48, %49, %50, %51, %52, %53, %54, %55, %56, %57, %58, %59, %60, %61, %62, %63, %64, %65, %66, %67, %68, %69, %70, %71, %72, %73, %74, %75, %76, %77, %78, %79, %80, %81, %82, %83, %84, %85, %86, %87, %88, %89, %90, %91, %92, %93, %94, %95, %96, %97, %98, %99, %100, %101, %102, %103, %104, %105, %106, %107, %108, %109, %110, %111, %112, %113, %114, %115, %116, %117, %118, %119, %120, %121, %122, %123, %124, %125, %126, %127}, %128, %129, p, 1, 1, 0, 1;\n}\n"
    : "+f"(d[0]), "+f"(d[1]), "+f"(d[2]), "+f"(d[3]), "+f"(d[4]), "+f"(d[5]), "+f"(d[6]), "+f"(d[7]), "+f"(d[8]), "+f"(d[9]), "+f"(d[10]), "+f"(d[11]), "+f"(d[12]), "+f"(d[13]), "+f"(d[14]), "+f"(d[15]), "+f"(d[16]), "+f"(d[17]), "+f"(d[18]), "+f"(d[19]), "+f"(d[20]), "+f"(d[21]), "+f"(d[22]), "+f"(d[23]), "+f"(d[24]), "+f"(d[25]), "+f"(d[26]), "+f"(d[27]), "+f"(d[28]), "+f"(d[29]), "+f"(d[30]), "+f"(d[31]), "+f"(d[32]), "+f"(d[33]), "+f"(d[34]), "+f"(d[35]), "+f"(d[36]), "+f"(d[37]), "+f"(d[38]), "+f"(d[39]), "+f"(d[40]), "+f"(d[41]), "+f"(d[42]), "+f"(d[43]), "+f"(d[44]), "+f"(d[45]), "+f"(d[46]), "+f"(d[47]), "+f"(d[48]), "+f"(d[49]), "+f"(d[50]), "+f"(d[51]), "+f"(d[52]), "+f"(d[53]), "+f"(d[54]), "+f"(d[55]), "+f"(d[56]), "+f"(d[57]), "+f"(d[58]), "+f"(d[59]), "+f"(d[60]), "+f"(d[61]), "+f"(d[62]), "+f"(d[63]), "+f"(d[64]), "+f"(d[65]), "+f"(d[66]), "+f"(d[67]), "+f"(d[68]), "+f"(d[69]), "+f"(d[70]), "+f"(d[71]), "+f"(d[72]), "+f"(d[73]), "+f"(d[74]), "+f"(d[75]), "+f"(d[76]), "+f"(d[77]), "+f"(d[78]), "+f"(d[79]), "+f"(d[80]), "+f"(d[81]), "+f"(d[82]), "+f"(d[83]), "+f"(d[84]), "+f"(d[85]), "+f"(d[86]), "+f"(d[87]), "+f"(d[88]), "+f"(d[89]), "+f"(d[90]), "+f"(d[91]), "+f"(d[92]), "+f"(d[93]), "+f"(d[94]), "+f"(d[95]), "+f"(d[96]), "+f"(d[97]), "+f"(d[98]), "+f"(d[99]), "+f"(d[100]), "+f"(d[101]), "+f"(d[102]), "+f"(d[103]), "+f"(d[104]), "+f"(d[105]), "+f"(d[106]), "+f"(d[107]), "+f"(d[108]), "+f"(d[109]), "+f"(d[110]), "+f"(d[111]), "+f"(d[112]), "+f"(d[113]), "+f"(d[114]), "+f"(d[115]), "+f"(d[116]), "+f"(d[117]), "+f"(d[118]), "+f"(d[119]), "+f"(d[120]), "+f"(d[121]), "+f"(d[122]), "+f"(d[123]), "+f"(d[124]), "+f"(d[125]), "+f"(d[126]), "+f"(d[127])
    : "l"(da), "l"(db), "r"(sd));
}
DEVI void mma_kv_init(float* d, uint32_t a0, uint32_t a1, uint32_t a2, uint32_t a3, uint64_t db) {
  asm volatile("wgmma.mma_async.sync.aligned.m64n72k16.f32.bf16.bf16 {%0, %1, %2, %3, %4, %5, %6, %7, %8, %9, %10, %11, %12, %13, %14, %15, %16, %17, %18, %19, %20, %21, %22, %23, %24, %25, %26, %27, %28, %29, %30, %31, %32, %33, %34, %35}, {%36,%37,%38,%39}, %40, 0, 1, 1, 1;\n"
    : "=f"(d[0]), "=f"(d[1]), "=f"(d[2]), "=f"(d[3]), "=f"(d[4]), "=f"(d[5]), "=f"(d[6]), "=f"(d[7]), "=f"(d[8]), "=f"(d[9]), "=f"(d[10]), "=f"(d[11]), "=f"(d[12]), "=f"(d[13]), "=f"(d[14]), "=f"(d[15]), "=f"(d[16]), "=f"(d[17]), "=f"(d[18]), "=f"(d[19]), "=f"(d[20]), "=f"(d[21]), "=f"(d[22]), "=f"(d[23]), "=f"(d[24]), "=f"(d[25]), "=f"(d[26]), "=f"(d[27]), "=f"(d[28]), "=f"(d[29]), "=f"(d[30]), "=f"(d[31]), "=f"(d[32]), "=f"(d[33]), "=f"(d[34]), "=f"(d[35])
    : "r"(a0), "r"(a1), "r"(a2), "r"(a3), "l"(db));
}
DEVI void mma_kv_acc(float* d, uint32_t a0, uint32_t a1, uint32_t a2, uint32_t a3, uint64_t db) {
  asm volatile("wgmma.mma_async.sync.aligned.m64n72k16.f32.bf16.bf16 {%0, %1, %2, %3, %4, %5, %6, %7, %8, %9, %10, %11, %12, %13, %14, %15, %16, %17, %18, %19, %20, %21, %22, %23, %24, %25, %26, %27, %28, %29, %30, %31, %32, %33, %34, %35}, {%36,%37,%38,%39}, %40, 1, 1, 1, 1;\n"
    : "+f"(d[0]), "+f"(d[1]), "+f"(d[2]), "+f"(d[3]), "+f"(d[4]), "+f"(d[5]), "+f"(d[6]), "+f"(d[7]), "+f"(d[8]), "+f"(d[9]), "+f"(d[10]), "+f"(d[11]), "+f"(d[12]), "+f"(d[13]), "+f"(d[14]), "+f"(d[15]), "+f"(d[16]), "+f"(d[17]), "+f"(d[18]), "+f"(d[19]), "+f"(d[20]), "+f"(d[21]), "+f"(d[22]), "+f"(d[23]), "+f"(d[24]), "+f"(d[25]), "+f"(d[26]), "+f"(d[27]), "+f"(d[28]), "+f"(d[29]), "+f"(d[30]), "+f"(d[31]), "+f"(d[32]), "+f"(d[33]), "+f"(d[34]), "+f"(d[35])
    : "r"(a0), "r"(a1), "r"(a2), "r"(a3), "l"(db));
}
DEVI void mma_o_init(float* d, uint32_t a0, uint32_t a1, uint32_t a2, uint32_t a3, uint64_t db) {
  asm volatile("wgmma.mma_async.sync.aligned.m64n40k16.f32.bf16.bf16 {%0, %1, %2, %3, %4, %5, %6, %7, %8, %9, %10, %11, %12, %13, %14, %15, %16, %17, %18, %19}, {%20,%21,%22,%23}, %24, 0, 1, 1, 1;\n"
    : "=f"(d[0]), "=f"(d[1]), "=f"(d[2]), "=f"(d[3]), "=f"(d[4]), "=f"(d[5]), "=f"(d[6]), "=f"(d[7]), "=f"(d[8]), "=f"(d[9]), "=f"(d[10]), "=f"(d[11]), "=f"(d[12]), "=f"(d[13]), "=f"(d[14]), "=f"(d[15]), "=f"(d[16]), "=f"(d[17]), "=f"(d[18]), "=f"(d[19])
    : "r"(a0), "r"(a1), "r"(a2), "r"(a3), "l"(db));
}
DEVI void mma_o_acc(float* d, uint32_t a0, uint32_t a1, uint32_t a2, uint32_t a3, uint64_t db) {
  asm volatile("wgmma.mma_async.sync.aligned.m64n40k16.f32.bf16.bf16 {%0, %1, %2, %3, %4, %5, %6, %7, %8, %9, %10, %11, %12, %13, %14, %15, %16, %17, %18, %19}, {%20,%21,%22,%23}, %24, 1, 1, 1, 1;\n"
    : "+f"(d[0]), "+f"(d[1]), "+f"(d[2]), "+f"(d[3]), "+f"(d[4]), "+f"(d[5]), "+f"(d[6]), "+f"(d[7]), "+f"(d[8]), "+f"(d[9]), "+f"(d[10]), "+f"(d[11]), "+f"(d[12]), "+f"(d[13]), "+f"(d[14]), "+f"(d[15]), "+f"(d[16]), "+f"(d[17]), "+f"(d[18]), "+f"(d[19])
    : "r"(a0), "r"(a1), "r"(a2), "r"(a3), "l"(db));
}
DEVI void fft1_init(uint32_t* d, uint32_t a0, uint32_t a1, uint32_t a2, uint32_t a3, uint64_t db) {
  asm volatile("wgmma.mma_async.sync.aligned.m64n128k16.f16.f16.f16 {%0, %1, %2, %3, %4, %5, %6, %7, %8, %9, %10, %11, %12, %13, %14, %15, %16, %17, %18, %19, %20, %21, %22, %23, %24, %25, %26, %27, %28, %29, %30, %31}, {%32,%33,%34,%35}, %36, 0, 1, 1, 1;\n"
    : "=r"(d[0]), "=r"(d[1]), "=r"(d[2]), "=r"(d[3]), "=r"(d[4]), "=r"(d[5]), "=r"(d[6]), "=r"(d[7]), "=r"(d[8]), "=r"(d[9]), "=r"(d[10]), "=r"(d[11]), "=r"(d[12]), "=r"(d[13]), "=r"(d[14]), "=r"(d[15]), "=r"(d[16]), "=r"(d[17]), "=r"(d[18]), "=r"(d[19]), "=r"(d[20]), "=r"(d[21]), "=r"(d[22]), "=r"(d[23]), "=r"(d[24]), "=r"(d[25]), "=r"(d[26]), "=r"(d[27]), "=r"(d[28]), "=r"(d[29]), "=r"(d[30]), "=r"(d[31])
    : "r"(a0), "r"(a1), "r"(a2), "r"(a3), "l"(db));
}
DEVI void fft1_acc(uint32_t* d, uint32_t a0, uint32_t a1, uint32_t a2, uint32_t a3, uint64_t db) {
  asm volatile("wgmma.mma_async.sync.aligned.m64n128k16.f16.f16.f16 {%0, %1, %2, %3, %4, %5, %6, %7, %8, %9, %10, %11, %12, %13, %14, %15, %16, %17, %18, %19, %20, %21, %22, %23, %24, %25, %26, %27, %28, %29, %30, %31}, {%32,%33,%34,%35}, %36, 1, 1, 1, 1;\n"
    : "+r"(d[0]), "+r"(d[1]), "+r"(d[2]), "+r"(d[3]), "+r"(d[4]), "+r"(d[5]), "+r"(d[6]), "+r"(d[7]), "+r"(d[8]), "+r"(d[9]), "+r"(d[10]), "+r"(d[11]), "+r"(d[12]), "+r"(d[13]), "+r"(d[14]), "+r"(d[15]), "+r"(d[16]), "+r"(d[17]), "+r"(d[18]), "+r"(d[19]), "+r"(d[20]), "+r"(d[21]), "+r"(d[22]), "+r"(d[23]), "+r"(d[24]), "+r"(d[25]), "+r"(d[26]), "+r"(d[27]), "+r"(d[28]), "+r"(d[29]), "+r"(d[30]), "+r"(d[31])
    : "r"(a0), "r"(a1), "r"(a2), "r"(a3), "l"(db));
}
DEVI void fft2_init(uint32_t* d, uint32_t a0, uint32_t a1, uint32_t a2, uint32_t a3, uint64_t db) {
  asm volatile("wgmma.mma_async.sync.aligned.m64n32k16.f16.f16.f16 {%0, %1, %2, %3, %4, %5, %6, %7}, {%8,%9,%10,%11}, %12, 0, 1, 1, 0;\n"
    : "=r"(d[0]), "=r"(d[1]), "=r"(d[2]), "=r"(d[3]), "=r"(d[4]), "=r"(d[5]), "=r"(d[6]), "=r"(d[7])
    : "r"(a0), "r"(a1), "r"(a2), "r"(a3), "l"(db));
}
DEVI void fft2_acc(uint32_t* d, uint32_t a0, uint32_t a1, uint32_t a2, uint32_t a3, uint64_t db) {
  asm volatile("wgmma.mma_async.sync.aligned.m64n32k16.f16.f16.f16 {%0, %1, %2, %3, %4, %5, %6, %7}, {%8,%9,%10,%11}, %12, 1, 1, 1, 0;\n"
    : "+r"(d[0]), "+r"(d[1]), "+r"(d[2]), "+r"(d[3]), "+r"(d[4]), "+r"(d[5]), "+r"(d[6]), "+r"(d[7])
    : "r"(a0), "r"(a1), "r"(a2), "r"(a3), "l"(db));
}
DEVI void fft3r_init(float* d, uint32_t a0, uint32_t a1, uint32_t a2, uint32_t a3, uint64_t db) {
  asm volatile("wgmma.mma_async.sync.aligned.m64n32k16.f32.f16.f16 {%0, %1, %2, %3, %4, %5, %6, %7, %8, %9, %10, %11, %12, %13, %14, %15}, {%16,%17,%18,%19}, %20, 0, 1, 1, 0;\n"
    : "=f"(d[0]), "=f"(d[1]), "=f"(d[2]), "=f"(d[3]), "=f"(d[4]), "=f"(d[5]), "=f"(d[6]), "=f"(d[7]), "=f"(d[8]), "=f"(d[9]), "=f"(d[10]), "=f"(d[11]), "=f"(d[12]), "=f"(d[13]), "=f"(d[14]), "=f"(d[15])
    : "r"(a0), "r"(a1), "r"(a2), "r"(a3), "l"(db));
}
DEVI void fft3r_acc(float* d, uint32_t a0, uint32_t a1, uint32_t a2, uint32_t a3, uint64_t db) {
  asm volatile("wgmma.mma_async.sync.aligned.m64n32k16.f32.f16.f16 {%0, %1, %2, %3, %4, %5, %6, %7, %8, %9, %10, %11, %12, %13, %14, %15}, {%16,%17,%18,%19}, %20, 1, 1, 1, 0;\n"
    : "+f"(d[0]), "+f"(d[1]), "+f"(d[2]), "+f"(d[3]), "+f"(d[4]), "+f"(d[5]), "+f"(d[6]), "+f"(d[7]), "+f"(d[8]), "+f"(d[9]), "+f"(d[10]), "+f"(d[11]), "+f"(d[12]), "+f"(d[13]), "+f"(d[14]), "+f"(d[15])
    : "r"(a0), "r"(a1), "r"(a2), "r"(a3), "l"(db));
}
DEVI void fft3_init(float* d, uint64_t da, uint64_t db) {
  asm volatile("wgmma.mma_async.sync.aligned.m64n32k16.f32.f16.f16 {%0, %1, %2, %3, %4, %5, %6, %7, %8, %9, %10, %11, %12, %13, %14, %15}, %16, %17, 0, 1, 1, 1, 0;\n"
    : "=f"(d[0]), "=f"(d[1]), "=f"(d[2]), "=f"(d[3]), "=f"(d[4]), "=f"(d[5]), "=f"(d[6]), "=f"(d[7]), "=f"(d[8]), "=f"(d[9]), "=f"(d[10]), "=f"(d[11]), "=f"(d[12]), "=f"(d[13]), "=f"(d[14]), "=f"(d[15])
    : "l"(da), "l"(db));
}
DEVI void fft3_acc(float* d, uint64_t da, uint64_t db) {
  asm volatile("wgmma.mma_async.sync.aligned.m64n32k16.f32.f16.f16 {%0, %1, %2, %3, %4, %5, %6, %7, %8, %9, %10, %11, %12, %13, %14, %15}, %16, %17, 1, 1, 1, 1, 0;\n"
    : "+f"(d[0]), "+f"(d[1]), "+f"(d[2]), "+f"(d[3]), "+f"(d[4]), "+f"(d[5]), "+f"(d[6]), "+f"(d[7]), "+f"(d[8]), "+f"(d[9]), "+f"(d[10]), "+f"(d[11]), "+f"(d[12]), "+f"(d[13]), "+f"(d[14]), "+f"(d[15])
    : "l"(da), "l"(db));
}

__device__ __align__(128) const uint32_t g_tables[2560] = {
0xa11ba1e4,0xa51ba5e4,0x18b61248,0x1cb61648,0x9f12a052,0xa311a452,0x1d7f1bdb,0x217f1fdb,0x9bdb9d7f,0x9fdba17f,0x20521f12,0x24522311,
0x924898b6,0x96489cb6,0x21e4211b,0x25e4251b,0xaa63ab5f,0xae5faf59,0x21e41bdb,0x25e41fdb,0xa86ba967,0xac6aad65,0x26e024e9,0x2ade28e8,
0xa4e9a6e0,0xa8e8aade,0x2967286b,0x2d652c6a,0x9bdba1e4,0x9fdba5e4,0x2b5f2a63,0x2f592e5f,0xadc2aea7,0xb1b6b294,0x254d1f12,0x294d2311,
0xabf6acde,0xafefb0d7,0x2a31286b,0x2e2d2c6a,0xa86baa31,0xac6aae2d,0x2cde2bf6,0x30d72fef,0x9f12a54d,0xa311a94d,0x2ea72dc2,0x329431b6,
0xb02cb0d2,0xb41ab4b7,0x27a9211b,0x2ba7251b,0xadc2af0c,0xb1b6b2f7,0x2c792a63,0x30742e5f,0xaa63ac79,0xae5fb074,0x2f0c2dc2,0x32f731b6,
0xa11ba7a9,0xa51baba7,0x30d2302c,0x34b7341a,0xb17ab257,0xb552b61a,0x290222ad,0x2d0026ad,0xaf8cb09f,0xb371b487,0x2ddc2c2e,0x31cf3029,
0xac2eaddc,0xb029b1cf,0x309f2f8c,0x34873371,0xa2ada902,0xa6adad00,0x3257317a,0x361a3552,0xb2cdb3e3,0xb682b76f,0x2a312420,0x2e2d281f,
0xb0acb1bb,0xb493b58d,0x2f3f2d2a,0x33283122,0xad2aaf3f,0xb122b328,0x31bb30ac,0x358d3493,0xa420aa31,0xa81fae2d,0x33e332cd,0x376f3682,
0xb413b4bc,0xb7a6b85a,0x2b5f24e9,0x2f5928e8,0xb194b2da,0xb56ab68d,0x30522e28,0x343e3219,0xae28b052,0xb219b43e,0x32da3194,0x368d356a,
0xa4e9ab5f,0xa8e8af59,0x34bc3413,0x385a37a6,0xb4c3b58c,0xb85fb8f3,0x2c4725b2,0x304229b1,0xb27eb3fd,0xb63cb785,0x31062f26,0x34e7330f,
0xaf26b106,0xb30fb4e7,0x33fd327e,0x3785363c,0xa5b2ac47,0xa9b1b042,0x358c34c3,0x38f3385f,0xb577b662,0xb8e5b982,0x2cde267b,0x30d72a7a,
0xb36bb493,0xb70ab83a,0x31bb3012,0x358d3402,0xb012b1bb,0xb402b58d,0x3493336b,0x383a370a,0xa67bacde,0xaa7ab0d7,0x36623577,0x398238e5,
0xb630b741,0xb962ba04,0x2d762744,0x316c2b43,0xb42eb52a,0xb7d2b8ad,0x32713092,0x3631347b,0xb092b271,0xb47bb631,0x352a342e,0x38ad37d2,
0xa744ad76,0xab43b16c,0x37413630,0x3a043962,0xb6eeb815,0xb9d6ba7a,0x2e0e2807,0x32012c06,0xb4a7b5c4,0xb84ab91b,0x33293113,0x36d234f3,
0xb113b329,0xb4f3b6d2,0x35c434a7,0x391b384a,0xa807ae0e,0xac06b201,0x381536ee,0x3a7a39d6,0xb7b4b88e,0xba41bae1,0x2ea7286b,0x32942c6a,
0xb523b662,0xb8a8b982,0x33e33194,0x376f356a,0xb194b3e3,0xb56ab76f,0x36623523,0x398238a8,0xa86baea7,0xac6ab294,0x388e37b4,0x3ae13a41,
0xb841b90f,0xbaa2bb3a,0x2f3f28d0,0x33282cce,0xb5a1b705,0xb902b9e3,0x344f3216,0x380535df,0xb216b44f,0xb5dfb805,0x370535a1,0x39e33902,
0xa8d0af3f,0xacceb328,0x390f3841,0x3b3a3aa2,0xb8acb997,0xbaf7bb83,0x2fd82935,0x33ba2d33,0xb621b7ac,0xb958ba3d,0x34ae3298,0x38503654,
0xb298b4ae,0xb654b850,0x37ac3621,0x3a3d3958,0xa935afd8,0xad33b3ba,0x399738ac,0x3b833af7,0xb91cba28,0xbb42bbbc,0x30392999,0x34262d97,
0xb6a4b82d,0xb9aaba90,0x350e331c,0x389936c6,0xb31cb50e,0xb6c6b899,0x382d36a4,0x3a9039aa,0xa999b039,0xad97b426,0x3a28391c,0x3bbc3b42,
0xb992bac3,0xbb81bbe3,0x308529fe,0x346f2dfb,0xb72ab886,0xb9f8badb,0x357033a0,0x38e03737,0xb3a0b570,0xb737b8e0,0x3886372a,0x3adb39f8,
0xa9feb085,0xadfbb46f,0x3ac33992,0x3be33b81,0x39cf3b16,0x3b9c3bf1,0xb0acaa31,0xb493ae2d,0x376f38b4,0x3a1d3afe,0xb5a1b3e3,0xb902b76f,
0x33e335a1,0x376f3902,0xb8b4b76f,0xbafeba1d,0x2a3130ac,0x2e2d3493,0xbb16b9cf,0xbbf1bb9c,0x39563a74,0x3b633bd2,0xb05fa9cc,0xb44badc9,
0x36e73859,0x39d23ab6,0xb53fb35e,0xb8bcb6ff,0x335e353f,0x36ff38bc,0xb859b6e7,0xbab6b9d2,0x29cc305f,0x2dc9344b,0xba74b956,0xbbd2bb63,
0x38e339de,0x3b1e3ba1,0xb012a967,0xb402ad65,0x36623801,0x39823a67,0xb4deb2da,0xb874b68d,0x32da34de,0x368d3874,0xb801b662,0xba67b982,
0x29673012,0x2d653402,0xb9deb8e3,0xbba1bb1e,0x38763952,0x3ace3b60,0xaf8ca902,0xb371ad00,0x35e13758,0x392e3a11,0xb47eb257,0xb82ab61a,
0x3257347e,0x361a382a,0xb758b5e1,0xba11b92e,0x29022f8c,0x2d003371,0xb952b876,0xbb60bace,0x380d38ce,0x3a733b10,0xaef3a89e,0xb2deac9c,
0x356236b3,0x38d639b3,0xb420b1d5,0xb7bdb5a5,0x31d53420,0x35a537bd,0xb6b3b562,0xb9b3b8d6,0x289e2ef3,0x2c9c32de,0xb8ceb80d,0xbb10ba73,
0x37503851,0x3a0d3ab0,0xae5aa839,0xb24bac38,0x34e53613,0x387a394f,0xb386b153,0xb721b52f,0x31533386,0x352f3721,0xb613b4e5,0xb94fb87a,
0x28392e5a,0x2c38324b,0xb851b750,0xbab0ba0d,0x368e37b4,0x399d3a41,0xadc2a7a9,0xb1b6aba7,0x346a3577,0x381a38e5,0xb2cdb0d2,0xb682b4b7,
0x30d232cd,0x34b73682,0xb577b46a,0xb8e5b81a,0x27a92dc2,0x2ba731b6,0xb7b4b68e,0xba41b99d,0x35d236d1,0x392439c5,0xad2aa6e0,0xb122aade,
0x33e334de,0x376f3874,0xb216b052,0xb5dfb43e,0x30523216,0x343e35df,0xb4deb3e3,0xb874b76f,0x26e02d2a,0x2ade3122,0xb6d1b5d2,0xb9c5b924,
0x351c35f6,0x38a3393c,0xac93a617,0xb08daa16,0x32f43448,0x36a437fe,0xb160afa5,0xb53ab389,0x2fa53160,0x3389353a,0xb448b2f4,0xb7feb6a4,
0x26172c93,0x2a16308d,0xb5f6b51c,0xb93cb8a3,0x346a3523,0x381a38a8,0xabf6a54d,0xafefa94d,0x3209336b,0x35d4370a,0xb0acaea7,0xb493b294,
0x2ea730ac,0x32943493,0xb36bb209,0xb70ab5d4,0x254d2bf6,0x294d2fef,0xb523b46a,0xb8a8b81a,0x33783456,0x3715380a,0xaac8a484,0xaec3a884,
0x3120324a,0x34ff360e,0xaff2ada9,0xb3d3b19e,0x2da92ff2,0x319e33d3,0xb24ab120,0xb60eb4ff,0x24842ac8,0x28842ec3,0xb456b378,0xb80ab715,
0x3223331c,0x35eb36c6,0xa999a376,0xad97a776,0x3039312d,0x3426350b,0xae8dacac,0xb27cb0a6,0x2cac2e8d,0x30a6327c,0xb12db039,0xb50bb426,
0x23762999,0x27762d97,0xb31cb223,0xb6c6b5eb,0x30d23194,0x34b7356a,0xa86ba1e4,0xac6aa5e4,0x2ea73012,0x32943402,0xad2aab5f,0xb122af59,
0x2b5f2d2a,0x2f593122,0xb012aea7,0xb402b294,0x21e4286b,0x25e42c6a,0xb194b0d2,0xb56ab4b7,0x2f0c3012,0x32f73402,0xa67ba052,0xaa7aa452,
0x2cde2df5,0x30d731e8,0xab91a967,0xaf8bad65,0x29672b91,0x2d652f8b,0xadf5acde,0xb1e8b0d7,0x2052267b,0x24522a7a,0xb012af0c,0xb402b2f7,
0x2c792d2a,0x30743122,0xa4209d7f,0xa81fa17f,0x2a312b91,0x2e2d2f8b,0xa8d0a6e0,0xacceaade,0x26e028d0,0x2ade2cce,0xab91aa31,0xaf8bae2d,
0x1d7f2420,0x217f281f,0xad2aac79,0xb122b074,0x27a9286b,0x2ba72c6a,0x9f1298b6,0xa3119cb6,0x254d267b,0x294d2a7a,0xa420a1e4,0xa81fa5e4,
0x21e42420,0x25e4281f,0xa67ba54d,0xaa7aa94d,0x18b61f12,0x1cb62311,0xa86ba7a9,0xac6aaba7,0x3f803f80,0x3f803f80,0x3f803f80,0x3f803f80,
0x3f803f80,0x3f803f80,0x3f803f80,0x3f803f80,0x3f803f80,0x3f803f80,0x3f803f80,0x3f803f80,0x3f803f80,0x3f803f80,0x3f803f80,0x3f803f80,
0x3f803f80,0x3f803f80,0x3f803f80,0x3f803f80,0x3f803f80,0x3f803f80,0x3f803f80,0x3f803f80,0x3f803f80,0x3f803f80,0x3f803f80,0x3f803f80,
0x3f803f80,0x3f803f80,0x3f803f80,0x3f803f80,0x3f803f80,0x3f803f80,0x3f803f80,0x3f803f80,0x3f803f80,0x3f803f80,0x3f803f80,0x3f803f80,
0x3f803f80,0x3f803f80,0x3f803f80,0x3f803f80,0x3f803f80,0x3f803f80,0x3f803f80,0x3f803f80,0x3f803f80,0x3f803f80,0x3f803f80,0x3f803f80,
0x3f803f80,0x3f803f80,0x3f803f80,0x3f803f80,0x3f803f80,0x3f803f80,0x3f803f80,0x3f803f80,0x3f803f80,0x3f803f80,0x3f803f80,0x3f803f80,
0x3f803f80,0x3f803f80,0x3f803f80,0x3f803f80,0x3f803f80,0x3f803f80,0x3f803f80,0x3f803f80,0x3f803f80,0x3f803f80,0x3f803f80,0x3f803f80,
0x3f803f80,0x3f803f80,0x3f803f80,0x3f803f80,0x3f803f80,0x3f803f80,0x3f803f80,0x3f803f80,0x3f803f80,0x3f803f80,0x3f803f80,0x3f803f80,
0x3f803f80,0x3f803f80,0x3f803f80,0x3f803f80,0x3f803f80,0x3f803f80,0x3f803f80,0x3f803f80,0x3f803f80,0x3f803f80,0x3f803f80,0x3f803f80,
0x3f803f80,0x3f803f80,0x3f803f80,0x3f803f80,0x3f803f80,0x3f803f80,0x3f803f80,0x3f803f80,0x3f803f80,0x3f803f80,0x3f803f80,0x3f803f80,
0x3f803f80,0x3f803f80,0x3f803f80,0x3f803f80,0x3f803f80,0x3f803f80,0x3f803f80,0x3f803f80,0x3f803f80,0x3f803f80,0x3f803f80,0x3f803f80,
0x3f803f80,0x3f803f80,0x3f803f80,0x3f803f80,0x3f803f80,0x3f803f80,0x3f803f80,0x3f803f80,0x3f803f80,0x3f803f80,0x3f803f80,0x3f803f80,
0x3f803f80,0x3f803f80,0x3f803f80,0x3f803f80,0x3f803f80,0x3f803f80,0x3f803f80,0x3f803f80,0x3f803f80,0x3f803f80,0x3f803f80,0x3f803f80,
0x3f803f80,0x3f803f80,0x3f803f80,0x3f803f80,0x3f803f80,0x3f803f80,0x3f803f80,0x3f803f80,0x3f803f80,0x3f803f80,0x3f803f80,0x3f803f80,
0x3f803f80,0x3f803f80,0x3f803f80,0x3f803f80,0x3f803f80,0x3f803f80,0x3f803f80,0x3f803f80,0x3f803f80,0x3f803f80,0x3f803f80,0x3f803f80,
0x3f803f80,0x3f803f80,0x3f803f80,0x3f803f80,0x3f803f80,0x3f803f80,0x3f803f80,0x3f803f80,0x3f803f80,0x3f803f80,0x3f803f80,0x3f803f80,
0x3f803f80,0x3f803f80,0x3f803f80,0x3f803f80,0x3f803f80,0x3f803f80,0x3f803f80,0x3f803f80,0x3f803f80,0x3f803f80,0x3f803f80,0x3f803f80,
0x3f803f80,0x3f803f80,0x3f803f80,0x3f803f80,0x3f803f80,0x3f803f80,0x3f803f80,0x3f803f80,0x3f803f80,0x3f803f80,0x3f803f80,0x3f803f80,
0x3f803f80,0x3f803f80,0x3f803f80,0x3f803f80,0x3f803f80,0x3f803f80,0x3f803f80,0x3f803f80,0x3f803f80,0x3f803f80,0x3f803f80,0x3f803f80,
0x3f803f80,0x3f803f80,0x3f803f80,0x3f803f80,0x3f803f80,0x3f803f80,0x3f803f80,0x3f803f80,0x3f803f80,0x3f803f80,0x3f803f80,0x3f803f80,
0x3f803f80,0x3f803f80,0x3f803f80,0x3f803f80,0x3f803f80,0x3f803f80,0x3f803f80,0x3f803f80,0x3f803f80,0x3f803f80,0x3f803f80,0x3f803f80,
0x3f803f80,0x3f803f80,0x3f803f80,0x3f803f80,0x3f803f80,0x3f803f80,0x3f803f80,0x3f803f80,0x3f803f80,0x3f803f80,0x3f803f80,0x3f803f80,
0x3f803f80,0x3f803f80,0x3f803f80,0x3f803f80,0x3f803f80,0x3f803f80,0x3f803f80,0x3f803f80,0x3f803f80,0x3f803f80,0x3f803f80,0x3f803f80,
0x3f803f80,0x3f803f80,0x3f803f80,0x3f803f80,0x3f803f80,0x3f803f80,0x3f803f80,0x3f803f80,0x3f803f80,0x3f803f80,0x3f803f80,0x3f803f80,
0x3f803f80,0x3f803f80,0x3f803f80,0x3f803f80,0x3f803f80,0x3f803f80,0x3f803f80,0x3f803f80,0x3f803f80,0x3f803f80,0x3f803f80,0x3f803f80,
0x3f803f80,0x3f803f80,0x3f803f80,0x3f803f80,0x3f803f80,0x3f803f80,0x3f803f80,0x3f803f80,0x3f803f80,0x3f803f80,0x3f803f80,0x3f803f80,
0x3f803f80,0x3f803f80,0x3f803f80,0x3f803f80,0x3f803f80,0x3f803f80,0x3f803f80,0x3f803f80,0x3f803f80,0x3f803f80,0x3f803f80,0x3f803f80,
0x3f803f80,0x3f803f80,0x3f803f80,0x3f803f80,0x3f803f80,0x3f803f80,0x3f803f80,0x3f803f80,0x3f803f80,0x3f803f80,0x3f803f80,0x3f803f80,
0x3f803f80,0x3f803f80,0x3f803f80,0x3f803f80,0x3f803f80,0x3f803f80,0x3f803f80,0x3f803f80,0x3f803f80,0x3f803f80,0x3f803f80,0x3f803f80,
0x3f803f80,0x3f803f80,0x3f803f80,0x3f803f80,0x3f803f80,0x3f803f80,0x3f803f80,0x3f803f80,0x3f803f80,0x3f803f80,0x3f803f80,0x3f803f80,
0x3f803f80,0x3f803f80,0x3f803f80,0x3f803f80,0x3f803f80,0x3f803f80,0x3f803f80,0x3f803f80,0x3f803f80,0x3f803f80,0x3f803f80,0x3f803f80,
0x3f803f80,0x3f803f80,0x3f803f80,0x3f803f80,0x3f803f80,0x3f803f80,0x3f803f80,0x3f803f80,0x3f803f80,0x3f803f80,0x3f803f80,0x3f803f80,
0x3f803f80,0x3f803f80,0x3f803f80,0x3f803f80,0x3f803f80,0x3f803f80,0x3f803f80,0x3f803f80,0x3f803f80,0x3f803f80,0x3f803f80,0x3f803f80,
0x3f803f80,0x3f803f80,0x3f803f80,0x3f803f80,0x3f803f80,0x3f803f80,0x3f803f80,0x3f803f80,0x3f803f80,0x3f803f80,0x3f803f80,0x3f803f80,
0x3f803f80,0x3f803f80,0x3f803f80,0x3f803f80,0x3f803f80,0x3f803f80,0x3f803f80,0x3f803f80,0x3f803f80,0x3f803f80,0x3f803f80,0x3f803f80,
0x3f803f80,0x3f803f80,0x3f803f80,0x3f803f80,0x3f803f80,0x3f803f80,0x3f803f80,0x3f803f80,0x3f803f80,0x3f803f80,0x3f803f80,0x3f803f80,
0x3f803f80,0x3f803f80,0x3f803f80,0x3f803f80,0x3f803f80,0x3f803f80,0x3f803f80,0x3f803f80,0x3f803f80,0x3f803f80,0x3f803f80,0x3f803f80,
0x3f803f80,0x3f803f80,0x3f803f80,0x3f803f80,0x3f803f80,0x3f803f80,0x3f803f80,0x3f803f80,0x3f803f80,0x3f803f80,0x3f803f80,0x3f803f80,
0x3f803f80,0x3f803f80,0x3f803f80,0x3f803f80,0x3f803f80,0x3f803f80,0x3f803f80,0x3f803f80,0x3f803f80,0x3f803f80,0x3f803f80,0x3f803f80,
0x3f803f80,0x3f803f80,0x3f803f80,0x3f803f80,0x3f803f80,0x3f803f80,0x3f803f80,0x3f803f80,0x3f803f80,0x3f803f80,0x3f803f80,0x3f803f80,
0x3f803f80,0x3f803f80,0x3f803f80,0x3f803f80,0x3f803f80,0x3f803f80,0x3f803f80,0x3f803f80,0x3f803f80,0x3f803f80,0x3f803f80,0x3f803f80,
0x3f803f80,0x3f803f80,0x3f803f80,0x3f803f80,0x3f803f80,0x3f803f80,0x3f803f80,0x3f803f80,0x3f803f80,0x3f803f80,0x3f803f80,0x3f803f80,
0x3f803f80,0x3f803f80,0x3f803f80,0x3f803f80,0x3f803f80,0x3f803f80,0x3f803f80,0x3f803f80,0x3f803f80,0x3f803f80,0x3f803f80,0x3f803f80,
0x3f803f80,0x3f803f80,0x3f803f80,0x3f803f80,0x3bf23bff,0x3ba53bd4,0x3b163b65,0x3a493ab6,0x3b7c3bfb,0x38bc3a60,0x2b43356a,0xb7f3b359,
0x3a933bf1,0x9cb63764,0xba9eb785,0xbb73bbf3,0x39463be2,0xb8cc28e8,0xbb42bbc2,0x3328b70a,0x374e3bcf,0xbbabb648,0xaec3baa9,0x3bfa3994,
0x33403bb7,0xbb85b9fc,0x3a64b0be,0x2c6a3b47,0xa4523b9a,0xb86abbae,0x3b6a3911,0xbbd0ad65,0xb4263b78,0x2adebbe6,0x30f03bfd,0xb5b1bbbc,
0x2f5925e4,0x34b73294,0x376f361a,0x38f3385a,0x35a52c9c,0x3a7338d6,0x3bfd3b87,0x3af13bc9,0x388e2fbd,0x3c003b18,0x387f3b10,0xb5d42f27,
0x3a04316c,0x3a673bfe,0xb6bb33d3,0xbbccbb2f,0x3b1e32f7,0x34933b5c,0xbbf5b86f,0x2d00b9bc,0x3bcb343e,0xb576394f,0xb8d1bbe9,0x3bfb36a4,
0x3c0034ff,0xbaac347b,0x3602ba31,0x32de3bf9,0x3bba35bc,0xbbfdb109,0x3be7aa7a,0xbb7a341a,0x394639cd,0x381538b2,0x358136dd,0x3153341a,
0xbb1eb9c9,0xbbf5bbdd,0xba39bb65,0xb4f3b889,0xb340b93c,0x3966340e,0x3bec3b87,0x37213a7e,0x3c003a4d,0x32193a21,0xbb5eb785,0xb894bbb0,
0xb426389e,0xbb37bb45,0x38b7b3d3,0x397d3bfc,0xbafebac1,0x3b13217f,0xadc93aa9,0xba49bb59,0x3979b7e8,0xb0d73b32,0xb6f4bbe9,0x3af139da,
0x38553b24,0xb9a1ba3d,0x3ab03911,0xbb73b759,0x3a043982,0x3ae13a7a,0x3b833b3a,0x3be33bbc,0x374e3986,0xae9131e8,0xb907b61a,0xbb9cba97,
0xbbcbba0d,0xb9e7bbbd,0x3074b56a,0x3b2a38ad,0x2452b8ee,0x3bda3924,0x363c3b10,0xba90b46f,0x3bba3a89,0xb6e836af,0xba76bbc2,0x39d2ac06,
0xb7c8384a,0xb77abc00,0x3bf8386f,0xb8f33654,0xb9d6baf4,0x3be836ff,0xbb3530be,0x37f3b974,0x3abab737,0xb9af3902,0x3865ba31,0xb5d43b1b,
0x32c62fbd,0x363134cf,0x38653785,0x398b38fd,0xb715b16c,0xbae1b970,0xbbfebbc2,0xba85bb92,0x392e32f7,0x3bf53b6c,0x37a63aa9,0xb7422311,
0xba81b43e,0xb9e7bbfc,0x380fb0be,0x3b963b7f,0x3b7134ff,0x32193b04,0xbc00b911,0x319eb929,0xbbefb5bc,0x36e8b8b2,0x382a3bfd,0xbbffb805,
0x3bf23676,0xbb1331e8,0x376fb9aa,0x2f8b3bde,0xbb7cb72c,0x3be8340e,0xbbfdaa16,0x3bb8b122,0xbbd2bbf1,0xbb60bba1,0xbab0bb10,0xb9c5ba41,
0x3b2c3be2,0x381539df,0xa94d33d3,0xb8a3b52f,0xba19bbcf,0x2e91b5f7,0x3b07386f,0x3b213c00,0x38a83bb7,0xb966aba7,0xbae5bbe9,0x3517b599,
0xb5dfbb9a,0x3bda37b2,0x1fdb3a31,0xbbe0ba1d,0x30293b78,0xbb37ba7a,0x3ad5aa7a,0xa7763aeb,0x2f59bb52,0x377a3bdd,0xbb16b9a6,0x3bf231cf,
0xb5a53b27,0x30d7bbbd,0x2b433bfe,0xb432bbe5,0x3a813a0d,0x3b3f3ae8,0x3bbf3b87,0x3bfb3be5,0xb5dfb8ee,0x3263ad97,0x399d3785,0x3bd03b01,
0xbbefba89,0xb958bb81,0x3389b3d3,0x3b7a394a,0xaf59384a,0xbbf7b9b8,0xb4c3baa9,0x3afb35eb,0x3b7c3af4,0xb825353a,0xb9f8bbe9,0x3a542884,
0x388eb737,0x360e3bf4,0xbbdcb911,0x398bb4db,0xb946bb4f,0x3bc03830,0xbb832a7a,0x38a3b8db,0xbb1e35c8,0x3a35b85f,0xb90739aa,0x3742bab6,
0xb8a8b93c,0xb6c6b80a,0xb402b56a,0xac6ab122,0xbb71ba4d,0xbbd7bbf8,0xb9b3bb10,0xb2deb7bd,0x3029389e,0xb9f4b58d,0xbbc6bbc2,0xb5b1ba00,
0x3bf23ac1,0x2dfb3999,0xbba3b86f,0xb7d2bb6f,0x35a5b7e8,0x3ad83b90,0xb95430be,0xb8e5bbff,0xba93bb24,0x3b682ef5,0xb2013a31,0xb9c5bb9f,
0xba043682,0x33ebbad1,0x35813bfd,0xba85ba5c,0x374e3b76,0xb90cbab3,0x3a3939a6,0xbb21b85a,0xb7c83b52,0x391bba9b,0xba2539aa,0x3afbb889,
0xb9793b27,0x3bc5b80a,0xbb8eaa16,0x38e538ad,0xbaba3af7,0x3b60ad97,0xb27cba2d,0xb98b3bb0,0xbb943ac4,0x3815358d,0x39e3bbea,0xba852c06,
0xbbf93a8c,0xae9139b8,0x3bacb874,0x3742bb59,0xbbe43a50,0xb9663b90,0x340233ba,0x3b96b974,0xbb573a11,0xbbda3bf4,0xb99d3b0d,0xb19e3759,
0xba5839cd,0xbb373ad1,0xbbc63b89,0xbbff3bee,0x3afe3676,0xba29b884,0x391f39a6,0xb7d2ba97,0x39d6372c,0xb3a2bae8,0xb5463bfe,0x3a54ba7e,
0x385537dd,0x3631bbf8,0xbbd63916,0x39c5346f,0x35233845,0x3ae1bb81,0xb96bb0a6,0xb8a33bfc,0x2d333899,0x3bf5b999,0x3487baa5,0xbb213654,
0xb13b38ea,0x39e7b53a,0x3bbfbbc3,0x3517b9da,0xb65f3937,0x32192ef5,0x39b3b790,0x3be0bb1b,0xb8e03982,0xb6e83830,0xb389355e,0xa7763042,
0xbb943682,0x3bebb371,0xbbfe2a7a,0x3bcc3042,0xad33bb76,0xb79b3bd4,0x3b07b9aa,0xbbfa32ad,0x3be4b50b,0xb6c6b8d6,0xb80f3bfe,0x3bfbb835,
0xb65f3bb5,0x3bd7b764,0x9fdbba2d,0xbbd03a41,0xba58330f,0xb9f43bfe,0x382a30a6,0x3b7abb92,0x3a45bbe1,0xadfbb648,0xbb163874,0xbafb3c00,
0x3699afef,0x3ad8b94f,0x3bfdbbc3,0x3a54bb7f,0xbbdf3bfa,0xbb683bae,0xba9e3b0d,0xb98b3a1d,0x35233b4f,0xb08dbbc8,0xa94d3bfd,0x3328bbee,
0xbbf935c8,0x3b0a3294,0xb7a6b9a6,0xad003bd3,0x313bbb98,0xbb3f3a60,0x3ae52a16,0xac6abace,0x3b57b44b,0x3263bb18,0xbc003916,0x32de38fd,
0xb8e03bce,0x3958a8e8,0x3ad5bbea,0xb5b1b52f,0xb8f83185,0xbbf73b5c,0xb76f3aa5,0x37d2a311,0x3b4abbf0,0x3825b9fc,0xab43b3ba,0xb8e53599,
0x31b6acce,0x360eb47b,0x387fb790,0x39c5b929,0x3a9337dd,0xb9a1b924,0x387f3a2d,0xb66bbb01,0xb946b845,0x308d3b45,0x36bbbbea,0xbac73a00,
0x374e3899,0x379bbc00,0xbbf53874,0x393335eb,0xb340b8ea,0xbb3f3b32,0x38d133ba,0x3941bbff,0xa4523937,0x3bd7b902,0x3602bb0d,0xbabd34db,
0x3426b982,0xb9583371,0xbbe73b89,0xb68d3a5c,0xb7c839c9,0x2dfb3294,0x391fb625,0x3bb3bab6,0x3979ba0d,0x3825b8d6,0x3546b6d2,0x3010b359,
0x388ebaf7,0xb9af3a21,0x3a9eb916,0xbb5437bd,0xba043ac4,0x3bebb6af,0xbb42b0a6,0x3840394a,0x3b1eba8c,0xbb0aa17f,0x2ec33aa5,0x3a15bb6f,
0xbbcb3a50,0x36c636ff,0x3a64bbc3,0xba09a884,0x3c00ba11,0x3263ba3d,0xbb6a3790,0xb8503b9f,0xbbba39cd,0xb9f43bc8,0x30f0355e,0x3b4cb8db,
0x3afeb986,0x3bf7bbd4,0x3a25bb63,0x3457b85a,0xb9d6393c,0xbad83a60,0xbb8e3b3d,0xbbef3bc9,0x33403b98,0xa9b1bbed,0xb0743bfe,0x3517bbc9,
0x3c00b44b,0xbaa2b4cf,0x363c3a2d,0x319ebbf3,0x3426bbce,0xbb8b39df,0x3a7630a6,0x2776bb2f,0xbafe3185,0xb4b73b6c,0x3bf8b874,0xaf8bb994,
0xb9793bf0,0x38bc2ba7,0x3b35bbc3,0xb432b6a4,0x3855acce,0x3c00bb04,0x3865bb0d,0xb66bad65,0x3b94bbff,0x38ccba7a,0x294db55e,0xb840341a,
0xad33a5e4,0xb49331e8,0xb7a63625,0xb9333889,0x3bcbb50b,0xbbfe305b,0x3bec2a16,0xbb96b359,0x2452bbb5,0xb87a3ba1,0x3b5eb916,0xbbe02f27,
0xbbba330f,0x35523970,0x38b7bbea,0xbbff370a,0xb7c83be1,0x3ba5b5f7,0x2dc9baa5,0xbbf239bc,0x39d6afef,0x3a73bbfc,0xb6f4b3ba,0xbbb83b47,
0x3ababbfa,0x1cb6b7b2,0xbab03790,0xbb543bf9,0xb52326ad,0xba6738b2,0xbbfe3b89,0xbac73bbc,0xbbf93bff,0xbbab3bdd,0xbb073b63,0xba153a97,
0xb8f83986,0xb77a385f,0xb4c33625,0xaf8b32ad,0xb699393c,0x30d7305b,0x3954b6d2,0x3bb8bace,0xb1b638ee,0x39afb4cf,0x3bdcbba7,0x366bba41,
0x2c38389e,0x3bebb970,0x3581bade,0xbac7352f,0x34e7384a,0x3b0abb6c,0xb907b24b,0xb9333c00,0x383a37e8,0x36c6bbfc,0xbbec38c1,0x39413599,
0x39c03737,0xb263bb04,0xb63c3bf6,0x3abdba1d,0x3aee3682,0xb9f4b8b2,0x38b739f0,0xb68dbaeb,0xba4539c9,0xbb133ab3,0xbba33b63,0xbbf23bd3,
0xbb4a3a0d,0xbbe83bed,0xb9f83b3d,0xb4323835,0xbbdf3a4d,0xb9a13ba1,0x320134ab,0x3b54b8fd,0xbbfc3a89,0xb08d39df,0x3b83b81a,0x3840bb92,
0xbb9e3ac1,0x379b35f7,0x3a39bbd8,0xba15a311,0xbacb3af4,0x3b3faba7,0xb074ba6f,0xba093b7f,0xb9903b24,0x3bd7b7b2,0xbb5eae5f,0x38503929,
0xb7fe3b4f,0x3958ba7a,0xba76395d,0x3b4cb805,0x2c3826ad,0x33ebb109,0x36bbb55e,0x38a3b805,0x3b9ebbff,0x390cba9b,0x2ec3b625,0xb74231cf,
0xb83a2c9c,0xbbfe3ae8,0xb8d13b3d,0x35173122,0xb9903bf1,0x387a2d97,0x3b6abba7,0xb19eb7bd,0x3aeeb16c,0x3552bb81,0xbbe7381a,0x27763a00,
0x3463bbcf,0xbba539b8,0x3a25324b,0x2f8bbb6f,0xbbff343e,0x3a73353a,0xb546ba6f,0xb4323bff,0x32c63b9a,0x9cb6bbf4,0xb27c3bf6,0x366bbb9f,
0xbbfc3bff,0xbbc03be6,0xbb423b89,0xba853aeb,0x34e7a5e4,0x3a35b884,0x3bf5bb63,0x3b21bbde,0x3acbbbfb,0x29b1b80a,0xba6436d2,0xbb963be5,
0xb9c02fbd,0xbaa23bf8,0x360234ab,0x3be0bb01,0xb7fe3be2,0x3b8bb58d,0x30f0bade,0xbbff394a,0x3bb2b2f7,0xb4b7b999,0xb91f3bd8,0x3bf2b5eb,
0x281fbbb7,0xb8bc3b90,0x3b8eb8c1,0xbbb82884,0xbbd234ff,0x3c00aef5,0xbbd6ae5f,0x3b5434db,0xbaba3a4d,0xbb683b18,0xbbd63ba7,0xbc003bf3,
0x3b94ba89,0x3bc0bbfe,0x396bbade,0x3153b70a,0xbbf93ac1,0xb90c3b5c,0x3487324b,0x3b9cb994,0x3be4baf4,0x29b1b94f,0xbbbf38c1,0xb7213b47,
0xbb573b24,0x387a347b,0x39b3bbf6,0xba902d65,0x3a58bb4f,0xbb8b3109,0x338939f0,0x397dbbbc,0xb8f83b76,0x3ba5b884,0xbba39648,0x38f33889,
0x3699bb98,0xb8bc3ae8,0x39f8b9eb,0xbaf138ad,0x3855b8ee,0x360eb764,0x327cb4ab,0x251baf27,0xb523389e,0x33eb28e8,0x39e3b81a,0x3be3bb2f,
0x2d33b84a,0xba353648,0xbbac3bd8,0xb4f339bc,0x313b37e8,0x3bfeb9fc,0x3402ba6f,0xbb2a36a4,0xb65fb737,0xbaa23bae,0x399d2e5f,0x3894bbf9,
0x38e03682,0x3552bbe6,0xbbc6395d,0x39d2341a,0xba45b5c8,0x34b73a9b,0x34c3bc00,0xba493a97,0x3b4a350b,0xba73b80a,0x39543962,0xb7f3ba7e,
0xbbe43bfb,0xbb853bbd,0xbae53b3d,0xba093a7e,0xb65f2fbd,0xbaac3924,0xbc003ba7,0xbabd3bb0,0x3a58bbe2,0xaadeb6af,0xbad5381a,0xbb4c3bfc,
0x3a45b2f7,0x3a29bc00,0xb76fb24b,0xbbb33b59,0xb6993bb7,0x3bc5b6ff,0x2b43ba6f,0xbbef39da,0xbbdf34ff,0x36313902,0x387fbbf6,0xbc003759,
0xac38bb78,0xb8153bc8,0x3b42b95d,0xbbe33042,0x3b9eb676,0xbbf53294,0x3bf51648,0xbb9cb2ad,0xb13b2c9c,0xb576340e,0xb80f36d2,0xb94138ad,
0x3b57bbf1,0x386aba21,0x1fdbb4ab,0xb850346f,0x38e0b16c,0x3bfdbb45,0x382abade,0xb68dac06,0xb8f83bcf,0x391ba17f,0x3b16bbd8,0xb457b654,
0xbb4a343e,0xb3a23b32,0x3bfdb8c1,0xb010b974,0x31b6bb9a,0xbb603a3d,0x3a9e2e5f,0x251bbb1b,0x3bfcb5bc,0xbae1b371,0x36bb39f0,0x3153bbee,
0x34e73b52,0xae91bbd4,0xaec33c00,0x34f3bbd3,0x3bb235c8,0xbbf7b1e8,0x3bf81648,0xbbb331cf,0x3bff350b,0xbad8340e,0x36f4b9eb,0x30103be5,
0x3bd2344b,0xb60e3924,0xb865bbf6,0x3c0037bd,0x3b2c330f,0x33eb3b45,0xbbfeb8c7,0x3153b94a,0x3a193185,0x3a353c00,0xb7a63232,0xbb9cbb6f,
0x38a82fef,0x3bfe3b32,0x380f3adb,0xb7212884,0x35df2cce,0x3aa23902,0x3c003ba9,0x3a903b9f,0x302926ad,0x35523371,0x382a36dd,0x397d38db,
0xb4633b76,0x2dfbbbdd,0x2dc93c00,0xb457bbde,0xa81f3b98,0xb825bbbd,0x3b353962,0xbbefb122,0x32c63bb5,0xbb68ba21,0x3ab0ae2d,0xa51b3b01,
0x37153bce,0xbbc0b6af,0xa94dba6b,0x3be33a00,0x392e3be1,0xb90c217f,0xbb07bbd9,0x34f3b5eb,0x3a813bf0,0xa9b136ff,0xbae5b820,0xbb2abbff,
0x3b713bfa,0x387a3a3d,0x9fdb349f,0xb894b4db,0x3bef3bff,0x3b8b3bc8,0x3ad53b3a,0x39d23a5c,0x3b2cb5bc,0xba673830,0x396bb95d,0xb8403a5c,
0xb92ebb52,0x3bab385f,0xbbac9648,0x3933b85a,0xb8a8372c,0xb576bbed,0x3bbf3962,0xba093359,0x3b713af7,0xb86a34cf,0xb99dbbf6,0x3abd2f27,
0x3029b845,0x3bfd39df,0x33893a6b,0xbb4cb70a,0xbbf2ba8c,0xb91bbb6c,0x34c3b232,0x3bb339bc,0x35a538ea,0xb3a22ba7,0xb9f8b820,0xbbefbb47,
0x3a933a11,0x3b603b04,0x3bdc3ba9,0x3c003bf9,0x37153b78,0xb8ccbad1,0x39e339f0,0xbac7b8db,0x3a19b676,0xb4933ab3,0xb487bc00,0x3a153ab6,
0xba81bb27,0x3b85305b,0xb40239eb,0xb941bbc9,0xb5df37dd,0xbaacbba1,0x39b3ae2d,0x38503bf3,0x3bef3ac4,0x2ade3970,0xbbc6b8c7,0xb68dbb2f,
0xaf59b899,0x3a2935f7,0x3ba33bd9,0x34573994,0xbb7cba50,0xbbc5bbfc,0xb954badb,0xb010b6a4,0x388e3937,0x363137b2,0x3201349f,0xa51b2d65,
0xb1b63bb5,0x9cb6bbf8,0x32013bf6,0xb5d4bbb0,0xac38bbce,0x38cc3b81,0xbb83b8c7,0x3bcc2c06,0x34e73be1,0xbbabb999,0x3a39b232,0x2d003b59,
0xb83abbf0,0x3b85353a,0x30743adb,0xbbfbb974,0x39c03bfa,0xb86a2ef5,0xbb5ebba9,0x32deb759,0xbaeebbff,0xaadeb830,0x3a7636dd,0x3b7a3bee,
0x3bb23bff,0x391b3ab3,0x2dc9361a,0xb7d2b2ad,0xbbffbbfb,0xbbc5bbed,0xbb35bb87,0xba54bace,0xbbdfb44b,0x3c002d97,0xbbdc2e2d,0x3b73b46f,
0x3bfc330f,0xba67358d,0x3581ba6b,0x33283bfc,0xbb9eb185,0x3493b9b8,0x39073bd9,0xbbfab654,0x3acb2fef,0x35763b90,0xbbecb820,0x2c6ab9da,
0xb990acce,0xbaacbbf4,0x363cb49f,0x3bd03b1b,0x37fe26ad,0x3bfd3ad1,0x38b73b3a,0xb5b13042,0xb46325e4,0xba29b85f,0xbbf8bb65,0xbafbbbd3,
0x281fac9c,0x33a2305b,0x36f4356a,0x38e53835,0x383a3b27,0xb966ba60,0x3a643962,0xbb2ab835,0xb99037dd,0x3219bb18,0x36023bf6,0xba90ba41,
0xbaeebac4,0x3b3728e8,0xb0f03a6b,0xb9d2bb92,0x3463b899,0x3b133b5c,0xb91f3232,0xb8f3bc00,0x3bff3a50,0x30d739fc,0xbb8eb820,0xb7f3bb7f,
0x32c63937,0xb9a1b47b,0xbbd6bba9,0xb5d4ba1d,0xbb2cb9cd,0xbbebbbe6,0xb9e3bb3a,0xb328b805,0xb92eb9c9,0xb79bb884,0xb487b61a,0xad00b1cf,
0xbacb372c,0x39e7b8d6,0xb8d139eb,0x3721bace,0xb9c0baf7,0x3bda3764,0xbb6a2e2d,0x3894b8fd,0x37feb845,0x36e83bfe,0xbbe7b8c7,0x397db52f,
0x3bb23a8c,0xb77a3648,0xba25bbd9,0x3a492311,0xa81f38ea,0xbbe8b94f,0xb546badb,0x3af13599,0xbbd2ba11,0xb9afbbae,0x327cb49f,0x3b733929,
0xb715b982,0x308db109,0x396b36dd,0x3bcc3aeb,0x3a193986,0x3b0a3a9b,0x3bac3b65,0x3bfa3bde,0x30003000,0x30003000,0x30003000,0x30003000,
0x2f643000,0x2a1f2da8,0xaa1f0000,0xaf64ada8,0x2da83000,0xada80000,0xada8b000,0x2da88000,0x2a1f3000,0xaf64ada8,0x2f648000,0xaa1f2da8,
0x00003000,0x8000b000,0x00003000,0x8000b000,0xaa1f3000,0x2f64ada8,0xaf640000,0x2a1f2da8,0xada83000,0x2da88000,0x2da8b000,0xada80000,
0xaf643000,0xaa1f2da8,0x2a1f8000,0x2f64ada8,0x30003000,0x30003000,0x30003000,0x30003000,0xaf64b000,0xaa1fada8,0x2a1f8000,0x2f642da8,
0x2da83000,0xada80000,0xada8b000,0x2da88000,0xaa1fb000,0x2f642da8,0xaf640000,0x2a1fada8,0x00003000,0x8000b000,0x00003000,0x8000b000,
0x2a1fb000,0xaf642da8,0x2f648000,0xaa1fada8,0xada83000,0x2da88000,0x2da8b000,0xada80000,0x2f64b000,0x2a1fada8,0xaa1f0000,0xaf642da8,
0x80008000,0x80008000,0x80008000,0x80008000,0xaa1f8000,0xaf64ada8,0xaf64b000,0xaa1fada8,0xada88000,0xada8b000,0x2da88000,0x2da83000,
0xaf648000,0x2a1fada8,0x2a1f3000,0xaf64ada8,0xb0008000,0x30008000,0xb0008000,0x30008000,0xaf648000,0x2a1f2da8,0x2a1fb000,0xaf642da8,
0xada88000,0xada83000,0x2da88000,0x2da8b000,0xaa1f8000,0xaf642da8,0xaf643000,0xaa1f2da8,0x80008000,0x80008000,0x80008000,0x80008000,
0x2a1f8000,0x2f642da8,0x2f643000,0x2a1f2da8,0xada88000,0xada8b000,0x2da88000,0x2da83000,0x2f648000,0xaa1f2da8,0xaa1fb000,0x2f642da8,
0xb0008000,0x30008000,0xb0008000,0x30008000,0x2f648000,0xaa1fada8,0xaa1f3000,0x2f64ada8,0xada88000,0xada83000,0x2da88000,0x2da8b000,
0x2a1f8000,0x2f64ada8,0x2f64b000,0x2a1fada8,0xb0003000,0xb0003000,0xb0003000,0xb0003000,0xaf643000,0xaa1f2da8,0x2a1f0000,0x2f64ada8,
0xada83000,0x2da80000,0x2da8b000,0xada88000,0xaa1f3000,0x2f64ada8,0xaf648000,0x2a1f2da8,0x80003000,0x0000b000,0x80003000,0x0000b000,
0x2a1f3000,0xaf64ada8,0x2f640000,0xaa1f2da8,0x2da83000,0xada88000,0xada8b000,0x2da80000,0x2f643000,0x2a1f2da8,0xaa1f8000,0xaf64ada8,
0xb0003000,0xb0003000,0xb0003000,0xb0003000,0x2f64b000,0x2a1fada8,0xaa1f8000,0xaf642da8,0xada83000,0x2da80000,0x2da8b000,0xada88000,
0x2a1fb000,0xaf642da8,0x2f640000,0xaa1fada8,0x80003000,0x0000b000,0x80003000,0x0000b000,0xaa1fb000,0x2f642da8,0xaf648000,0x2a1fada8,
0x2da83000,0xada88000,0xada8b000,0x2da80000,0xaf64b000,0xaa1fada8,0x2a1f0000,0x2f642da8,0x80008000,0x80008000,0x80008000,0x80008000,
0x2a1f8000,0x2f64ada8,0x2f64b000,0x2a1fada8,0x2da88000,0x2da8b000,0xada88000,0xada83000,0x2f648000,0xaa1fada8,0xaa1f3000,0x2f64ada8,
0x30008000,0xb0008000,0x30008000,0xb0008000,0x2f648000,0xaa1f2da8,0xaa1fb000,0x2f642da8,0x2da88000,0x2da83000,0xada88000,0xada8b000,
0x2a1f8000,0x2f642da8,0x2f643000,0x2a1f2da8,0x80008000,0x80008000,0x80008000,0x80008000,0xaa1f8000,0xaf642da8,0xaf643000,0xaa1f2da8,
0x2da88000,0x2da8b000,0xada88000,0xada83000,0xaf648000,0x2a1f2da8,0x2a1fb000,0xaf642da8,0x30008000,0xb0008000,0x30008000,0xb0008000,
0xaf648000,0x2a1fada8,0x2a1f3000,0xaf64ada8,0x2da88000,0x2da83000,0xada88000,0xada8b000,0xaa1f8000,0xaf64ada8,0xaf64b000,0xaa1fada8,
0x00000000,0x00000000,0x00000000,0x00000000,0x2a1f0000,0x2f642da8,0x2f643000,0x2a1f2da8,0x2da80000,0x2da83000,0xada80000,0xada8b000,
0x2f640000,0xaa1f2da8,0xaa1fb000,0x2f642da8,0x30000000,0xb0000000,0x30000000,0xb0000000,0x2f640000,0xaa1fada8,0xaa1f3000,0x2f64ada8,
0x2da80000,0x2da8b000,0xada80000,0xada83000,0x2a1f0000,0x2f64ada8,0x2f64b000,0x2a1fada8,0x00000000,0x00000000,0x00000000,0x00000000,
0xaa1f0000,0xaf64ada8,0xaf64b000,0xaa1fada8,0x2da80000,0x2da83000,0xada80000,0xada8b000,0xaf640000,0x2a1fada8,0x2a1f3000,0xaf64ada8,
0x30000000,0xb0000000,0x30000000,0xb0000000,0xaf640000,0x2a1f2da8,0x2a1fb000,0xaf642da8,0x2da80000,0x2da8b000,0xada80000,0xada83000,
0xaa1f0000,0xaf642da8,0xaf643000,0xaa1f2da8,0x30003000,0x30003000,0x30003000,0x30003000,0x2f643000,0x2a1f2da8,0xaa1f0000,0xaf64ada8,
0x2da83000,0xada80000,0xada8b000,0x2da88000,0x2a1f3000,0xaf64ada8,0x2f648000,0xaa1f2da8,0x00003000,0x8000b000,0x00003000,0x8000b000,
0xaa1f3000,0x2f64ada8,0xaf640000,0x2a1f2da8,0xada83000,0x2da88000,0x2da8b000,0xada80000,0xaf643000,0xaa1f2da8,0x2a1f8000,0x2f64ada8,
0x30003000,0x30003000,0x30003000,0x30003000,0xaf64b000,0xaa1fada8,0x2a1f8000,0x2f642da8,0x2da83000,0xada80000,0xada8b000,0x2da88000,
0xaa1fb000,0x2f642da8,0xaf640000,0x2a1fada8,0x00003000,0x8000b000,0x00003000,0x8000b000,0x2a1fb000,0xaf642da8,0x2f648000,0xaa1fada8,
0xada83000,0x2da88000,0x2da8b000,0xada80000,0x2f64b000,0x2a1fada8,0xaa1f0000,0xaf642da8,0x00000000,0x00000000,0x00000000,0x00000000,
0xaa1f0000,0xaf642da8,0xaf643000,0xaa1f2da8,0xada80000,0xada83000,0x2da80000,0x2da8b000,0xaf640000,0x2a1f2da8,0x2a1fb000,0xaf642da8,
0xb0000000,0x30000000,0xb0000000,0x30000000,0xaf640000,0x2a1fada8,0x2a1f3000,0xaf64ada8,0xada80000,0xada8b000,0x2da80000,0x2da83000,
0xaa1f0000,0xaf64ada8,0xaf64b000,0xaa1fada8,0x00000000,0x00000000,0x00000000,0x00000000,0x2a1f0000,0x2f64ada8,0x2f64b000,0x2a1fada8,
0xada80000,0xada83000,0x2da80000,0x2da8b000,0x2f640000,0xaa1fada8,0xaa1f3000,0x2f64ada8,0xb0000000,0x30000000,0xb0000000,0x30000000,
0x2f640000,0xaa1f2da8,0xaa1fb000,0x2f642da8,0xada80000,0xada8b000,0x2da80000,0x2da83000,0x2a1f0000,0x2f642da8,0x2f643000,0x2a1f2da8,
0xb0003000,0xb0003000,0xb0003000,0xb0003000,0xaf643000,0xaa1f2da8,0x2a1f0000,0x2f64ada8,0xada83000,0x2da80000,0x2da8b000,0xada88000,
0xaa1f3000,0x2f64ada8,0xaf648000,0x2a1f2da8,0x80003000,0x0000b000,0x80003000,0x0000b000,0x2a1f3000,0xaf64ada8,0x2f640000,0xaa1f2da8,
0x2da83000,0xada88000,0xada8b000,0x2da80000,0x2f643000,0x2a1f2da8,0xaa1f8000,0xaf64ada8,0xb0003000,0xb0003000,0xb0003000,0xb0003000,
0x2f64b000,0x2a1fada8,0xaa1f8000,0xaf642da8,0xada83000,0x2da80000,0x2da8b000,0xada88000,0x2a1fb000,0xaf642da8,0x2f640000,0xaa1fada8,
0x80003000,0x0000b000,0x80003000,0x0000b000,0xaa1fb000,0x2f642da8,0xaf648000,0x2a1fada8,0x2da83000,0xada88000,0xada8b000,0x2da80000,
0xaf64b000,0xaa1fada8,0x2a1f0000,0x2f642da8};

constexpr int kThreads = 384;
constexpr int kCtas = 128;

constexpr uint32_t SM_BASE = 1024;
constexpr uint32_t QKV_STAGE = 32768;
constexpr uint32_t SLOT = 16384;
constexpr uint32_t SM_KV = 2 * SLOT;
constexpr uint32_t SM_SIG = 131072;
constexpr uint32_t SM_STG = 196608;
constexpr uint32_t SM_Q = SM_STG;
constexpr uint32_t SM_Y0 = 3 * SLOT;
constexpr uint32_t SM_YT = SM_STG + 16384;
constexpr uint32_t SM_TW = SM_STG + 24576, SM_ONES = SM_TW + 2048, SM_F1 = SM_ONES + 2048, SM_F2 = SM_F1 + 4096;
constexpr uint32_t SM_BAR = SM_F2 + 2048;
constexpr uint32_t SM_SC = SM_BAR + 640;
constexpr uint32_t SM_TOTAL = 232448;
constexpr uint32_t A_SLOTS = 0xB2910, B_SLOTS = 0xA7654;

enum Bar { B_QKV_EMPTY = 0, B_QKV_DONE = 4, B_CONV_DONE = 5,
           B_OUT_EMPTY = 8,
           B_H_FULL = 16, B_YIN = 19, B_RDY0 = 21, B_RDY1 = 22, B_ZEROED = 23,
           B_OUT_FULL = 24, B_PREP_FULL = 29,
           B_Q_FULL = 32, B_OT_FREE = 36, B_Y_READY = 38, B_FLAGS1 = 39,
           B_SEG = 40, B_SIG_READY = 44, B_KV_READY = 45,
           B_KVP = 48, B_O_WRITTEN = 49,
           B_PREP_EMPTY = 56,
           B_QKV_FULL = 64, B_STG_FREE = 68, B_FIRST = 69 };
constexpr uint32_t BAR_LOG2 = 0x13200044;

constexpr int KV_SLICE = 640;
constexpr int XCH_FLAG = 2 * SLOT + 17 * KV_SLICE;
constexpr int XCH_BYTES = 11 * 4096;

struct Params {
  CUtensorMap x, w, wk, wo, outa, k, v, q;
  const __nv_bfloat16* shift_k;
  const __nv_bfloat16* ssm_k;
  const __nv_bfloat16* ssm_d;
  const __nv_bfloat16* q_ptr;
  __nv_bfloat16* out_ptr;
  const __nv_bfloat16* wo_ptr;
  int zero;
};

__device__ __align__(128) uint8_t g_xch[kCtas][XCH_BYTES];
__device__ unsigned g_ready, g_epoch[kCtas];

#define TSTAMP(cond, i) do { } while (0)
#define GSTAMP(cond, i) do { } while (0)
#define LOOPSTAMP(id, cond, i) do { } while (0)

constexpr int kSpinLimit = 1 << 17;

DEVI void mbar_init(uint32_t a, uint32_t c) { asm volatile("mbarrier.init.shared::cta.b64 [%0], %1;" :: "r"(a), "r"(c) : "memory"); }
DEVI void mbar_expect(uint32_t a, uint32_t b) { asm volatile("mbarrier.arrive.expect_tx.shared::cta.b64 _, [%0], %1;" :: "r"(a), "r"(b) : "memory"); }
DEVI void mbar_arrive(uint32_t a) { asm volatile("mbarrier.arrive.shared::cta.b64 _, [%0];" :: "r"(a) : "memory"); }
DEVI void mbar_arrive_if(uint32_t a, bool pred) {
  asm volatile("{\n.reg .pred p;\nsetp.ne.b32 p, %1, 0;\n@p mbarrier.arrive.shared::cta.b64 _, [%0];\n}" :: "r"(a), "r"((int)pred) : "memory");
}
DEVI void mbar_wait(uint32_t a, uint32_t parity) {
  asm volatile("{\n.reg .pred p;\n.reg .u32 n;\nmov.u32 n, 0;\nW_LOOP:\n"
               "mbarrier.try_wait.parity.shared::cta.b64 p, [%0], %1;\nadd.u32 n, n, 1;\n"
               "setp.lt.and.u32 p, n, %2, !p;\n@p bra W_LOOP;\n}"
               :: "r"(a), "r"(parity), "n"(kSpinLimit) : "memory");
}
DEVI bool mbar_test(uint32_t a, uint32_t parity) {
  uint32_t ok;
  asm volatile("{\n.reg .pred p;\nmbarrier.test_wait.parity.shared::cta.b64 p, [%1], %2;\nselp.u32 %0, 1, 0, p;\n}" : "=r"(ok) : "r"(a), "r"(parity) : "memory");
  return ok;
}
DEVI bool elect() {
  uint32_t ok;
  asm volatile("{\n.reg .pred p;\nelect.sync _|p, 0xffffffff;\nselp.u32 %0, 1, 0, p;\n}" : "=r"(ok));
  return ok;
}
DEVI void flag_wait(const unsigned* p, unsigned target) {
  int n = 0; unsigned v;
  do {
    asm volatile("ld.acquire.gpu.global.u32 %0, [%1];" : "=r"(v) : "l"(p) : "memory");
  } while ((int)(v - target) < 0 && ++n < kSpinLimit);
}
DEVI void st_relaxed(void* p, uint32_t v) { asm volatile("st.relaxed.gpu.global.b32 [%0], %1;" :: "l"(p), "r"(v) : "memory"); }
DEVI uint32_t ld_relaxed(const void* p) { uint32_t v; asm volatile("ld.relaxed.gpu.global.b32 %0, [%1];" : "=r"(v) : "l"(p) : "memory"); return v; }
DEVI void ld_relaxed4(uint32_t* v, const void* p) {
  asm volatile("ld.relaxed.gpu.global.v4.b32 {%0,%1,%2,%3}, [%4];" : "=r"(v[0]), "=r"(v[1]), "=r"(v[2]), "=r"(v[3]) : "l"(p) : "memory");
}
template <int N> DEVI bool all_arrived(const uint32_t* v) {
  uint32_t m = v[0];
#pragma unroll
  for (int i = 1; i + 1 < N; i += 2) m = __vimax3_u32(m, v[i], v[i + 1]);
  if (N % 2 == 0) m = max(m, v[N - 1]);
  return __all_sync(0xffffffffu, m != 0xffffffffu);
}
DEVI void flag_add(unsigned* p) {
  asm volatile("fence.release.gpu;\nred.relaxed.gpu.global.add.u32 [%0], 1;" :: "l"(p) : "memory");
}
DEVI void fence_async_smem() { asm volatile("fence.proxy.async.shared::cta;" ::: "memory"); }
DEVI void bar_sync(int id, int n) { asm volatile("bar.sync %0, %1;" :: "r"(id), "r"(n) : "memory"); }
DEVI void cluster_arrive() { asm volatile("barrier.cluster.arrive.relaxed.aligned;" ::: "memory"); }
DEVI void cluster_wait() { asm volatile("barrier.cluster.wait.aligned;" ::: "memory"); }
DEVI void wg_fence() { asm volatile("wgmma.fence.sync.aligned;" ::: "memory"); }
DEVI void wg_commit() { asm volatile("wgmma.commit_group.sync.aligned;" ::: "memory"); }
template <int N> DEVI void wg_wait() { asm volatile("wgmma.wait_group.sync.aligned %0;" :: "n"(N) : "memory"); }
template <int N> DEVI void pin(uint32_t* r) {
#pragma unroll
  for (int i = 0; i < N; i++) asm volatile("" : "+r"(r[i]) :: "memory");
}
template <int N> DEVI void pin(float* r) {
#pragma unroll
  for (int i = 0; i < N; i++) asm volatile("" : "+f"(r[i]) :: "memory");
}

DEVI void sched_fence(int zero, int id) { asm volatile("{\n.reg .pred p;\nsetp.eq.b32 p, %0, %1;\nS_LOOP:\n@p st.volatile.shared.b32 [%0], %0;\n@p bra S_LOOP;\n}" :: "r"(zero), "r"(id + 1) : "memory"); }
DEVI void pin_range(float* r, int i0, int i1) {
#pragma unroll
  for (int i = i0; i < i1; i++) asm volatile("" : "+f"(r[i]) :: "memory");
}
DEVI void keep(uint32_t& x) { asm volatile("" : "+r"(x) :: "memory"); }
DEVI void keep(int& x) { asm volatile("" : "+r"(x) :: "memory"); }
template <class T> DEVI void keep(T*& x) { asm volatile("" : "+l"(x) :: "memory"); }

DEVI void tma2d(uint32_t dst, const CUtensorMap* m, int c0, int c1, uint32_t bar) {
  asm volatile("cp.async.bulk.tensor.2d.shared::cluster.global.mbarrier::complete_tx::bytes [%0], [%1, {%3, %4}], [%2];"
               :: "r"(dst), "l"(m), "r"(bar), "r"(c0), "r"(c1) : "memory");
}
DEVI void tma2d_mc(uint32_t dst, const CUtensorMap* m, int c0, int c1, uint32_t bar) {
  asm volatile("cp.async.bulk.tensor.2d.shared::cluster.global.mbarrier::complete_tx::bytes.multicast::cluster [%0], [%1, {%3, %4}], [%2], %5;"
               :: "r"(dst), "l"(m), "r"(bar), "r"(c0), "r"(c1), "h"((uint16_t)3) : "memory");
}
DEVI void tma3d(uint32_t dst, const CUtensorMap* m, int c0, int c1, int c2, uint32_t bar) {
  asm volatile("cp.async.bulk.tensor.3d.shared::cluster.global.mbarrier::complete_tx::bytes [%0], [%1, {%3, %4, %5}], [%2];"
               :: "r"(dst), "l"(m), "r"(bar), "r"(c0), "r"(c1), "r"(c2) : "memory");
}
DEVI void tma3d_mc(uint32_t dst, const CUtensorMap* m, int c0, int c1, int c2, uint32_t bar) {
  asm volatile("cp.async.bulk.tensor.3d.shared::cluster.global.mbarrier::complete_tx::bytes.multicast::cluster [%0], [%1, {%3, %4, %5}], [%2], %6;"
               :: "r"(dst), "l"(m), "r"(bar), "r"(c0), "r"(c1), "r"(c2), "h"((uint16_t)3) : "memory");
}
DEVI void tma2d_store(const CUtensorMap* m, uint32_t src, int c0, int c1) {
  asm volatile("cp.async.bulk.tensor.2d.global.shared::cta.bulk_group [%0, {%2, %3}], [%1];" :: "l"(m), "r"(src), "r"(c0), "r"(c1) : "memory");
}
DEVI void bulk_load(uint32_t dst, const void* src, uint32_t bytes, uint32_t bar) {
  asm volatile("cp.async.bulk.shared::cluster.global.mbarrier::complete_tx::bytes [%0], [%1], %2, [%3];" :: "r"(dst), "l"(src), "r"(bytes), "r"(bar) : "memory");
}
DEVI void bulk_store(void* dst, uint32_t src, uint32_t bytes) {
  asm volatile("cp.async.bulk.global.shared::cta.bulk_group [%0], [%1], %2;" :: "l"(dst), "r"(src), "r"(bytes) : "memory");
}
DEVI uint32_t peer_addr(uint32_t a, int rank) { uint32_t r; asm("mapa.shared::cluster.u32 %0, %1, %2;" : "=r"(r) : "r"(a), "r"(rank)); return r; }
DEVI void bulk_to_peer(uint32_t dst, uint32_t src, uint32_t bytes, uint32_t bar, int rank) {
  asm volatile("cp.async.bulk.shared::cluster.shared::cta.mbarrier::complete_tx::bytes [%0], [%1], %2, [%3];"
               :: "r"(peer_addr(dst, rank)), "r"(src), "r"(bytes), "r"(peer_addr(bar, rank)) : "memory");
}
DEVI void l2_prefetch(const void* p, uint32_t bytes) {
  asm volatile("cp.async.bulk.prefetch.L2.global [%0], %1;" :: "l"(p), "r"(bytes) : "memory");
}
DEVI void l2_prefetch2d(const CUtensorMap* m, int c0, int c1) {
  asm volatile("cp.async.bulk.prefetch.tensor.2d.L2.global [%0, {%1, %2}];" :: "l"(m), "r"(c0), "r"(c1) : "memory");
}
DEVI void l2_prefetch3d(const CUtensorMap* m, int c0, int c1, int c2) {
  asm volatile("cp.async.bulk.prefetch.tensor.3d.L2.global [%0, {%1, %2, %3}];" :: "l"(m), "r"(c0), "r"(c1), "r"(c2) : "memory");
}
DEVI uint32_t clock32() { uint32_t t; asm volatile("mov.u32 %0, %%clock;" : "=r"(t) :: "memory"); return t; }
DEVI void delay(uint32_t cycles) { const uint32_t t = clock32(); while (clock32() - t < cycles) { } }
DEVI void bulk_commit() { asm volatile("cp.async.bulk.commit_group;" ::: "memory"); }
DEVI void bulk_wait_all() { asm volatile("cp.async.bulk.wait_group 0;" ::: "memory"); }
DEVI void bulk_wait_read() { asm volatile("cp.async.bulk.wait_group.read 0;" ::: "memory"); }
DEVI void prefetch_map(const CUtensorMap* m) { asm volatile("prefetch.tensormap [%0];" :: "l"(m) : "memory"); }
DEVI void arrive_both(uint32_t bar, int lane, bool pred = true) {
  asm volatile("{\n.reg .pred p;\n.reg .b32 r;\nsetp.ne.b32 p, %2, 0;\nmapa.shared::cluster.u32 r, %0, %1;\n@p mbarrier.arrive.shared::cluster.b64 _, [r];\n}"
               :: "r"(bar), "r"(lane & 1), "r"((int)(pred && lane < 2)) : "memory");
}

DEVI uint64_t make_desc(uint32_t off, uint32_t lbo, uint32_t sbo, uint32_t mode) {
  const uint32_t lo = (off >> 4) + (SM_BASE >> 4) + ((lbo >> 4) << 16), hi = (sbo >> 4) | (mode << 30);
  return ((uint64_t)hi << 32) | lo;
}
DEVI uint32_t pack_bf16(float lo, float hi) { uint32_t r; asm("cvt.rn.bf16x2.f32 %0, %1, %2;" : "=r"(r) : "f"(hi), "f"(lo)); return r; }
DEVI uint32_t pack_f16(float lo, float hi) { uint32_t r; asm("cvt.rn.f16x2.f32 %0, %1, %2;" : "=r"(r) : "f"(hi), "f"(lo)); return r; }
DEVI void stsm4(uint32_t addr, uint32_t r0, uint32_t r1, uint32_t r2, uint32_t r3) {
  asm volatile("stmatrix.sync.aligned.m8n8.x4.shared.b16 [%0], {%1,%2,%3,%4};" :: "r"(addr), "r"(r0), "r"(r1), "r"(r2), "r"(r3) : "memory");
}
DEVI void stsm2(uint32_t addr, uint32_t r0, uint32_t r1) {
  asm volatile("stmatrix.sync.aligned.m8n8.x2.shared.b16 [%0], {%1,%2};" :: "r"(addr), "r"(r0), "r"(r1) : "memory");
}
DEVI void stsm4_t(uint32_t addr, uint32_t r0, uint32_t r1, uint32_t r2, uint32_t r3) {
  asm volatile("stmatrix.sync.aligned.m8n8.x4.trans.shared.b16 [%0], {%1,%2,%3,%4};" :: "r"(addr), "r"(r0), "r"(r1), "r"(r2), "r"(r3) : "memory");
}
DEVI void ldsm4(uint32_t* r, uint32_t addr) {
  asm volatile("ldmatrix.sync.aligned.m8n8.x4.shared.b16 {%0,%1,%2,%3}, [%4];" : "=r"(r[0]), "=r"(r[1]), "=r"(r[2]), "=r"(r[3]) : "r"(addr) : "memory");
}
DEVI void ldsm4_t(uint32_t* r, uint32_t addr) {
  asm volatile("ldmatrix.sync.aligned.m8n8.x4.trans.shared.b16 {%0,%1,%2,%3}, [%4];" : "=r"(r[0]), "=r"(r[1]), "=r"(r[2]), "=r"(r[3]) : "r"(addr) : "memory");
}
DEVI uint32_t lds32(uint32_t a) { uint32_t v; asm volatile("ld.shared.b32 %0, [%1];" : "=r"(v) : "r"(a) : "memory"); return v; }
DEVI uint4 lds128(uint32_t a) {
  uint4 v; asm volatile("ld.shared.v4.b32 {%0,%1,%2,%3}, [%4];" : "=r"(v.x), "=r"(v.y), "=r"(v.z), "=r"(v.w) : "r"(a) : "memory"); return v;
}
DEVI uint32_t bmul2(uint32_t a, uint32_t b) { uint32_t r; asm("mul.rn.bf16x2 %0, %1, %2;" : "=r"(r) : "r"(a), "r"(b)); return r; }
DEVI uint32_t bfma2(uint32_t a, uint32_t b, uint32_t c) { uint32_t r; asm("fma.rn.bf16x2 %0, %1, %2, %3;" : "=r"(r) : "r"(a), "r"(b), "r"(c)); return r; }
DEVI float bf_lo(uint32_t w) { return __uint_as_float(w << 16); }
DEVI float bf_hi(uint32_t w) { return __uint_as_float(w & 0xffff0000u); }
DEVI uint32_t elu1(float a0, float a1) {
  constexpr float L = 1.4426950408889634f;
  float e0, e1;
  asm("ex2.approx.ftz.f32 %0, %1;" : "=f"(e0) : "f"(-fabsf(fmaf(a0, L, -L))));
  asm("ex2.approx.ftz.f32 %0, %1;" : "=f"(e1) : "f"(-fabsf(fmaf(a1, L, -L))));
  return pack_bf16(fmaxf(e0, a0), fmaxf(e1, a1));
}
DEVI float rcp(float x) { float r; asm("rcp.approx.ftz.f32 %0, %1;" : "=f"(r) : "f"(x)); return r; }
DEVI uint32_t add_eps(uint32_t x) { uint32_t r; asm("add.rn.bf16x2 %0, %1, %2;" : "=r"(r) : "r"(x), "r"(0x35863586u)); return r; }

#define FIN 0
DEVI uint32_t hmul(uint32_t a, uint32_t b) { uint32_t r; asm("mul.rn.f16x2 %0, %1, %2;" : "=r"(r) : "r"(a), "r"(b)); return r; }
DEVI uint32_t hfma(uint32_t a, uint32_t b, uint32_t c) { uint32_t r; asm("fma.rn.f16x2 %0, %1, %2, %3;" : "=r"(r) : "r"(a), "r"(b), "r"(c)); return r; }
DEVI uint32_t hneg(uint32_t a) { uint32_t r; asm("neg.f16x2 %0, %1;" : "=r"(r) : "r"(a)); return r; }
DEVI uint32_t hadd(uint32_t a, uint32_t b) { uint32_t r; asm("add.rn.f16x2 %0, %1, %2;" : "=r"(r) : "r"(a), "r"(b)); return r; }
DEVI uint32_t hsub(uint32_t a, uint32_t b) { uint32_t r; asm("sub.rn.f16x2 %0, %1, %2;" : "=r"(r) : "r"(a), "r"(b)); return r; }
struct Cx { uint32_t re, im; };
DEVI Cx cmul(Cx a, Cx b) { return {hfma(a.re, b.re, hneg(hmul(a.im, b.im))), hfma(a.re, b.im, hmul(a.im, b.re))}; }
DEVI Cx cfma(Cx a, Cx b, Cx c) { return {hfma(a.re, b.re, hfma(hneg(a.im), b.im, c.re)), hfma(a.re, b.im, hfma(a.im, b.re, c.im))}; }
DEVI Cx rot(Cx a, Cx t) {
  const uint32_t x = hfma(hneg(t.re), a.im, a.re), y = hfma(t.im, x, a.im);
  return {hfma(hneg(t.re), y, x), y};
}
struct Fft {
  uint32_t fa[8];
  Cx tw[2];
  uint32_t vld;
  uint64_t dF2a, dF2b;
  uint32_t vst;
  DEVI void stage1(uint32_t* d1, uint32_t slot) const {
    wg_fence();
    fft1_init(d1, fa[0], fa[1], fa[2], fa[3], make_desc(slot, 4096, 1024, 1));
    fft1_acc(d1, fa[4], fa[5], fa[6], fa[7], make_desc(slot + 2048, 4096, 1024, 1));
    wg_commit();
  }
  DEVI void stage2(uint32_t* d, const Cx* t) const {
    wg_fence();
    fft2_init(d, t[0].re, t[1].re, t[2].re, t[3].re, dF2a);
    fft2_acc(d, t[0].im, t[1].im, t[2].im, t[3].im, dF2b);
    wg_commit();
  }
  template <int PR> DEVI void fwd(const uint32_t* d1, uint32_t* d2) const {
    Cx t[4];
#pragma unroll
    for (int e = 0; e < 4; e++) {
      const int j = 8 * (PR & 1) + 4 * (e >> 1) + 2 * (PR >> 1) + (e & 1);
      t[e] = rot({d1[2 * j], d1[2 * j + 1]}, tw[e >> 1]);
    }
    stage2(d2 + 8 * PR, t);
  }
  static DEVI Cx U(const uint32_t* d2, int p, int hi) { return {d2[16 * (p >> 1) + 2 * hi + (p & 1)], d2[16 * (p >> 1) + 4 + 2 * hi + (p & 1)]}; }
  static DEVI Cx H(const uint32_t* d2, int p, int hi) { return U(d2 + 8, p, hi); }
  DEVI void prod01(const uint32_t* d2, Cx* p1, uint32_t* d3) const {
    Cx z[4];
#pragma unroll
    for (int hi = 0; hi < 2; hi++) {
      const Cx p0 = cmul(H(d2, 0, hi), U(d2, 0, hi));
      p1[hi] = cfma(H(d2, 1, hi), U(d2, 0, hi), cmul(H(d2, 0, hi), U(d2, 1, hi)));
      z[2 * hi] = {p0.im, p0.re};
      z[2 * hi + 1] = {hsub(p1[hi].im, p0.re), hadd(p1[hi].re, p0.im)};
    }
    stage2(d3, z);
  }
  DEVI void prod23(const uint32_t* d2, const Cx* p1, uint32_t* d3) const {
    Cx z[4];
#pragma unroll
    for (int hi = 0; hi < 2; hi++) {
      const Cx p2 = cfma(H(d2, 2, hi), U(d2, 0, hi), cfma(H(d2, 0, hi), U(d2, 2, hi), cmul(H(d2, 1, hi), U(d2, 1, hi))));
      const Cx z3 = cfma(H(d2, 3, hi), U(d2, 0, hi), cfma(H(d2, 2, hi), U(d2, 1, hi),
                    cfma(H(d2, 1, hi), U(d2, 2, hi), cfma(H(d2, 0, hi), U(d2, 3, hi), {p2.im, hneg(p2.re)}))));
      z[2 * hi] = {hsub(p2.im, p1[hi].re), hadd(p2.re, p1[hi].im)};
      z[2 * hi + 1] = {z3.im, z3.re};
    }
    stage2(d3 + 8, z);
  }
  template <int PB> DEVI void inv(const uint32_t* d3, uint32_t slot) const {
    Cx v[4];
#pragma unroll
    for (int e = 0; e < 4; e++) {
      const int r = 8 * PB + 2 * (e & 1) + (e >> 1);
      v[e] = rot({d3[r], d3[r + 4]}, tw[e & 1]);
    }
    stsm4(slot + (vst ^ (PB * 64)), v[0].im, v[1].im, v[2].im, v[3].im);
    stsm4(slot + 1024 + (vst ^ (PB * 64)), v[0].re, v[1].re, v[2].re, v[3].re);
  }
  DEVI void last(float* dy, uint32_t slot, int wg, bool fenced = false) const {
    if (!fenced) fence_async_smem();
    bar_sync(2 + wg, 128);
    wg_fence();
    fft3_init(dy, make_desc(slot, 4096, 1024, 1), make_desc(SM_F1, 128, 1024, 0));
#pragma unroll
    for (int ks = 1; ks < 4; ks++) fft3_acc(dy, make_desc(slot + ks * 2048, 4096, 1024, 1), make_desc(SM_F1 + ks * 256, 128, 1024, 0));
    wg_commit();
  }
  static DEVI void store_y(const float* dy, uint32_t a) {
    stsm4_t(a, pack_bf16(dy[0], dy[1]), pack_bf16(dy[2], dy[3]), pack_bf16(dy[4], dy[5]), pack_bf16(dy[6], dy[7]));
    stsm4_t(a + 512, pack_bf16(dy[8], dy[9]), pack_bf16(dy[10], dy[11]), pack_bf16(dy[12], dy[13]), pack_bf16(dy[14], dy[15]));
  }
};
DEVI uint32_t normalize(uint32_t* x, uint32_t dst) {
  uint32_t m = x[0];
#pragma unroll
  for (int i = 1; i < 32; i++) asm("max.xorsign.abs.bf16x2 %0, %0, %1;" : "+r"(m) : "r"(x[i]));
  const uint32_t e = min(__reduce_max_sync(0xffffffffu, max(m & 0x7fffu, (m >> 16) & 0x7fffu)) >> 7, 252u);
  if (e > 140) {
#pragma unroll
    for (int i = 0; i < 32; i++) x[i] = bmul2(x[i], 15u * 0x00800080u);
  }
  const uint32_t sc = (e > 140 ? 253u - e : 141u - e) * 0x00800080u;
#pragma unroll
  for (int i = 0; i < 8; i++) {
    uint32_t y[4];
#pragma unroll
    for (int n = 0; n < 4; n++) {
      const uint32_t w = bmul2(x[4 * i + n], sc);
      y[n] = (w & 0x7fff7fffu) * 7u + w;
    }
    stsm4((dst ^ ((i >> 1) << 4)) + (i & 1) * 2048, y[0], y[1], y[2], y[3]);
  }
  return e;
}
#define RFENCE 1
#define EFENCE 0
#define UDESC 1
#define QF 0
#define KF 1
#define LATE 0
#define PPACE2 PPACE
#define PPACE3 (LATE ? 1 : PPACE)
#define C1DELAY 1
#define SAMP 128
#define PD1 600
#define PD2 500
#define SPLIT0 1
#define TAIL 3
#define DBG 0
#define XPF 3
#define PSTART 5
#define HSTART 3
#define PF0 28
#define PPACE 300
#define FDELAY 150
#define PH0 2
#define QA 4
#define QB 2
#define QC 4
#define S1POS 1

__global__ void __cluster_dims__(2, 1, 1) __launch_bounds__(kThreads, 1)
fused_kernel(const __grid_constant__ Params P) {
  extern __shared__ __align__(1024) uint8_t smem[];
  if (threadIdx.x == 0) { prefetch_map(&P.x); prefetch_map(&P.w); prefetch_map(&P.wk); prefetch_map(blockIdx.x & 1 ? &P.v : &P.k); }
  const uint32_t sb = __shfl_sync(0xffffffffu, (uint32_t)__cvta_generic_to_shared(smem), 0);
  const int tid = threadIdx.x, lane = tid & 31;
  const int warp = __shfl_sync(0xffffffffu, tid >> 5, 0);
  const int bc = blockIdx.x >> 1, late = ((bc - 36) * 37) >> 8;
  const int rp = bc < 4 ? 0 : bc < 36 ? (bc - 4) & 7 : bc - 35 - 7 * late, j = bc < 4 ? 4 + bc : bc < 36 ? (bc - 4) >> 3 : 4 + late;
  const int rho = blockIdx.x & 1, cl = 8 * rp + j, cta = 2 * cl + rho, r = rp * 2 + rho;
  auto bar = [&](int i) { return sb + SM_BAR + 8u * i; };
  TSTAMP(tid == 0, 0); GSTAMP(tid == 0, 30);
  auto load_stage = [&](int it) {
    const uint32_t st = sb + (it & 3) * QKV_STAGE, fb = bar(B_QKV_FULL + (it & 3));
    mbar_expect(fb, QKV_STAGE);
    tma2d_mc(st + 24576 + rho * 4096, &P.wk, 1024 + 128 * j + 64 * rho, 32 * it, fb);
    tma3d_mc(st + 8192 + rho * 8192, &P.w, 0, 32 * it, 32 * rho + 2 * j, fb);
    tma2d(st, &P.x, 32 * it, 128 * r, fb);
  };
  if (warp == 8 && elect()) {
    mbar_init(bar(SPLIT0 ? B_FIRST : B_QKV_FULL), 1);
    mbar_expect(bar(SPLIT0 ? B_FIRST : B_QKV_FULL), SPLIT0 ? 16384 : QKV_STAGE);
    tma2d(sb, &P.x, 0, 128 * r, bar(SPLIT0 ? B_FIRST : B_QKV_FULL));
    tma3d(sb + 24576, &P.w, 0, 0, 16 + 2 * j, bar(SPLIT0 ? B_FIRST : B_QKV_FULL));
    if (SPLIT0) { mbar_init(bar(B_QKV_FULL), 1); mbar_expect(bar(B_QKV_FULL), 16384); }
    tma3d(sb + 8192, &P.w, 0, 0, 2 * j, bar(B_QKV_FULL));
    tma3d(sb + 16384, &P.w, 0, 0, 32 + 2 * j, bar(B_QKV_FULL));
    for (int i = 1; i < 5; i++) mbar_init(bar(B_QKV_FULL + i), 1);
    asm volatile("fence.mbarrier_init.release.cluster;" ::: "memory");
  }
  LOOPSTAMP(3, tid == 256, 13);
  __syncwarp();
  cluster_arrive();

  if (warp < 8) {
    asm volatile("setmaxnreg.inc.sync.aligned.u32 224;");
    const int wg = warp >> 2, wq = warp & 3;
    const int never = __shfl_sync(0xffffffffu, P.zero, 0);
    const uint32_t orow = wq * 2048 + (lane & 15) * 128, ox = ((lane >> 4) ^ (lane & 7)) << 4;
    float aq[64];
    Fft F;
    uint32_t a1[32];
    {
      float ak[64], avq[128];
      auto k_step = [&](uint32_t st, int kk, int acc) {
        mma_tn(ak, make_desc(st + 24576 + wg * 4096 + kk * 2048, 4096, 1024, 1), make_desc(st + kk * 32, 16, 512, 2), acc);
      };
      auto vq_step = [&](uint32_t st, int kk, int acc) {
        mma_nt256(avq, make_desc(st + wg * 4096 + kk * 32, 16, 512, 2), make_desc(st + 8192 + kk * 2048, 4096, 1024, 1), acc);
      };
#pragma unroll
      for (int i = 0; i < 64; i++) { ak[i] = 1.f; avq[i] = 1.f; avq[64 + i] = 0.f; }
      pin<64>(ak); pin<128>(avq);
      cluster_wait();
      cluster_arrive();
      cluster_wait();
      LOOPSTAMP(3, tid == 0, 17);
      if (SPLIT0) {
        mbar_wait(bar(B_FIRST), 0);
        TSTAMP(tid == 0, 1);
        wg_fence();
        k_step(0, 0, 1); k_step(0, 1, 1);
        wg_commit();
        mbar_wait(bar(B_QKV_FULL), 0);
        wg_fence();
        vq_step(0, 0, 1); vq_step(0, 1, 1);
        wg_commit();
      }
#pragma unroll 1
      for (int it = SPLIT0; it < 29; ++it) {
        mbar_wait(bar(B_QKV_FULL + (it & 3)), (it >> 2) & 1);
        TSTAMP(tid == 0 && it == 0, 1); TSTAMP(tid == 0 && it == 4, 6); TSTAMP(tid == 0 && it == 12, 29); TSTAMP(tid == 0 && it == 20, 27); LOOPSTAMP(1, tid == 0 && it < 27, 1 + it); LOOPSTAMP(3, tid == 0 && it < 12, 1 + it);
        const uint32_t st = (it & 3) * QKV_STAGE;
        wg_fence();
        k_step(st, 0, 1);
        wg_commit();
        wg_wait<1>();
        arrive_both(bar(B_QKV_EMPTY + ((it - 1) & 3)), lane, SPLIT0 || it > 0);
        wg_fence();
        vq_step(st, 0, 1);
        k_step(st, 1, 1);
        vq_step(st, 1, 1);
        wg_commit();
      }
#pragma unroll 1
      for (int s = 1; s < 4; ++s) {
        mbar_wait(bar(B_QKV_FULL + s), 1);
        wg_fence();
        k_step(s * QKV_STAGE, 0, 1);
        k_step(s * QKV_STAGE, 1, 1);
        wg_commit();
      }
      uint32_t pk[32];
      auto phi_k = [&](int i0, int i1) {
#pragma unroll
        for (int i = i0; i < i1; i++) { pk[i] = elu1(ak[2 * i], ak[2 * i + 1]); asm volatile("" : "+r"(pk[i]) :: "memory"); }
        if (KF) sched_fence(never, i0);
      };
#pragma unroll
      for (int n = 0; n < 6; n++) {
        wg_fence();
        vq_step((1 + (n >> 1)) * QKV_STAGE, n & 1, 1);
        wg_commit();
        if (n == 0) {
          wg_wait<1>();
          pin<64>(ak);
          TSTAMP(tid == 0, 2);
          bar_sync(1, 256);
        }
        phi_k(n ? PH0 + (32 - PH0) * (n - 1) / 5 : 0, PH0 + (32 - PH0) * n / 5);
      }
      mbar_wait(bar(B_SIG_READY), 0);
      ldsm4_t(F.fa, sb + SM_F1 + (lane >> 4) * 1024 + wq * 256 + (lane & 15) * 16);
      ldsm4_t(F.fa + 4, sb + SM_F1 + 2048 + (lane >> 4) * 1024 + wq * 256 + (lane & 15) * 16);
      const uint4 tw = lds128(sb + SM_TW + (tid & 127) * 16);
      F.tw[0] = {tw.x, tw.y}; F.tw[1] = {tw.z, tw.w};
      F.vld = sb + ((lane >> 4) * 8 + (lane & 7)) * 128 + (((2 * wq + ((lane >> 3) & 1)) ^ (lane & 7)) << 4);
      F.dF2a = make_desc(SM_F2, 128, 512, 0) + (UDESC ? (uint64_t)never * 0x100000001ull : 0); F.dF2b = F.dF2a + 16;
      F.vst = sb + (16 * wq + (lane & 7)) * 128 + (((lane >> 3) ^ (lane & 7)) << 4);
      wg_wait<0>();
      pin<128>(avq);
      if (S1POS == 0) F.stage1(a1, SM_SIG + wg * 8192);
      arrive_both(bar(B_QKV_DONE), lane);
      TSTAMP(tid == 0, 3);
#pragma unroll
      for (int t = 0; t < 8; t++) {
        const float* b = avq + 64 + 8 * t;
        stsm4(sb + (t >> 2) * SLOT + wg * 8192 + orow + (ox ^ ((t & 3) << 5)), pack_bf16(b[0], b[1]), pack_bf16(b[2], b[3]), pack_bf16(b[4], b[5]), pack_bf16(b[6], b[7]));
      }
#pragma unroll
      for (int i = 0; i < 64; i++) aq[i] = avq[i];
      fence_async_smem();
      bar_sync(1, 256);
      float dkv[36];
#pragma unroll
      for (int ks = 0; ks < 8; ks++) {
        const uint32_t va = wg * SLOT + ks * 2048;
        const uint64_t db = make_desc(va, SM_ONES - va, 1024, 1);
        uint32_t a[4];
        pin<4>(pk + 4 * ks);
#pragma unroll
        for (int i = 0; i < 4; i++) a[i] = add_eps(pk[4 * ks + i]);
        wg_fence();
        if (ks == 0) mma_kv_init(dkv, a[0], a[1], a[2], a[3], db);
        else mma_kv_acc(dkv, a[0], a[1], a[2], a[3], db);
      }
      wg_commit();
      uint8_t* box = g_xch[warp * 16 + j] + 2 * SLOT + r * KV_SLICE + lane * 16;
      uint8_t* zbox = box + (lane & 1) * 8 * XCH_BYTES + 512 + (lane & 28) - lane * 16;
      keep(box); keep(zbox);
      if (S1POS == 1) F.stage1(a1, SM_SIG + wg * 8192);
      mbar_wait(bar(B_ZEROED), 0);
      wg_wait<S1POS == 1>();
      pin<36>(dkv);
      if (S1POS == 2) F.stage1(a1, SM_SIG + wg * 8192);
      TSTAMP(tid == 0, 4);
      auto put = [&](const float* d) {
#pragma unroll
        for (int m = 0; m < 2; m++)
          asm volatile("st.relaxed.gpu.global.v4.b32 [%0], {%1,%2,%3,%4};" :: "l"(box + m * 8 * XCH_BYTES), "r"(pack_bf16(d[2 * m], d[2 * m + 1])),
                       "r"(pack_bf16(d[2 * m + 4], d[2 * m + 5])), "r"(pack_bf16(d[2 * m + 8], d[2 * m + 9])), "r"(pack_bf16(d[2 * m + 12], d[2 * m + 13])) : "memory");
      };
      if (wq < 2) put(dkv); else put(dkv + 16);
      asm volatile("{\n.reg .pred p;\nsetp.eq.b32 p, %2, 0;\n@p st.relaxed.gpu.global.b32 [%0], %1;\n}" :: "l"(zbox), "f"(lane & 1 ? dkv[34] : dkv[32]), "r"(lane & 2) : "memory");
      __syncwarp();
      mbar_arrive_if(bar(B_KVP), lane == 0);
      TSTAMP(tid == 0, 5);
    }

    uint32_t pq[32];
    auto phi_q = [&](int i0, int i1) {
      pin_range(aq, 2 * i0, 2 * i1);
#pragma unroll
      for (int i = i0; i < i1; i++) { pq[i] = add_eps(elu1(aq[2 * i], aq[2 * i + 1])); keep(pq[i]); }
      if (QF && i1 > i0) sched_fence(never, 40 + i0);
    };
    uint32_t a2[32];
    float by[16];
    auto conv_pair = [&](uint32_t sa, uint32_t ya, uint32_t first) {
      const uint32_t sc = sa + SLOT;
      uint32_t b1[32], b2[32], a3[16], b3[16];
      float ay[16];
      Cx pa[2], pb[2];
      sched_fence(never, 80);
      F.stage1(b1, sc);
      F.prod01(a2, pa, a3);
      F.prod23(a2, pa, a3);
      wg_wait<1>(); pin<32>(b1); pin<8>(a3);
      F.inv<0>(a3, sa);
      F.fwd<0>(b1, b2);
      wg_wait<1>(); pin<8>(a3 + 8);
      F.inv<1>(a3, sa);
      F.fwd<1>(b1, b2);
      if (EFENCE == 1 && !FIN) fence_async_smem();
      F.fwd<2>(b1, b2);
      if (EFENCE == 2 && !FIN) fence_async_smem();
      F.fwd<3>(b1, b2);
      F.last(ay, sa, wg, EFENCE);
      wg_wait<3>(); pin<16>(b2);
      F.prod01(b2, pb, b3);
      wg_wait<2>(); pin<16>(b2 + 16);
      F.prod23(b2, pb, b3);
      mbar_wait(bar(B_RDY1), first);
      wg_wait<1>(); pin<8>(b3); pin<16>(ay);
      F.inv<0>(b3, sc);
      Fft::store_y(ay, ya);
      wg_wait<0>(); pin<8>(b3 + 8);
      F.inv<1>(b3, sc);
    };
    const bool ylocal = (wq >> 1) == rho;
    const uint32_t yoff = sb + (wq & 1) * 1024 + ((lane ^ wg ^ (2 * rho)) << 4);
    const uint32_t ya0 = yoff + (ylocal ? SM_Y0 + wg * 8192 : SM_YT + wg * 4096), ya1 = (yoff ^ 64) + (ylocal ? SM_SIG + wg * 8192 : SM_YT + wg * 4096);
    auto pair_done = [&](uint32_t ya, int seg) {
      pin<16>(by);
      Fft::store_y(by, (ya ^ 32) + 2048);
      if (!RFENCE) fence_async_smem();
      __syncwarp();
      mbar_arrive_if(bar(B_SEG + 2 * seg + wg), lane == 0);
    };
    const uint32_t s0 = SM_SIG + wg * 8192, s1 = s0 + 2 * SLOT;
    phi_q(0, QA);
    wg_wait<0>(); pin<32>(a1);
    bar_sync(2 + wg, 128);
    F.fwd<0>(a1, a2); phi_q(QA, QA + QB);
    F.fwd<1>(a1, a2); phi_q(QA + QB, QA + 2 * QB);
    F.fwd<2>(a1, a2); phi_q(QA + 2 * QB, QA + 3 * QB);
    F.fwd<3>(a1, a2);
    phi_q(QA + 3 * QB, QA + 3 * QB + QC);
    wg_wait<0>(); pin<32>(a2);
#pragma unroll 1
    for (uint32_t sa = s0;; sa += 2 * SLOT + P.zero) {
    conv_pair(sa, sa == s1 ? ya1 : ya0, sa != s1);
    if (sa == s1) break;
    F.last(by, s0 + SLOT, wg);
    F.stage1(a1, s1);
    phi_q(QA + 3 * QB + QC, 32);
    wg_wait<1>();
    pair_done(ya0, 0);
    TSTAMP(tid == 0, 7); TSTAMP(tid == 128, 10);
    {
      float dn[4][20];
      wg_wait<0>(); pin<32>(a1);
      bar_sync(2 + wg, 128);
      F.fwd<0>(a1, a2); F.fwd<1>(a1, a2); F.fwd<2>(a1, a2); F.fwd<3>(a1, a2);
      mbar_wait(bar(B_KV_READY), 0);
      TSTAMP(tid == 0, 8);
      auto head_mma = [&](int h) {
        wg_fence();
        const uint64_t db = make_desc(SM_KV + h * 2560, 640, 128, 0);
        const uint32_t* a = pq + 8 * h;
        mma_o_init(dn[h], a[0], a[1], a[2], a[3], db);
        mma_o_acc(dn[h], a[4], a[5], a[6], a[7], db + (1280 >> 4));
        wg_commit();
      };
      auto head_store = [&](int h) {
        pin<20>(dn[h]);
        const float i0 = rcp(dn[h][16] + 1e-6f), i1 = rcp(dn[h][18] + 1e-6f);
        const uint32_t p0 = pack_bf16(i0, i0), p1 = pack_bf16(i1, i1);
#pragma unroll
        for (int hf = 0; hf < 2; hf++) {
          const float* a = dn[h] + 8 * hf;
          const uint32_t dst = sb + (h >> 1) * SLOT + wg * 8192 + orow + (ox ^ (((h & 1) * 2 + hf) << 5));
          stsm4(dst, bmul2(pack_bf16(a[0], a[1]), p0), bmul2(pack_bf16(a[2], a[3]), p1), bmul2(pack_bf16(a[4], a[5]), p0), bmul2(pack_bf16(a[6], a[7]), p1));
        }
        if (h & 1) { if (!RFENCE) fence_async_smem(); __syncwarp(); mbar_arrive_if(bar(B_O_WRITTEN + (h >> 1)), lane == 0); }
      };
      head_mma(0); head_mma(1);
      wg_wait<1>(); head_store(0);
      head_mma(2);
      wg_wait<1>(); head_store(1);
      head_mma(3);
      wg_wait<1>(); head_store(2);
      wg_wait<0>(); head_store(3);
      TSTAMP(tid == 0, 9);
      pin<32>(a2);
    }
    }
    if (FIN && RFENCE) mbar_wait(bar(B_OT_FREE), 0);
    F.last(by, s1 + SLOT, wg);

    float acc[64];
    auto stage_mma = [&](int s, int kk, int accumulate) {
      mma_nt(acc, make_desc(((A_SLOTS >> (4 * s)) & 15) * SLOT + wg * 8192 + kk * 32, 16, 1024, 1),
             make_desc(((B_SLOTS >> (4 * s)) & 15) * SLOT + kk * 2048, 8192, 1024, 1), accumulate);
    };
    {
      mbar_wait(bar(B_OUT_FULL), 0);
      wg_fence();
#pragma unroll
      for (int kk = 0; kk < 2; kk++) stage_mma(0, kk, kk);
      wg_commit();
      wg_wait<1>();
      arrive_both(bar(B_CONV_DONE), lane);
      cluster_arrive();
      wg_fence();
#pragma unroll
      for (int kk = 2; kk < 4; kk++) stage_mma(0, kk, 1);
      wg_commit();
      pair_done(ya1, 1);
      TSTAMP(tid == 0, 11); TSTAMP(tid == 128, 12);
      int s = 1, sprev = 0;
      uint32_t ph = 0;
#pragma unroll 1
      for (int ks = 1; ks < 12; ++ks) {
        mbar_wait(bar(B_OUT_FULL + s), ph);
        LOOPSTAMP(2, tid == 0, 1 + ks);
        TSTAMP(tid == 0 && ks == 2, 13); TSTAMP(tid == 0 && ks == 9, 14);
        wg_fence();
        stage_mma(s, 0, 1);
        wg_commit();
        wg_wait<1>();
        arrive_both(bar(B_OUT_EMPTY + sprev), lane);
        wg_fence();
#pragma unroll
        for (int kk = 1; kk < 4; kk++) stage_mma(s, kk, 1);
        wg_commit();
        sprev = s;
        if (++s == 5) { s = 0; ph ^= 1; }
      }
#pragma unroll 1
      for (int ks = 12; ks < 16; ++ks) {
        asm volatile("{\n.reg .pred p;\nsetp.ne.b32 p, %0, 0;\n@p bar.sync 1, 256;\n}" :: "r"((int)(ks == 16 - TAIL && wg)) : "memory");
        mbar_wait(bar(B_OUT_FULL + s), ks == 15);
        wg_fence();
#pragma unroll
        for (int kk = 0; kk < 4; kk++) stage_mma(s, kk, 1);
        wg_commit();
        if (++s == 5) s = 0;
      }
    }
    asm volatile("{\n.reg .pred p;\nsetp.eq.b32 p, %0, 0;\n@p bar.arrive 1, 256;\n}" :: "r"(wg) : "memory");
    wg_wait<0>(); pin<64>(acc);
    TSTAMP(tid == 0, 15); TSTAMP(tid == 128, 16);
#pragma unroll
    for (int hf = 0; hf < 2; hf++) {
      const uint32_t dst = sb + (1 + 8 * hf) * SLOT + wg * 8192;
#pragma unroll
      for (int t = 0; t < 4; t++) {
        const float* a = acc + 32 * hf + 8 * t;
        stsm4(dst + orow + (ox ^ (t << 5)), pack_bf16(a[0], a[1]), pack_bf16(a[2], a[3]), pack_bf16(a[4], a[5]), pack_bf16(a[6], a[7]));
      }
      fence_async_smem();
      __syncwarp();
      if ((!(DBG & 4) || wg) && elect()) { tma2d_store(&P.outa, dst + wq * 2048, 128 * j + 64 * hf, 128 * r + 16 * warp); bulk_commit(); }
    }
    const bool stale = __any_sync(0xffffffffu, acc[0] != acc[0] || acc[2] != acc[2] || (DBG & 256));
    if (elect()) bulk_wait_read();
    TSTAMP(tid == 128, 17);
    __syncwarp();
    cluster_wait();
    TSTAMP(tid == 128, 28); GSTAMP(tid == 128, 31);
    if (stale) {
      __threadfence();
#pragma unroll
      for (int i = 0; i < 64; i++) acc[i] = 0.f;
      const int row = warp * 16 + (lane >> 2);
#pragma unroll 1
      for (int k = 0; k < 1024; k += 2) {
        const uint8_t* src = g_xch[r * 8 + (k >> 7)] + ((k >> 6) & 1) * SLOT + row * 128 + ((((k >> 3) ^ row) & 7) << 4) + (k & 7) * 2;
        uint32_t a[2];
        int n = 0;
        do { a[0] = ld_relaxed(src); a[1] = ld_relaxed(src + 1024); } while (!all_arrived<2>(a) && ++n < kSpinLimit);
#pragma unroll 1
        for (int e = 0; e < 2; e++) {
          const float a0 = e ? bf_hi(a[0]) : bf_lo(a[0]), a1 = e ? bf_hi(a[1]) : bf_lo(a[1]);
          const uint32_t* wrow = reinterpret_cast<const uint32_t*>(P.wo_ptr + (k + e) * 1024 + 128 * j) + (lane & 3);
#pragma unroll
          for (int i = 0; i < 16; i++) {
            const uint32_t w = __ldg(wrow + 4 * i);
            acc[4 * i] += a0 * bf_lo(w); acc[4 * i + 1] += a0 * bf_hi(w);
            acc[4 * i + 2] += a1 * bf_lo(w); acc[4 * i + 3] += a1 * bf_hi(w);
          }
        }
      }
      uint32_t* op = reinterpret_cast<uint32_t*>(P.out_ptr + (128 * r + row) * 2048 + 128 * j) + (lane & 3);
#pragma unroll
      for (int i = 0; i < 32; i++) op[(i & 1) * 8192 + (i >> 1) * 4] = pack_bf16(acc[2 * i], acc[2 * i + 1]);
    }
  } else {
    asm volatile("setmaxnreg.dec.sync.aligned.u32 56;");
    if (warp == 8) {
      cluster_wait();
      cluster_arrive();
      LOOPSTAMP(3, tid == 256, 15);
#pragma unroll 1
      for (int it = 1; it < 4; it++) if (elect()) load_stage(it);
      LOOPSTAMP(3, tid == 256, 16);
      __syncwarp();
      cluster_wait();
    } else {
      if (elect()) {
#pragma unroll 1
        for (int g = warp - 9; g < 8; g += 3)
          for (int i = 0; i < 8; i++) mbar_init(bar(8 * g + i), 1u << ((BAR_LOG2 >> (4 * g)) & 7));
        if (warp == 11) for (int i = 0; i < 6; i++) mbar_expect(bar(B_H_FULL + i), i < 2 ? 12288 : i < 5 ? 8192 : 16);
        asm volatile("fence.mbarrier_init.release.cluster;" ::: "memory");
      }
      LOOPSTAMP(3, tid == 288, 14);
      __syncwarp();
      cluster_wait();
      cluster_arrive();
#pragma unroll
      for (int i = 0; i < 3; i++) asm volatile("st.shared.v4.b32 [%0], {%1,%1,%1,%1};" :: "r"(sb + SM_F1 + i * 1536 + (tid - 288) * 16), "r"(0xffffffffu) : "memory");
      fence_async_smem();
      asm volatile("bar.arrive 5, 128;" ::: "memory");
      if ((sb & 0xffffff) != SM_BASE) __trap();
      cluster_wait();
    }
    auto chunk = [&](int ks) { const int c = ks >= 9, t = ks - 2 - 7 * c; return ks < 2 ? 2 * j + ks : 2 * (t + (t >= j)) + c; };
    auto load_q = [&](int n) {
      mbar_expect(bar(B_Q_FULL + (n & 3)), 4096);
      tma2d(sb + SM_Q + (n & 3) * 4096, &P.q, cl * 16, rho * 1024 + n * 128, bar(B_Q_FULL + (n & 3)));
    };
    auto load_wo = [&](uint32_t dst, int c, uint32_t bytes, uint32_t fb) {
      mbar_expect(fb, bytes);
      tma2d_mc(dst + rho * 8192, &P.wo, 128 * j + 64 * rho, c * 64, fb);
    };
    uint8_t* const xch = g_xch[r * 8 + j];
    if (warp == 8) {
      int ck = 0, cw = 0, cph = 1;
      const CUtensorMap* kvmap = rho ? &P.v : &P.k;
#pragma unroll 1
      for (int it = 4 - XPF; it < 32 || (ck < 20 && it < kSpinLimit); ++it) {
        if (it >= 4 && it < 32) {
          mbar_wait(bar(B_QKV_EMPTY + (it & 3)), ((it >> 2) - 1) & 1);
          if (elect()) load_stage(it);
          LOOPSTAMP(3, lane == 0 && it < 12, 15 + it);
        }
        if (it < 32 - XPF) {
          if (((it + XPF) & 7) == rp && elect()) {
            l2_prefetch2d(&P.wk, 1024 + 128 * j + 64 * rho, 32 * (it + XPF));
            l2_prefetch3d(&P.w, 0, 32 * (it + XPF), 32 * rho + 2 * j);
          }
          if (((it + XPF) & 7) == j && elect()) l2_prefetch2d(&P.x, 32 * (it + XPF), 128 * r);
        }
        const int n = it - HSTART;
        if (n >= 0 && n < 8) {
          if (elect()) bulk_load(sb + SM_SIG + n * 8192 + 4096, P.ssm_k + (size_t)(cta * 8 + n) * 2048, 4096, bar(B_H_FULL + (n >= 3) + (n >= 6)));
        } else if (n >= 8 && n < 19) {
          if (n == 8) bar_sync(5, 128);
          if (elect()) bulk_store(xch + (n - 8) * 4096, sb + SM_F1, 4096);
        } else if (it >= PF0 && it < PF0 + 4) {
          if (elect()) l2_prefetch(it < PF0 + 2 ? P.wo_ptr + cta * 8192 + (it - PF0) * 4096 : P.q_ptr + (512 + (it - PF0 - 2) * 1024 + cta * 4) * 1024, 8192);
        }
        if (ck < 16 && it >= PSTART && __all_sync(0xffffffffu, mbar_test(bar(B_PREP_EMPTY + cw), cph))) {
          if (elect()) {
            mbar_expect(bar(B_PREP_FULL + cw), 8704);
            tma3d_mc(sb + SM_STG + cw * 8704 + rho * 4608, kvmap, cl * 16, ck * 8 - 1 + rho, 0, bar(B_PREP_FULL + cw));
          }
          ++ck;
          if (++cw == 3) { cw = 0; cph ^= 1; }
        } else if (ck >= 16 && ck < 20 && __all_sync(0xffffffffu, mbar_test(bar(B_STG_FREE), 0))) {
          if (elect()) load_q(ck - 16);
          ++ck;
        }
      }
      if (elect()) {
        bulk_commit();
        bulk_wait_read();
        mbar_expect(bar(B_SIG_READY), 10240);
        bulk_load(sb + SM_TW, g_tables, 10240, bar(B_SIG_READY));
        flag_add(&g_ready);
        prefetch_map(&P.wo); prefetch_map(&P.outa); prefetch_map(&P.q);
        const unsigned epoch = ld_relaxed(&g_epoch[cta]) + 1;
        g_epoch[cta] = epoch;
        flag_wait(&g_ready, kCtas * epoch);
        mbar_arrive(bar(B_ZEROED));
      }
      __syncwarp();
      mbar_wait(bar(B_QKV_DONE), 0);
#pragma unroll 1
      for (int ks = 0; ks < 4; ++ks) if (elect()) load_wo(sb + (4 + ks) * SLOT, chunk(ks), ks < 2 ? SLOT : 2 * SLOT, bar(B_OUT_FULL + ks));
    } else {
      const int at = tid - 288, aw = warp - 9, ch0 = cta * 8;
      {
        const uint32_t stg = sb + SM_STG + aw * 8704, pf = bar(B_PREP_FULL + aw), pe = bar(B_PREP_EMPTY + aw);
        const uint4 wv = __ldg(reinterpret_cast<const uint4*>(P.shift_k + (ch0 + 2 * (lane & 3)) * 4));
        const float skip = __bfloat162float(P.ssm_d[ch0 + (lane & 7)]);
        const uint32_t w0 = __byte_perm(wv.x, wv.z, 0x5410), w1 = __byte_perm(wv.x, wv.z, 0x7632);
        const uint32_t w2 = __byte_perm(wv.y, wv.w, 0x5410), w3 = __byte_perm(wv.y, wv.w, 0x7632);
        auto swz32 = [](uint32_t a) { return a ^ ((a >> 3) & 16); };
        const uint32_t kl = (lane >> 3) * 288 + (lane & 7) * 32 + rho * 16;
        const uint32_t ka = stg + swz32(kl + 32), kh = stg + swz32(kl + 12 * 288), va = stg + 4608 + swz32(lane * 32 + rho * 16);
        const uint32_t ua = sb + SM_SIG + (lane & 7) * 8192 + (((lane >> 3) ^ (lane & 7)) << 4);
        uint32_t eh = 0;
#pragma unroll 1
        for (int ck = aw, rd = 0; rd < 9; ck += 3, ++rd) {
          if (rd == 6) {
            bar_sync(4, 96);
            if (at == 64) mbar_arrive(bar(B_STG_FREE));
          }
          const int c = rd < 6 ? ck : ck - 18;
          if (c < 8) {
            uint32_t x[32], dst = sb + SM_SIG + c * 8192;
            if (rd < 6) {
              mbar_wait(bar(B_H_FULL + rd), 0);
#pragma unroll
              for (int i = 0; i < 8; i++) ldsm4(x + 4 * i, dst + 4096 + i * 512 + lane * 16);
              const float d = __shfl_sync(0xffffffffu, skip, c);
              if (lane == 0) x[0] = pack_bf16(bf_lo(x[0]) + d, bf_hi(x[0]));
              dst += 4096 + (lane >> 1) * 128 + ((((lane & 1) * 4) ^ ((lane >> 1) & 7)) << 4);
            } else {
#pragma unroll
              for (int i = 0; i < 8; i++) ldsm4_t(x + 4 * i, dst + i * 512 + ((lane ^ c) << 4));
              dst += (lane >> 4) * 1024 + (lane & 7) * 128 + ((((lane >> 1) & 4) ^ (lane & 7)) << 4);
            }
            const uint32_t e = normalize(x, dst);
            if (rd < 6) {
              eh |= e << (8 * rd);
            } else {
              const int f = min(max((int)(e + (eh & 255)) - 125, 0), 254);
              eh >>= 8;
              if (lane == 0) asm volatile("st.shared.b16 [%0], %1;" :: "r"(sb + SM_SC + rho * 16 + 2 * c), "h"((uint16_t)(f << 7)) : "memory");
            }
          }
          if (ck < 16) {
            mbar_wait(pf, rd & 1);
            uint32_t k[20], v[16];
            ldsm4(k, kh);
#pragma unroll
            for (int m = 0; m < 4; m++) { ldsm4(k + 4 + 4 * m, (ka ^ ((m & 1) << 4)) + m * 1152); ldsm4(v + 4 * m, va + m * 1024); }
            arrive_both(pe + ((k[3] | k[4] | k[8] | k[12] | k[16] | v[0] | v[4] | v[8] | v[12]) & P.zero), lane, ck < 13);
#pragma unroll
            for (int m = 0; m < 4; m++) {
              uint32_t u[4];
#pragma unroll
              for (int n = 0; n < 4; n++) {
                const uint32_t* kk = k + 4 + 4 * m + n;
                u[n] = bmul2(bfma2(kk[0], w0, bfma2(kk[-1], w1, bfma2(kk[-2], w2, bmul2(kk[-3], w3)))), v[4 * m + n]);
              }
              stsm4_t((ua ^ (m << 6)) + ck * 256, u[0], u[1], u[2], u[3]);
            }
          }
        }
        fence_async_smem();
        __syncwarp();
        if (lane == 0) mbar_arrive(bar(B_SIG_READY));
        bar_sync(4, 96);
        if (at == 32) {
          const uint4 s = lds128(sb + SM_SC + rho * 16);
          asm volatile("st.async.weak.shared::cluster.mbarrier::complete_tx::bytes.v4.b32 [%0], {%1,%2,%3,%4}, [%5];"
                       :: "r"(peer_addr(sb + SM_SC + rho * 16, rho ^ 1)), "r"(s.x), "r"(s.y), "r"(s.z), "r"(s.w), "r"(peer_addr(bar(B_RDY0), rho ^ 1)) : "memory");
        }
        TSTAMP(at == 0, 20); LOOPSTAMP(4, at == 0, 22);
      }
    }
    __syncwarp();
    {
      const int a4 = warp - 8;
      const uint8_t* part = xch + 2 * SLOT + (lane >> 3) * 4 * KV_SLICE + (a4 * 8 + (lane & 7)) * 16;
      const uint8_t* zpart = xch + 2 * SLOT + (lane & 15) * KV_SLICE + 512 + (a4 * 2 + (lane >> 4)) * 4;
      uint8_t* red = xch + 2 * SLOT + 16 * KV_SLICE + (a4 * 8 + (lane & 7)) * 16 + (lane >> 3) * 4;
      uint8_t* zred = xch + 2 * SLOT + 16 * KV_SLICE + 512 + (a4 * 2 + (lane >> 4)) * 4;
      const uint8_t* all = g_xch[a4 * 32 + j] + 2 * SLOT + 16 * KV_SLICE + lane * 16;
      const uint8_t* zall = all + 512 + (lane & 28) - lane * 16;
      keep(part); keep(zpart); keep(red); keep(zred); keep(all); keep(zall);
      uint32_t v[20];
      int n = 0;
      mbar_wait(bar(B_KVP), 0);
      if (PD1) delay(PD1);
      do {
#pragma unroll
        for (int i = 0; i < 4; i++) ld_relaxed4(v + 4 * i, part + i * KV_SLICE);
        v[16] = ld_relaxed(zpart);
      } while (!all_arrived<17>(v) && ++n < kSpinLimit);
      TSTAMP(tid == 288, 21);
      float lo[4], hi[4], z = __uint_as_float(v[16]);
#pragma unroll
      for (int b = 0; b < 4; b++) {
        lo[b] = (bf_lo(v[b]) + bf_lo(v[4 + b])) + (bf_lo(v[8 + b]) + bf_lo(v[12 + b]));
        hi[b] = (bf_hi(v[b]) + bf_hi(v[4 + b])) + (bf_hi(v[8 + b]) + bf_hi(v[12 + b]));
      }
      const bool u16 = lane & 16, u8 = lane & 8;
#pragma unroll
      for (int b = 0; b < 2; b++) {
        lo[b] = (u16 ? lo[b + 2] : lo[b]) + __shfl_xor_sync(0xffffffffu, u16 ? lo[b] : lo[b + 2], 16);
        hi[b] = (u16 ? hi[b + 2] : hi[b]) + __shfl_xor_sync(0xffffffffu, u16 ? hi[b] : hi[b + 2], 16);
      }
      const float l = (u8 ? lo[1] : lo[0]) + __shfl_xor_sync(0xffffffffu, u8 ? lo[0] : lo[1], 8);
      const float h = (u8 ? hi[1] : hi[0]) + __shfl_xor_sync(0xffffffffu, u8 ? hi[0] : hi[1], 8);
      st_relaxed(red, pack_bf16(l, h));
#pragma unroll
      for (int o = 8; o; o >>= 1) z += __shfl_xor_sync(0xffffffffu, z, o);
      if ((lane & 15) == 0) st_relaxed(zred, pack_bf16(z, z));
      TSTAMP(tid == 288, 22);
      n = 0;
      if (PD2) delay(PD2);
      do {
#pragma unroll
        for (int i = 0; i < 4; i++) {
          ld_relaxed4(v + 4 * i, all + i * 8 * XCH_BYTES);
          v[16 + i] = ld_relaxed(zall + i * 8 * XCH_BYTES);
        }
      } while (!all_arrived<20>(v) && ++n < kSpinLimit);
#pragma unroll
      for (int i = 0; i < 4; i++) {
        const uint32_t dst = sb + SM_KV + (a4 * 4 + i) * 640;
        stsm4(dst + lane * 16, v[4 * i], v[4 * i + 1], v[4 * i + 2], v[4 * i + 3]);
        asm volatile("st.shared.b32 [%0], %1;" :: "r"(dst + 512 + lane * 4), "r"(v[16 + i]) : "memory");
      }
      fence_async_smem();
      __syncwarp();
      if (lane == 0) mbar_arrive(bar(B_KV_READY));
      TSTAMP(tid == 288, 23);
    }
    if (warp != 10) cluster_arrive();
    if (warp == 8) {
      int s = 4;
      uint32_t ph = 1;
#pragma unroll 1
      for (int ks = 4; ks < 16; ++ks) {
        uint32_t fb = bar(B_OUT_FULL + s), dst = sb + ((B_SLOTS >> (4 * s)) & 15) * SLOT;
        int c = chunk(ks);
        keep(fb); keep(dst); keep(c);
        mbar_wait(bar(ks == 4 ? B_CONV_DONE : B_OUT_EMPTY + s), ks == 4 ? 0 : ph);
        if (elect()) load_wo(dst, c, 2 * SLOT, fb);
        if (++s == 5) { s = 0; ph ^= 1; }
      }
    } else {
      auto wait_chunks = [&](unsigned mask) {
        unsigned ready;
        int n = 0;
        do {
          ready = __ballot_sync(0xffffffffu, ld_relaxed(g_xch[r * 8 + ((lane >> 1) & 7)] + XCH_FLAG) + 1 > (lane & 1));
        } while ((~ready & mask) && ++n < kSpinLimit);
        return ready;
      };
      if (warp == 9) {
        if (elect()) {
#pragma unroll 1
          for (int c = 0; c < 2; c++) {
            mbar_wait(bar(B_O_WRITTEN + c), 0);
            TSTAMP(c == 0, 19);
            fence_async_smem();
            bulk_store(xch + c * SLOT, sb + c * SLOT, SLOT);
            bulk_commit();
            bulk_wait_read();
            if (c) mbar_arrive(bar(B_OT_FREE));
            delay(FDELAY);
            st_relaxed(xch + XCH_FLAG, c);
            if (!c) delay(C1DELAY);
            TSTAMP(c == 1, 25);
          }
        }
        __syncwarp();
        wait_chunks(0xaaaa);
        if (lane == 0) mbar_arrive(bar(B_FLAGS1));
      } else if (warp == 10) {
        mbar_wait(bar(B_RDY0), 0);
        mbar_wait(bar(B_QKV_DONE), 0);
#pragma unroll 1
        for (int n = 0; n < 4; n++) {
          const int w = n & 1;
          if (n == 2) for (int i = 0; i < 4; i++) mbar_wait(bar(B_Q_FULL + i), 0);
          mbar_wait(bar(B_SEG + n), 0);
          if (RFENCE) fence_async_smem();
          if (elect()) bulk_to_peer(sb + (n < 2 ? SM_Y0 : SM_SIG) + w * 8192 + 4096, sb + SM_YT + w * 4096, 4096, bar(B_YIN + (n >> 1)), rho ^ 1);
          if (w) {
            mbar_wait(bar(B_YIN + (n >> 1)), 0);
            if (lane == 0) asm volatile("mbarrier.arrive.shared::cluster.b64 _, [%0];" :: "r"(n < 2 ? peer_addr(bar(B_RDY1), rho ^ 1) : bar(B_Y_READY)) : "memory");
          }
        }
        __syncwarp();
        cluster_arrive();
        TSTAMP(lane == 0, 26);
      } else {
        mbar_wait(bar(B_O_WRITTEN), 0);
        unsigned ready = 0;
        int s = 2;
        uint32_t ph = 1;
#pragma unroll 1
        for (int ks = 2; ks < 16; ++ks) {
          const int c = chunk(ks);
          uint32_t fb = bar(B_OUT_FULL + s), dst = sb + ((A_SLOTS >> (4 * s)) & 15) * SLOT;
          uint8_t* src = g_xch[r * 8 + (c >> 1)] + (c & 1) * SLOT;
          keep(fb); keep(dst); keep(src);
          if (ks < 5 || ks == 9) {
            const unsigned need = ks < 4 ? 1u << c : 0x5555u;
            if (ks == 9) mbar_wait(bar(B_FLAGS1), 0);
            else if (~ready & need) ready = wait_chunks(need);
          }
          if (ks == 3 || ks == 5) mbar_wait(bar(ks == 3 ? B_O_WRITTEN + 1 : B_OT_FREE), 0);
          if (ks >= 4) mbar_wait(bar(ks == 4 ? B_CONV_DONE : B_OUT_EMPTY + s), ks == 4 ? 0 : ph);
          if (elect()) bulk_load(dst, src, SLOT, fb);
          TSTAMP(ks == 2 && lane == 0, 18); LOOPSTAMP(2, lane == 0, 11 + ks);
          if (++s == 5) { s = 0; ph ^= 1; }
        }
      }
    }
    if (LATE || warp == 9 || warp == 10) {
      const int yc = (lane & 1) + ((lane >> 2) & 2) + (lane & 2) * 2, ysrc = (lane >> 2) & 1;
      const uint32_t ya = sb + (yc & 4 ? SM_SIG : SM_Y0) + (yc & 1) * 8192 + (yc & 2) * 1024 + (ysrc ^ rho) * 4096 +
                          (lane >> 4) * 128 + ((yc ^ (2 * ysrc)) << 4);
      uint32_t s0, s1;
      mbar_wait(bar(B_Y_READY), 0);
      asm volatile("ld.shared.v2.b32 {%0,%1}, [%2];" : "=r"(s0), "=r"(s1) : "r"(sb + SM_SC + (lane & 3) * 8) : "memory");
#pragma unroll 1
      for (int n = warp == 8 ? 6 : warp == 11 ? 7 : warp - 9; n < 8; n += LATE && n >= 4 ? 8 : 2) {
        __nv_bfloat16* op = P.out_ptr + (rho * 1024 + n * 128 + (lane >> 2)) * 2048 + 1024 + cl * 16 + (lane & 3) * 4;
        const uint32_t qa = sb + SM_Q + (n & 3) * 4096 + lane * 8;
        if (n >= 4 && !(DBG & 1)) mbar_wait(bar(B_Q_FULL + (n & 3)), 1);
#pragma unroll 1
        for (int u0 = 0; u0 < (DBG & 2 ? 0 : 8); u0 += 2) {
          const uint32_t t0 = clock32();
          uint32_t y[2][4], q[2][4];
#pragma unroll
          for (int u = 0; u < 2; u++) {
            ldsm4_t(y[u], (ya ^ ((u0 + u) << 4)) + n * 256);
#pragma unroll
            for (int m = 0; m < 2; m++)
              asm volatile("ld.shared.v2.b32 {%0,%1}, [%2];" : "=r"(q[u][2 * m]), "=r"(q[u][2 * m + 1]) : "r"(qa + (u0 + u) * 512 + m * 256) : "memory");
          }
#pragma unroll
          for (int u = 0; u < 2; u++)
#pragma unroll
            for (int m = 0; m < 2; m++)
              asm volatile("st.global.v2.b32 [%0], {%1,%2};" :: "l"(op + (u0 * 16 + u * 16 + m * 8) * 2048),
                           "r"(bmul2(q[u][2 * m], bmul2(y[u][2 * m], s0))), "r"(bmul2(q[u][2 * m + 1], bmul2(y[u][2 * m + 1], s1))) : "memory");
          while (clock32() - t0 < (n < 4 ? PPACE : n < 6 ? PPACE2 : PPACE3)) { }
        }
        __syncwarp();
        if (n < 4 && !(DBG & 1) && elect()) load_q(n + 4);
      }
      TSTAMP(tid == 320, 24); TSTAMP(tid == 352, 27);
    }
    __syncwarp();
    cluster_wait();
  }
}

typedef CUresult (*EncodeFn)(CUtensorMap*, CUtensorMapDataType, cuuint32_t, void*, const cuuint64_t*, const cuuint64_t*,
                             const cuuint32_t*, const cuuint32_t*, CUtensorMapInterleave, CUtensorMapSwizzle,
                             CUtensorMapL2promotion, CUtensorMapFloatOOBfill);

void encode(EncodeFn fn, CUtensorMap* m, const void* p, int rank, const cuuint64_t* dims, const cuuint64_t* strides,
            const cuuint32_t* box, CUtensorMapSwizzle sw) {
  const cuuint32_t es[3] = {1, 1, 1};
  fn(m, CU_TENSOR_MAP_DATA_TYPE_BFLOAT16, rank, const_cast<void*>(p), dims, strides, box, es, CU_TENSOR_MAP_INTERLEAVE_NONE, sw,
     CU_TENSOR_MAP_L2_PROMOTION_NONE, CU_TENSOR_MAP_FLOAT_OOB_FILL_NONE);
}
void encode2d(EncodeFn fn, CUtensorMap* m, const void* p, uint64_t cols, uint64_t rows, uint32_t bc, uint32_t br, CUtensorMapSwizzle sw) {
  const cuuint64_t dims[2] = {cols, rows}, strides[1] = {cols * 2};
  const cuuint32_t box[2] = {bc, br};
  encode(fn, m, p, 2, dims, strides, box, sw);
}
void encode3d(EncodeFn fn, CUtensorMap* m, const void* p, uint32_t nblk) {
  const cuuint64_t dims[3] = {1024, 128, 16}, strides[2] = {2048 * 16, 2048};
  const cuuint32_t box[3] = {16, nblk, 16};
  encode(fn, m, p, 3, dims, strides, box, CU_TENSOR_MAP_SWIZZLE_32B);
}

}

extern "C" void kernel_launch(void* const* d_in, const int* in_sizes, int n_in, void* d_out, int out_size) {
  static EncodeFn fn = nullptr;
  if (!fn) {
    cudaDriverEntryPointQueryResult qr;
    cudaGetDriverEntryPoint("cuTensorMapEncodeTiled", (void**)&fn, cudaEnableDefault, &qr);
    cudaFuncSetAttribute(fused_kernel, cudaFuncAttributeMaxDynamicSharedMemorySize, SM_TOTAL);
  }
  Params P;
  encode2d(fn, &P.x, d_in[0], 1024, 2048, 32, 128, CU_TENSOR_MAP_SWIZZLE_64B);
  {
    const cuuint64_t dims[3] = {64, 1024, 48}, strides[2] = {6144, 128};
    const cuuint32_t box[3] = {64, 32, 2};
    encode(fn, &P.w, d_in[1], 3, dims, strides, box, CU_TENSOR_MAP_SWIZZLE_128B);
  }
  encode2d(fn, &P.wk, d_in[1], 3072, 1024, 64, 32, CU_TENSOR_MAP_SWIZZLE_128B);
  encode2d(fn, &P.wo, d_in[2], 1024, 1024, 64, 64, CU_TENSOR_MAP_SWIZZLE_128B);
  encode2d(fn, &P.outa, d_out, 2048, 2048, 64, 16, CU_TENSOR_MAP_SWIZZLE_128B);
  encode3d(fn, &P.k, d_in[4], 9);
  encode3d(fn, &P.v, d_in[5], 8);
  encode2d(fn, &P.q, d_in[3], 1024, 2048, 16, 128, CU_TENSOR_MAP_SWIZZLE_NONE);
  P.shift_k = (const __nv_bfloat16*)d_in[6];
  P.ssm_k = (const __nv_bfloat16*)d_in[7];
  P.ssm_d = (const __nv_bfloat16*)d_in[8];
  P.zero = 0;
  P.q_ptr = (const __nv_bfloat16*)d_in[3];
  P.out_ptr = (__nv_bfloat16*)d_out;
  P.wo_ptr = (const __nv_bfloat16*)d_in[2];
  fused_kernel<<<kCtas, kThreads, SM_TOTAL>>>(P);
}
```

```cpp
#include <cuda.h>
#include <cuda_runtime.h>
#include <cuda_bf16.h>
#include <stdint.h>

#define DEVI __device__ __forceinline__

namespace {

DEVI void mma_nt(float* d, uint64_t da, uint64_t db, int sd) {
  asm volatile("{\n.reg .pred p;\nsetp.ne.b32 p, %66, 0;\nwgmma.mma_async.sync.aligned.m64n128k16.f32.bf16.bf16 {%0, %1, %2, %3, %4, %5, %6, %7, %8, %9, %10, %11, %12, %13, %14, %15, %16, %17, %18, %19, %20, %21, %22, %23, %24, %25, %26, %27, %28, %29, %30, %31, %32, %33, %34, %35, %36, %37, %38, %39, %40, %41, %42, %43, %44, %45, %46, %47, %48, %49, %50, %51, %52, %53, %54, %55, %56, %57, %58, %59, %60, %61, %62, %63}, %64, %65, p, 1, 1, 0, 1;\n}\n"
    : "+f"(d[0]), "+f"(d[1]), "+f"(d[2]), "+f"(d[3]), "+f"(d[4]), "+f"(d[5]), "+f"(d[6]), "+f"(d[7]), "+f"(d[8]), "+f"(d[9]), "+f"(d[10]), "+f"(d[11]), "+f"(d[12]), "+f"(d[13]), "+f"(d[14]), "+f"(d[15]), "+f"(d[16]), "+f"(d[17]), "+f"(d[18]), "+f"(d[19]), "+f"(d[20]), "+f"(d[21]), "+f"(d[22]), "+f"(d[23]), "+f"(d[24]), "+f"(d[25]), "+f"(d[26]), "+f"(d[27]), "+f"(d[28]), "+f"(d[29]), "+f"(d[30]), "+f"(d[31]), "+f"(d[32]), "+f"(d[33]), "+f"(d[34]), "+f"(d[35]), "+f"(d[36]), "+f"(d[37]), "+f"(d[38]), "+f"(d[39]), "+f"(d[40]), "+f"(d[41]), "+f"(d[42]), "+f"(d[43]), "+f"(d[44]), "+f"(d[45]), "+f"(d[46]), "+f"(d[47]), "+f"(d[48]), "+f"(d[49]), "+f"(d[50]), "+f"(d[51]), "+f"(d[52]), "+f"(d[53]), "+f"(d[54]), "+f"(d[55]), "+f"(d[56]), "+f"(d[57]), "+f"(d[58]), "+f"(d[59]), "+f"(d[60]), "+f"(d[61]), "+f"(d[62]), "+f"(d[63])
    : "l"(da), "l"(db), "r"(sd));
}
DEVI void mma_tn(float* d, uint64_t da, uint64_t db, int sd) {
  asm volatile("{\n.reg .pred p;\nsetp.ne.b32 p, %66, 0;\nwgmma.mma_async.sync.aligned.m64n128k16.f32.bf16.bf16 {%0, %1, %2, %3, %4, %5, %6, %7, %8, %9, %10, %11, %12, %13, %14, %15, %16, %17, %18, %19, %20, %21, %22, %23, %24, %25, %26, %27, %28, %29, %30, %31, %32, %33, %34, %35, %36, %37, %38, %39, %40, %41, %42, %43, %44, %45, %46, %47, %48, %49, %50, %51, %52, %53, %54, %55, %56, %57, %58, %59, %60, %61, %62, %63}, %64, %65, p, 1, 1, 1, 0;\n}\n"
    : "+f"(d[0]), "+f"(d[1]), "+f"(d[2]), "+f"(d[3]), "+f"(d[4]), "+f"(d[5]), "+f"(d[6]), "+f"(d[7]), "+f"(d[8]), "+f"(d[9]), "+f"(d[10]), "+f"(d[11]), "+f"(d[12]), "+f"(d[13]), "+f"(d[14]), "+f"(d[15]), "+f"(d[16]), "+f"(d[17]), "+f"(d[18]), "+f"(d[19]), "+f"(d[20]), "+f"(d[21]), "+f"(d[22]), "+f"(d[23]), "+f"(d[24]), "+f"(d[25]), "+f"(d[26]), "+f"(d[27]), "+f"(d[28]), "+f"(d[29]), "+f"(d[30]), "+f"(d[31]), "+f"(d[32]), "+f"(d[33]), "+f"(d[34]), "+f"(d[35]), "+f"(d[36]), "+f"(d[37]), "+f"(d[38]), "+f"(d[39]), "+f"(d[40]), "+f"(d[41]), "+f"(d[42]), "+f"(d[43]), "+f"(d[44]), "+f"(d[45]), "+f"(d[46]), "+f"(d[47]), "+f"(d[48]), "+f"(d[49]), "+f"(d[50]), "+f"(d[51]), "+f"(d[52]), "+f"(d[53]), "+f"(d[54]), "+f"(d[55]), "+f"(d[56]), "+f"(d[57]), "+f"(d[58]), "+f"(d[59]), "+f"(d[60]), "+f"(d[61]), "+f"(d[62]), "+f"(d[63])
    : "l"(da), "l"(db), "r"(sd));
}
DEVI void mma_own_init(float* d, uint32_t a0, uint32_t a1, uint32_t a2, uint32_t a3, uint64_t db) {
  asm volatile("wgmma.mma_async.sync.aligned.m64n128k16.f32.bf16.bf16 {%0, %1, %2, %3, %4, %5, %6, %7, %8, %9, %10, %11, %12, %13, %14, %15, %16, %17, %18, %19, %20, %21, %22, %23, %24, %25, %26, %27, %28, %29, %30, %31, %32, %33, %34, %35, %36, %37, %38, %39, %40, %41, %42, %43, %44, %45, %46, %47, %48, %49, %50, %51, %52, %53, %54, %55, %56, %57, %58, %59, %60, %61, %62, %63}, {%64,%65,%66,%67}, %68, 0, 1, 1, 1;\n"
    : "=f"(d[0]), "=f"(d[1]), "=f"(d[2]), "=f"(d[3]), "=f"(d[4]), "=f"(d[5]), "=f"(d[6]), "=f"(d[7]), "=f"(d[8]), "=f"(d[9]), "=f"(d[10]), "=f"(d[11]), "=f"(d[12]), "=f"(d[13]), "=f"(d[14]), "=f"(d[15]), "=f"(d[16]), "=f"(d[17]), "=f"(d[18]), "=f"(d[19]), "=f"(d[20]), "=f"(d[21]), "=f"(d[22]), "=f"(d[23]), "=f"(d[24]), "=f"(d[25]), "=f"(d[26]), "=f"(d[27]), "=f"(d[28]), "=f"(d[29]), "=f"(d[30]), "=f"(d[31]), "=f"(d[32]), "=f"(d[33]), "=f"(d[34]), "=f"(d[35]), "=f"(d[36]), "=f"(d[37]), "=f"(d[38]), "=f"(d[39]), "=f"(d[40]), "=f"(d[41]), "=f"(d[42]), "=f"(d[43]), "=f"(d[44]), "=f"(d[45]), "=f"(d[46]), "=f"(d[47]), "=f"(d[48]), "=f"(d[49]), "=f"(d[50]), "=f"(d[51]), "=f"(d[52]), "=f"(d[53]), "=f"(d[54]), "=f"(d[55]), "=f"(d[56]), "=f"(d[57]), "=f"(d[58]), "=f"(d[59]), "=f"(d[60]), "=f"(d[61]), "=f"(d[62]), "=f"(d[63])
    : "r"(a0), "r"(a1), "r"(a2), "r"(a3), "l"(db));
}
DEVI void mma_own_acc(float* d, uint32_t a0, uint32_t a1, uint32_t a2, uint32_t a3, uint64_t db) {
  asm volatile("wgmma.mma_async.sync.aligned.m64n128k16.f32.bf16.bf16 {%0, %1, %2, %3, %4, %5, %6, %7, %8, %9, %10, %11, %12, %13, %14, %15, %16, %17, %18, %19, %20, %21, %22, %23, %24, %25, %26, %27, %28, %29, %30, %31, %32, %33, %34, %35, %36, %37, %38, %39, %40, %41, %42, %43, %44, %45, %46, %47, %48, %49, %50, %51, %52, %53, %54, %55, %56, %57, %58, %59, %60, %61, %62, %63}, {%64,%65,%66,%67}, %68, 1, 1, 1, 1;\n"
    : "+f"(d[0]), "+f"(d[1]), "+f"(d[2]), "+f"(d[3]), "+f"(d[4]), "+f"(d[5]), "+f"(d[6]), "+f"(d[7]), "+f"(d[8]), "+f"(d[9]), "+f"(d[10]), "+f"(d[11]), "+f"(d[12]), "+f"(d[13]), "+f"(d[14]), "+f"(d[15]), "+f"(d[16]), "+f"(d[17]), "+f"(d[18]), "+f"(d[19]), "+f"(d[20]), "+f"(d[21]), "+f"(d[22]), "+f"(d[23]), "+f"(d[24]), "+f"(d[25]), "+f"(d[26]), "+f"(d[27]), "+f"(d[28]), "+f"(d[29]), "+f"(d[30]), "+f"(d[31]), "+f"(d[32]), "+f"(d[33]), "+f"(d[34]), "+f"(d[35]), "+f"(d[36]), "+f"(d[37]), "+f"(d[38]), "+f"(d[39]), "+f"(d[40]), "+f"(d[41]), "+f"(d[42]), "+f"(d[43]), "+f"(d[44]), "+f"(d[45]), "+f"(d[46]), "+f"(d[47]), "+f"(d[48]), "+f"(d[49]), "+f"(d[50]), "+f"(d[51]), "+f"(d[52]), "+f"(d[53]), "+f"(d[54]), "+f"(d[55]), "+f"(d[56]), "+f"(d[57]), "+f"(d[58]), "+f"(d[59]), "+f"(d[60]), "+f"(d[61]), "+f"(d[62]), "+f"(d[63])
    : "r"(a0), "r"(a1), "r"(a2), "r"(a3), "l"(db));
}
DEVI void mma_nt256(float* d, uint64_t da, uint64_t db, int sd) {
  asm volatile("{\n.reg .pred p;\nsetp.ne.b32 p, %130, 0;\nwgmma.mma_async.sync.aligned.m64n256k16.f32.bf16.bf16 {%0, %1, %2, %3, %4, %5, %6, %7, %8, %9, %10, %11, %12, %13, %14, %15, %16, %17, %18, %19, %20, %21, %22, %23, %24, %25, %26, %27, %28, %29, %30, %31, %32, %33, %34, %35, %36, %37, %38, %39, %40, %41, %42, %43, %44, %45, %46, %47, %48, %49, %50, %51, %52, %53, %54, %55, %56, %57, %58, %59, %60, %61, %62, %63, %64, %65, %66, %67, %68, %69, %70, %71, %72, %73, %74, %75, %76, %77, %78, %79, %80, %81, %82, %83, %84, %85, %86, %87, %88, %89, %90, %91, %92, %93, %94, %95, %96, %97, %98, %99, %100, %101, %102, %103, %104, %105, %106, %107, %108, %109, %110, %111, %112, %113, %114, %115, %116, %117, %118, %119, %120, %121, %122, %123, %124, %125, %126, %127}, %128, %129, p, 1, 1, 0, 1;\n}\n"
    : "+f"(d[0]), "+f"(d[1]), "+f"(d[2]), "+f"(d[3]), "+f"(d[4]), "+f"(d[5]), "+f"(d[6]), "+f"(d[7]), "+f"(d[8]), "+f"(d[9]), "+f"(d[10]), "+f"(d[11]), "+f"(d[12]), "+f"(d[13]), "+f"(d[14]), "+f"(d[15]), "+f"(d[16]), "+f"(d[17]), "+f"(d[18]), "+f"(d[19]), "+f"(d[20]), "+f"(d[21]), "+f"(d[22]), "+f"(d[23]), "+f"(d[24]), "+f"(d[25]), "+f"(d[26]), "+f"(d[27]), "+f"(d[28]), "+f"(d[29]), "+f"(d[30]), "+f"(d[31]), "+f"(d[32]), "+f"(d[33]), "+f"(d[34]), "+f"(d[35]), "+f"(d[36]), "+f"(d[37]), "+f"(d[38]), "+f"(d[39]), "+f"(d[40]), "+f"(d[41]), "+f"(d[42]), "+f"(d[43]), "+f"(d[44]), "+f"(d[45]), "+f"(d[46]), "+f"(d[47]), "+f"(d[48]), "+f"(d[49]), "+f"(d[50]), "+f"(d[51]), "+f"(d[52]), "+f"(d[53]), "+f"(d[54]), "+f"(d[55]), "+f"(d[56]), "+f"(d[57]), "+f"(d[58]), "+f"(d[59]), "+f"(d[60]), "+f"(d[61]), "+f"(d[62]), "+f"(d[63]), "+f"(d[64]), "+f"(d[65]), "+f"(d[66]), "+f"(d[67]), "+f"(d[68]), "+f"(d[69]), "+f"(d[70]), "+f"(d[71]), "+f"(d[72]), "+f"(d[73]), "+f"(d[74]), "+f"(d[75]), "+f"(d[76]), "+f"(d[77]), "+f"(d[78]), "+f"(d[79]), "+f"(d[80]), "+f"(d[81]), "+f"(d[82]), "+f"(d[83]), "+f"(d[84]), "+f"(d[85]), "+f"(d[86]), "+f"(d[87]), "+f"(d[88]), "+f"(d[89]), "+f"(d[90]), "+f"(d[91]), "+f"(d[92]), "+f"(d[93]), "+f"(d[94]), "+f"(d[95]), "+f"(d[96]), "+f"(d[97]), "+f"(d[98]), "+f"(d[99]), "+f"(d[100]), "+f"(d[101]), "+f"(d[102]), "+f"(d[103]), "+f"(d[104]), "+f"(d[105]), "+f"(d[106]), "+f"(d[107]), "+f"(d[108]), "+f"(d[109]), "+f"(d[110]), "+f"(d[111]), "+f"(d[112]), "+f"(d[113]), "+f"(d[114]), "+f"(d[115]), "+f"(d[116]), "+f"(d[117]), "+f"(d[118]), "+f"(d[119]), "+f"(d[120]), "+f"(d[121]), "+f"(d[122]), "+f"(d[123]), "+f"(d[124]), "+f"(d[125]), "+f"(d[126]), "+f"(d[127])
    : "l"(da), "l"(db), "r"(sd));
}
DEVI void mma_kv_init(float* d, uint32_t a0, uint32_t a1, uint32_t a2, uint32_t a3, uint64_t db) {
  asm volatile("wgmma.mma_async.sync.aligned.m64n72k16.f32.bf16.bf16 {%0, %1, %2, %3, %4, %5, %6, %7, %8, %9, %10, %11, %12, %13, %14, %15, %16, %17, %18, %19, %20, %21, %22, %23, %24, %25, %26, %27, %28, %29, %30, %31, %32, %33, %34, %35}, {%36,%37,%38,%39}, %40, 0, 1, 1, 1;\n"
    : "=f"(d[0]), "=f"(d[1]), "=f"(d[2]), "=f"(d[3]), "=f"(d[4]), "=f"(d[5]), "=f"(d[6]), "=f"(d[7]), "=f"(d[8]), "=f"(d[9]), "=f"(d[10]), "=f"(d[11]), "=f"(d[12]), "=f"(d[13]), "=f"(d[14]), "=f"(d[15]), "=f"(d[16]), "=f"(d[17]), "=f"(d[18]), "=f"(d[19]), "=f"(d[20]), "=f"(d[21]), "=f"(d[22]), "=f"(d[23]), "=f"(d[24]), "=f"(d[25]), "=f"(d[26]), "=f"(d[27]), "=f"(d[28]), "=f"(d[29]), "=f"(d[30]), "=f"(d[31]), "=f"(d[32]), "=f"(d[33]), "=f"(d[34]), "=f"(d[35])
    : "r"(a0), "r"(a1), "r"(a2), "r"(a3), "l"(db));
}
DEVI void mma_kv_acc(float* d, uint32_t a0, uint32_t a1, uint32_t a2, uint32_t a3, uint64_t db) {
  asm volatile("wgmma.mma_async.sync.aligned.m64n72k16.f32.bf16.bf16 {%0, %1, %2, %3, %4, %5, %6, %7, %8, %9, %10, %11, %12, %13, %14, %15, %16, %17, %18, %19, %20, %21, %22, %23, %24, %25, %26, %27, %28, %29, %30, %31, %32, %33, %34, %35}, {%36,%37,%38,%39}, %40, 1, 1, 1, 1;\n"
    : "+f"(d[0]), "+f"(d[1]), "+f"(d[2]), "+f"(d[3]), "+f"(d[4]), "+f"(d[5]), "+f"(d[6]), "+f"(d[7]), "+f"(d[8]), "+f"(d[9]), "+f"(d[10]), "+f"(d[11]), "+f"(d[12]), "+f"(d[13]), "+f"(d[14]), "+f"(d[15]), "+f"(d[16]), "+f"(d[17]), "+f"(d[18]), "+f"(d[19]), "+f"(d[20]), "+f"(d[21]), "+f"(d[22]), "+f"(d[23]), "+f"(d[24]), "+f"(d[25]), "+f"(d[26]), "+f"(d[27]), "+f"(d[28]), "+f"(d[29]), "+f"(d[30]), "+f"(d[31]), "+f"(d[32]), "+f"(d[33]), "+f"(d[34]), "+f"(d[35])
    : "r"(a0), "r"(a1), "r"(a2), "r"(a3), "l"(db));
}
DEVI void mma_o_init(float* d, uint32_t a0, uint32_t a1, uint32_t a2, uint32_t a3, uint64_t db) {
  asm volatile("wgmma.mma_async.sync.aligned.m64n40k16.f32.bf16.bf16 {%0, %1, %2, %3, %4, %5, %6, %7, %8, %9, %10, %11, %12, %13, %14, %15, %16, %17, %18, %19}, {%20,%21,%22,%23}, %24, 0, 1, 1, 1;\n"
    : "=f"(d[0]), "=f"(d[1]), "=f"(d[2]), "=f"(d[3]), "=f"(d[4]), "=f"(d[5]), "=f"(d[6]), "=f"(d[7]), "=f"(d[8]), "=f"(d[9]), "=f"(d[10]), "=f"(d[11]), "=f"(d[12]), "=f"(d[13]), "=f"(d[14]), "=f"(d[15]), "=f"(d[16]), "=f"(d[17]), "=f"(d[18]), "=f"(d[19])
    : "r"(a0), "r"(a1), "r"(a2), "r"(a3), "l"(db));
}
DEVI void mma_o_acc(float* d, uint32_t a0, uint32_t a1, uint32_t a2, uint32_t a3, uint64_t db) {
  asm volatile("wgmma.mma_async.sync.aligned.m64n40k16.f32.bf16.bf16 {%0, %1, %2, %3, %4, %5, %6, %7, %8, %9, %10, %11, %12, %13, %14, %15, %16, %17, %18, %19}, {%20,%21,%22,%23}, %24, 1, 1, 1, 1;\n"
    : "+f"(d[0]), "+f"(d[1]), "+f"(d[2]), "+f"(d[3]), "+f"(d[4]), "+f"(d[5]), "+f"(d[6]), "+f"(d[7]), "+f"(d[8]), "+f"(d[9]), "+f"(d[10]), "+f"(d[11]), "+f"(d[12]), "+f"(d[13]), "+f"(d[14]), "+f"(d[15]), "+f"(d[16]), "+f"(d[17]), "+f"(d[18]), "+f"(d[19])
    : "r"(a0), "r"(a1), "r"(a2), "r"(a3), "l"(db));
}
DEVI void fft1_init(uint32_t* d, uint32_t a0, uint32_t a1, uint32_t a2, uint32_t a3, uint64_t db) {
  asm volatile("wgmma.mma_async.sync.aligned.m64n128k16.f16.f16.f16 {%0, %1, %2, %3, %4, %5, %6, %7, %8, %9, %10, %11, %12, %13, %14, %15, %16, %17, %18, %19, %20, %21, %22, %23, %24, %25, %26, %27, %28, %29, %30, %31}, {%32,%33,%34,%35}, %36, 0, 1, 1, 1;\n"
    : "=r"(d[0]), "=r"(d[1]), "=r"(d[2]), "=r"(d[3]), "=r"(d[4]), "=r"(d[5]), "=r"(d[6]), "=r"(d[7]), "=r"(d[8]), "=r"(d[9]), "=r"(d[10]), "=r"(d[11]), "=r"(d[12]), "=r"(d[13]), "=r"(d[14]), "=r"(d[15]), "=r"(d[16]), "=r"(d[17]), "=r"(d[18]), "=r"(d[19]), "=r"(d[20]), "=r"(d[21]), "=r"(d[22]), "=r"(d[23]), "=r"(d[24]), "=r"(d[25]), "=r"(d[26]), "=r"(d[27]), "=r"(d[28]), "=r"(d[29]), "=r"(d[30]), "=r"(d[31])
    : "r"(a0), "r"(a1), "r"(a2), "r"(a3), "l"(db));
}
DEVI void fft1_acc(uint32_t* d, uint32_t a0, uint32_t a1, uint32_t a2, uint32_t a3, uint64_t db) {
  asm volatile("wgmma.mma_async.sync.aligned.m64n128k16.f16.f16.f16 {%0, %1, %2, %3, %4, %5, %6, %7, %8, %9, %10, %11, %12, %13, %14, %15, %16, %17, %18, %19, %20, %21, %22, %23, %24, %25, %26, %27, %28, %29, %30, %31}, {%32,%33,%34,%35}, %36, 1, 1, 1, 1;\n"
    : "+r"(d[0]), "+r"(d[1]), "+r"(d[2]), "+r"(d[3]), "+r"(d[4]), "+r"(d[5]), "+r"(d[6]), "+r"(d[7]), "+r"(d[8]), "+r"(d[9]), "+r"(d[10]), "+r"(d[11]), "+r"(d[12]), "+r"(d[13]), "+r"(d[14]), "+r"(d[15]), "+r"(d[16]), "+r"(d[17]), "+r"(d[18]), "+r"(d[19]), "+r"(d[20]), "+r"(d[21]), "+r"(d[22]), "+r"(d[23]), "+r"(d[24]), "+r"(d[25]), "+r"(d[26]), "+r"(d[27]), "+r"(d[28]), "+r"(d[29]), "+r"(d[30]), "+r"(d[31])
    : "r"(a0), "r"(a1), "r"(a2), "r"(a3), "l"(db));
}
DEVI void fft2_init(uint32_t* d, uint32_t a0, uint32_t a1, uint32_t a2, uint32_t a3, uint64_t db) {
  asm volatile("wgmma.mma_async.sync.aligned.m64n32k16.f16.f16.f16 {%0, %1, %2, %3, %4, %5, %6, %7}, {%8,%9,%10,%11}, %12, 0, 1, 1, 0;\n"
    : "=r"(d[0]), "=r"(d[1]), "=r"(d[2]), "=r"(d[3]), "=r"(d[4]), "=r"(d[5]), "=r"(d[6]), "=r"(d[7])
    : "r"(a0), "r"(a1), "r"(a2), "r"(a3), "l"(db));
}
DEVI void fft2_acc(uint32_t* d, uint32_t a0, uint32_t a1, uint32_t a2, uint32_t a3, uint64_t db) {
  asm volatile("wgmma.mma_async.sync.aligned.m64n32k16.f16.f16.f16 {%0, %1, %2, %3, %4, %5, %6, %7}, {%8,%9,%10,%11}, %12, 1, 1, 1, 0;\n"
    : "+r"(d[0]), "+r"(d[1]), "+r"(d[2]), "+r"(d[3]), "+r"(d[4]), "+r"(d[5]), "+r"(d[6]), "+r"(d[7])
    : "r"(a0), "r"(a1), "r"(a2), "r"(a3), "l"(db));
}
DEVI void fft1s_init(uint32_t* d, uint64_t da, uint64_t db) {
  asm volatile("wgmma.mma_async.sync.aligned.m64n128k16.f16.f16.f16 {%0, %1, %2, %3, %4, %5, %6, %7, %8, %9, %10, %11, %12, %13, %14, %15, %16, %17, %18, %19, %20, %21, %22, %23, %24, %25, %26, %27, %28, %29, %30, %31}, %32, %33, 0, 1, 1, 1, 1;\n"
    : "=r"(d[0]), "=r"(d[1]), "=r"(d[2]), "=r"(d[3]), "=r"(d[4]), "=r"(d[5]), "=r"(d[6]), "=r"(d[7]), "=r"(d[8]), "=r"(d[9]), "=r"(d[10]), "=r"(d[11]), "=r"(d[12]), "=r"(d[13]), "=r"(d[14]), "=r"(d[15]), "=r"(d[16]), "=r"(d[17]), "=r"(d[18]), "=r"(d[19]), "=r"(d[20]), "=r"(d[21]), "=r"(d[22]), "=r"(d[23]), "=r"(d[24]), "=r"(d[25]), "=r"(d[26]), "=r"(d[27]), "=r"(d[28]), "=r"(d[29]), "=r"(d[30]), "=r"(d[31])
    : "l"(da), "l"(db));
}
DEVI void fft1s_acc(uint32_t* d, uint64_t da, uint64_t db) {
  asm volatile("wgmma.mma_async.sync.aligned.m64n128k16.f16.f16.f16 {%0, %1, %2, %3, %4, %5, %6, %7, %8, %9, %10, %11, %12, %13, %14, %15, %16, %17, %18, %19, %20, %21, %22, %23, %24, %25, %26, %27, %28, %29, %30, %31}, %32, %33, 1, 1, 1, 1, 1;\n"
    : "+r"(d[0]), "+r"(d[1]), "+r"(d[2]), "+r"(d[3]), "+r"(d[4]), "+r"(d[5]), "+r"(d[6]), "+r"(d[7]), "+r"(d[8]), "+r"(d[9]), "+r"(d[10]), "+r"(d[11]), "+r"(d[12]), "+r"(d[13]), "+r"(d[14]), "+r"(d[15]), "+r"(d[16]), "+r"(d[17]), "+r"(d[18]), "+r"(d[19]), "+r"(d[20]), "+r"(d[21]), "+r"(d[22]), "+r"(d[23]), "+r"(d[24]), "+r"(d[25]), "+r"(d[26]), "+r"(d[27]), "+r"(d[28]), "+r"(d[29]), "+r"(d[30]), "+r"(d[31])
    : "l"(da), "l"(db));
}
DEVI void fft3_init(float* d, uint32_t a0, uint32_t a1, uint32_t a2, uint32_t a3, uint64_t db) {
  asm volatile("wgmma.mma_async.sync.aligned.m64n32k16.f32.f16.f16 {%0, %1, %2, %3, %4, %5, %6, %7, %8, %9, %10, %11, %12, %13, %14, %15}, {%16,%17,%18,%19}, %20, 0, 1, 1, 0;\n"
    : "=f"(d[0]), "=f"(d[1]), "=f"(d[2]), "=f"(d[3]), "=f"(d[4]), "=f"(d[5]), "=f"(d[6]), "=f"(d[7]), "=f"(d[8]), "=f"(d[9]), "=f"(d[10]), "=f"(d[11]), "=f"(d[12]), "=f"(d[13]), "=f"(d[14]), "=f"(d[15])
    : "r"(a0), "r"(a1), "r"(a2), "r"(a3), "l"(db));
}
DEVI void fft3_acc(float* d, uint32_t a0, uint32_t a1, uint32_t a2, uint32_t a3, uint64_t db) {
  asm volatile("wgmma.mma_async.sync.aligned.m64n32k16.f32.f16.f16 {%0, %1, %2, %3, %4, %5, %6, %7, %8, %9, %10, %11, %12, %13, %14, %15}, {%16,%17,%18,%19}, %20, 1, 1, 1, 0;\n"
    : "+f"(d[0]), "+f"(d[1]), "+f"(d[2]), "+f"(d[3]), "+f"(d[4]), "+f"(d[5]), "+f"(d[6]), "+f"(d[7]), "+f"(d[8]), "+f"(d[9]), "+f"(d[10]), "+f"(d[11]), "+f"(d[12]), "+f"(d[13]), "+f"(d[14]), "+f"(d[15])
    : "r"(a0), "r"(a1), "r"(a2), "r"(a3), "l"(db));
}

__device__ __align__(128) const uint32_t g_tables[2560] = {
0xa11ba1e4,0xa51ba5e4,0x18b61248,0x1cb61648,0x9f12a052,0xa311a452,0x1d7f1bdb,0x217f1fdb,0x9bdb9d7f,0x9fdba17f,0x20521f12,0x24522311,
0x924898b6,0x96489cb6,0x21e4211b,0x25e4251b,0xaa63ab5f,0xae5faf59,0x21e41bdb,0x25e41fdb,0xa86ba967,0xac6aad65,0x26e024e9,0x2ade28e8,
0xa4e9a6e0,0xa8e8aade,0x2967286b,0x2d652c6a,0x9bdba1e4,0x9fdba5e4,0x2b5f2a63,0x2f592e5f,0xadc2aea7,0xb1b6b294,0x254d1f12,0x294d2311,
0xabf6acde,0xafefb0d7,0x2a31286b,0x2e2d2c6a,0xa86baa31,0xac6aae2d,0x2cde2bf6,0x30d72fef,0x9f12a54d,0xa311a94d,0x2ea72dc2,0x329431b6,
0xb02cb0d2,0xb41ab4b7,0x27a9211b,0x2ba7251b,0xadc2af0c,0xb1b6b2f7,0x2c792a63,0x30742e5f,0xaa63ac79,0xae5fb074,0x2f0c2dc2,0x32f731b6,
0xa11ba7a9,0xa51baba7,0x30d2302c,0x34b7341a,0xb17ab257,0xb552b61a,0x290222ad,0x2d0026ad,0xaf8cb09f,0xb371b487,0x2ddc2c2e,0x31cf3029,
0xac2eaddc,0xb029b1cf,0x309f2f8c,0x34873371,0xa2ada902,0xa6adad00,0x3257317a,0x361a3552,0xb2cdb3e3,0xb682b76f,0x2a312420,0x2e2d281f,
0xb0acb1bb,0xb493b58d,0x2f3f2d2a,0x33283122,0xad2aaf3f,0xb122b328,0x31bb30ac,0x358d3493,0xa420aa31,0xa81fae2d,0x33e332cd,0x376f3682,
0xb413b4bc,0xb7a6b85a,0x2b5f24e9,0x2f5928e8,0xb194b2da,0xb56ab68d,0x30522e28,0x343e3219,0xae28b052,0xb219b43e,0x32da3194,0x368d356a,
0xa4e9ab5f,0xa8e8af59,0x34bc3413,0x385a37a6,0xb4c3b58c,0xb85fb8f3,0x2c4725b2,0x304229b1,0xb27eb3fd,0xb63cb785,0x31062f26,0x34e7330f,
0xaf26b106,0xb30fb4e7,0x33fd327e,0x3785363c,0xa5b2ac47,0xa9b1b042,0x358c34c3,0x38f3385f,0xb577b662,0xb8e5b982,0x2cde267b,0x30d72a7a,
0xb36bb493,0xb70ab83a,0x31bb3012,0x358d3402,0xb012b1bb,0xb402b58d,0x3493336b,0x383a370a,0xa67bacde,0xaa7ab0d7,0x36623577,0x398238e5,
0xb630b741,0xb962ba04,0x2d762744,0x316c2b43,0xb42eb52a,0xb7d2b8ad,0x32713092,0x3631347b,0xb092b271,0xb47bb631,0x352a342e,0x38ad37d2,
0xa744ad76,0xab43b16c,0x37413630,0x3a043962,0xb6eeb815,0xb9d6ba7a,0x2e0e2807,0x32012c06,0xb4a7b5c4,0xb84ab91b,0x33293113,0x36d234f3,
0xb113b329,0xb4f3b6d2,0x35c434a7,0x391b384a,0xa807ae0e,0xac06b201,0x381536ee,0x3a7a39d6,0xb7b4b88e,0xba41bae1,0x2ea7286b,0x32942c6a,
0xb523b662,0xb8a8b982,0x33e33194,0x376f356a,0xb194b3e3,0xb56ab76f,0x36623523,0x398238a8,0xa86baea7,0xac6ab294,0x388e37b4,0x3ae13a41,
0xb841b90f,0xbaa2bb3a,0x2f3f28d0,0x33282cce,0xb5a1b705,0xb902b9e3,0x344f3216,0x380535df,0xb216b44f,0xb5dfb805,0x370535a1,0x39e33902,
0xa8d0af3f,0xacceb328,0x390f3841,0x3b3a3aa2,0xb8acb997,0xbaf7bb83,0x2fd82935,0x33ba2d33,0xb621b7ac,0xb958ba3d,0x34ae3298,0x38503654,
0xb298b4ae,0xb654b850,0x37ac3621,0x3a3d3958,0xa935afd8,0xad33b3ba,0x399738ac,0x3b833af7,0xb91cba28,0xbb42bbbc,0x30392999,0x34262d97,
0xb6a4b82d,0xb9aaba90,0x350e331c,0x389936c6,0xb31cb50e,0xb6c6b899,0x382d36a4,0x3a9039aa,0xa999b039,0xad97b426,0x3a28391c,0x3bbc3b42,
0xb992bac3,0xbb81bbe3,0x308529fe,0x346f2dfb,0xb72ab886,0xb9f8badb,0x357033a0,0x38e03737,0xb3a0b570,0xb737b8e0,0x3886372a,0x3adb39f8,
0xa9feb085,0xadfbb46f,0x3ac33992,0x3be33b81,0x39cf3b16,0x3b9c3bf1,0xb0acaa31,0xb493ae2d,0x376f38b4,0x3a1d3afe,0xb5a1b3e3,0xb902b76f,
0x33e335a1,0x376f3902,0xb8b4b76f,0xbafeba1d,0x2a3130ac,0x2e2d3493,0xbb16b9cf,0xbbf1bb9c,0x39563a74,0x3b633bd2,0xb05fa9cc,0xb44badc9,
0x36e73859,0x39d23ab6,0xb53fb35e,0xb8bcb6ff,0x335e353f,0x36ff38bc,0xb859b6e7,0xbab6b9d2,0x29cc305f,0x2dc9344b,0xba74b956,0xbbd2bb63,
0x38e339de,0x3b1e3ba1,0xb012a967,0xb402ad65,0x36623801,0x39823a67,0xb4deb2da,0xb874b68d,0x32da34de,0x368d3874,0xb801b662,0xba67b982,
0x29673012,0x2d653402,0xb9deb8e3,0xbba1bb1e,0x38763952,0x3ace3b60,0xaf8ca902,0xb371ad00,0x35e13758,0x392e3a11,0xb47eb257,0xb82ab61a,
0x3257347e,0x361a382a,0xb758b5e1,0xba11b92e,0x29022f8c,0x2d003371,0xb952b876,0xbb60bace,0x380d38ce,0x3a733b10,0xaef3a89e,0xb2deac9c,
0x356236b3,0x38d639b3,0xb420b1d5,0xb7bdb5a5,0x31d53420,0x35a537bd,0xb6b3b562,0xb9b3b8d6,0x289e2ef3,0x2c9c32de,0xb8ceb80d,0xbb10ba73,
0x37503851,0x3a0d3ab0,0xae5aa839,0xb24bac38,0x34e53613,0x387a394f,0xb386b153,0xb721b52f,0x31533386,0x352f3721,0xb613b4e5,0xb94fb87a,
0x28392e5a,0x2c38324b,0xb851b750,0xbab0ba0d,0x368e37b4,0x399d3a41,0xadc2a7a9,0xb1b6aba7,0x346a3577,0x381a38e5,0xb2cdb0d2,0xb682b4b7,
0x30d232cd,0x34b73682,0xb577b46a,0xb8e5b81a,0x27a92dc2,0x2ba731b6,0xb7b4b68e,0xba41b99d,0x35d236d1,0x392439c5,0xad2aa6e0,0xb122aade,
0x33e334de,0x376f3874,0xb216b052,0xb5dfb43e,0x30523216,0x343e35df,0xb4deb3e3,0xb874b76f,0x26e02d2a,0x2ade3122,0xb6d1b5d2,0xb9c5b924,
0x351c35f6,0x38a3393c,0xac93a617,0xb08daa16,0x32f43448,0x36a437fe,0xb160afa5,0xb53ab389,0x2fa53160,0x3389353a,0xb448b2f4,0xb7feb6a4,
0x26172c93,0x2a16308d,0xb5f6b51c,0xb93cb8a3,0x346a3523,0x381a38a8,0xabf6a54d,0xafefa94d,0x3209336b,0x35d4370a,0xb0acaea7,0xb493b294,
0x2ea730ac,0x32943493,0xb36bb209,0xb70ab5d4,0x254d2bf6,0x294d2fef,0xb523b46a,0xb8a8b81a,0x33783456,0x3715380a,0xaac8a484,0xaec3a884,
0x3120324a,0x34ff360e,0xaff2ada9,0xb3d3b19e,0x2da92ff2,0x319e33d3,0xb24ab120,0xb60eb4ff,0x24842ac8,0x28842ec3,0xb456b378,0xb80ab715,
0x3223331c,0x35eb36c6,0xa999a376,0xad97a776,0x3039312d,0x3426350b,0xae8dacac,0xb27cb0a6,0x2cac2e8d,0x30a6327c,0xb12db039,0xb50bb426,
0x23762999,0x27762d97,0xb31cb223,0xb6c6b5eb,0x30d23194,0x34b7356a,0xa86ba1e4,0xac6aa5e4,0x2ea73012,0x32943402,0xad2aab5f,0xb122af59,
0x2b5f2d2a,0x2f593122,0xb012aea7,0xb402b294,0x21e4286b,0x25e42c6a,0xb194b0d2,0xb56ab4b7,0x2f0c3012,0x32f73402,0xa67ba052,0xaa7aa452,
0x2cde2df5,0x30d731e8,0xab91a967,0xaf8bad65,0x29672b91,0x2d652f8b,0xadf5acde,0xb1e8b0d7,0x2052267b,0x24522a7a,0xb012af0c,0xb402b2f7,
0x2c792d2a,0x30743122,0xa4209d7f,0xa81fa17f,0x2a312b91,0x2e2d2f8b,0xa8d0a6e0,0xacceaade,0x26e028d0,0x2ade2cce,0xab91aa31,0xaf8bae2d,
0x1d7f2420,0x217f281f,0xad2aac79,0xb122b074,0x27a9286b,0x2ba72c6a,0x9f1298b6,0xa3119cb6,0x254d267b,0x294d2a7a,0xa420a1e4,0xa81fa5e4,
0x21e42420,0x25e4281f,0xa67ba54d,0xaa7aa94d,0x18b61f12,0x1cb62311,0xa86ba7a9,0xac6aaba7,0x3f803f80,0x3f803f80,0x3f803f80,0x3f803f80,
0x3f803f80,0x3f803f80,0x3f803f80,0x3f803f80,0x3f803f80,0x3f803f80,0x3f803f80,0x3f803f80,0x3f803f80,0x3f803f80,0x3f803f80,0x3f803f80,
0x3f803f80,0x3f803f80,0x3f803f80,0x3f803f80,0x3f803f80,0x3f803f80,0x3f803f80,0x3f803f80,0x3f803f80,0x3f803f80,0x3f803f80,0x3f803f80,
0x3f803f80,0x3f803f80,0x3f803f80,0x3f803f80,0x3f803f80,0x3f803f80,0x3f803f80,0x3f803f80,0x3f803f80,0x3f803f80,0x3f803f80,0x3f803f80,
0x3f803f80,0x3f803f80,0x3f803f80,0x3f803f80,0x3f803f80,0x3f803f80,0x3f803f80,0x3f803f80,0x3f803f80,0x3f803f80,0x3f803f80,0x3f803f80,
0x3f803f80,0x3f803f80,0x3f803f80,0x3f803f80,0x3f803f80,0x3f803f80,0x3f803f80,0x3f803f80,0x3f803f80,0x3f803f80,0x3f803f80,0x3f803f80,
0x3f803f80,0x3f803f80,0x3f803f80,0x3f803f80,0x3f803f80,0x3f803f80,0x3f803f80,0x3f803f80,0x3f803f80,0x3f803f80,0x3f803f80,0x3f803f80,
0x3f803f80,0x3f803f80,0x3f803f80,0x3f803f80,0x3f803f80,0x3f803f80,0x3f803f80,0x3f803f80,0x3f803f80,0x3f803f80,0x3f803f80,0x3f803f80,
0x3f803f80,0x3f803f80,0x3f803f80,0x3f803f80,0x3f803f80,0x3f803f80,0x3f803f80,0x3f803f80,0x3f803f80,0x3f803f80,0x3f803f80,0x3f803f80,
0x3f803f80,0x3f803f80,0x3f803f80,0x3f803f80,0x3f803f80,0x3f803f80,0x3f803f80,0x3f803f80,0x3f803f80,0x3f803f80,0x3f803f80,0x3f803f80,
0x3f803f80,0x3f803f80,0x3f803f80,0x3f803f80,0x3f803f80,0x3f803f80,0x3f803f80,0x3f803f80,0x3f803f80,0x3f803f80,0x3f803f80,0x3f803f80,
0x3f803f80,0x3f803f80,0x3f803f80,0x3f803f80,0x3f803f80,0x3f803f80,0x3f803f80,0x3f803f80,0x3f803f80,0x3f803f80,0x3f803f80,0x3f803f80,
0x3f803f80,0x3f803f80,0x3f803f80,0x3f803f80,0x3f803f80,0x3f803f80,0x3f803f80,0x3f803f80,0x3f803f80,0x3f803f80,0x3f803f80,0x3f803f80,
0x3f803f80,0x3f803f80,0x3f803f80,0x3f803f80,0x3f803f80,0x3f803f80,0x3f803f80,0x3f803f80,0x3f803f80,0x3f803f80,0x3f803f80,0x3f803f80,
0x3f803f80,0x3f803f80,0x3f803f80,0x3f803f80,0x3f803f80,0x3f803f80,0x3f803f80,0x3f803f80,0x3f803f80,0x3f803f80,0x3f803f80,0x3f803f80,
0x3f803f80,0x3f803f80,0x3f803f80,0x3f803f80,0x3f803f80,0x3f803f80,0x3f803f80,0x3f803f80,0x3f803f80,0x3f803f80,0x3f803f80,0x3f803f80,
0x3f803f80,0x3f803f80,0x3f803f80,0x3f803f80,0x3f803f80,0x3f803f80,0x3f803f80,0x3f803f80,0x3f803f80,0x3f803f80,0x3f803f80,0x3f803f80,
0x3f803f80,0x3f803f80,0x3f803f80,0x3f803f80,0x3f803f80,0x3f803f80,0x3f803f80,0x3f803f80,0x3f803f80,0x3f803f80,0x3f803f80,0x3f803f80,
0x3f803f80,0x3f803f80,0x3f803f80,0x3f803f80,0x3f803f80,0x3f803f80,0x3f803f80,0x3f803f80,0x3f803f80,0x3f803f80,0x3f803f80,0x3f803f80,
0x3f803f80,0x3f803f80,0x3f803f80,0x3f803f80,0x3f803f80,0x3f803f80,0x3f803f80,0x3f803f80,0x3f803f80,0x3f803f80,0x3f803f80,0x3f803f80,
0x3f803f80,0x3f803f80,0x3f803f80,0x3f803f80,0x3f803f80,0x3f803f80,0x3f803f80,0x3f803f80,0x3f803f80,0x3f803f80,0x3f803f80,0x3f803f80,
0x3f803f80,0x3f803f80,0x3f803f80,0x3f803f80,0x3f803f80,0x3f803f80,0x3f803f80,0x3f803f80,0x3f803f80,0x3f803f80,0x3f803f80,0x3f803f80,
0x3f803f80,0x3f803f80,0x3f803f80,0x3f803f80,0x3f803f80,0x3f803f80,0x3f803f80,0x3f803f80,0x3f803f80,0x3f803f80,0x3f803f80,0x3f803f80,
0x3f803f80,0x3f803f80,0x3f803f80,0x3f803f80,0x3f803f80,0x3f803f80,0x3f803f80,0x3f803f80,0x3f803f80,0x3f803f80,0x3f803f80,0x3f803f80,
0x3f803f80,0x3f803f80,0x3f803f80,0x3f803f80,0x3f803f80,0x3f803f80,0x3f803f80,0x3f803f80,0x3f803f80,0x3f803f80,0x3f803f80,0x3f803f80,
0x3f803f80,0x3f803f80,0x3f803f80,0x3f803f80,0x3f803f80,0x3f803f80,0x3f803f80,0x3f803f80,0x3f803f80,0x3f803f80,0x3f803f80,0x3f803f80,
0x3f803f80,0x3f803f80,0x3f803f80,0x3f803f80,0x3f803f80,0x3f803f80,0x3f803f80,0x3f803f80,0x3f803f80,0x3f803f80,0x3f803f80,0x3f803f80,
0x3f803f80,0x3f803f80,0x3f803f80,0x3f803f80,0x3f803f80,0x3f803f80,0x3f803f80,0x3f803f80,0x3f803f80,0x3f803f80,0x3f803f80,0x3f803f80,
0x3f803f80,0x3f803f80,0x3f803f80,0x3f803f80,0x3f803f80,0x3f803f80,0x3f803f80,0x3f803f80,0x3f803f80,0x3f803f80,0x3f803f80,0x3f803f80,
0x3f803f80,0x3f803f80,0x3f803f80,0x3f803f80,0x3f803f80,0x3f803f80,0x3f803f80,0x3f803f80,0x3f803f80,0x3f803f80,0x3f803f80,0x3f803f80,
0x3f803f80,0x3f803f80,0x3f803f80,0x3f803f80,0x3f803f80,0x3f803f80,0x3f803f80,0x3f803f80,0x3f803f80,0x3f803f80,0x3f803f80,0x3f803f80,
0x3f803f80,0x3f803f80,0x3f803f80,0x3f803f80,0x3f803f80,0x3f803f80,0x3f803f80,0x3f803f80,0x3f803f80,0x3f803f80,0x3f803f80,0x3f803f80,
0x3f803f80,0x3f803f80,0x3f803f80,0x3f803f80,0x3f803f80,0x3f803f80,0x3f803f80,0x3f803f80,0x3f803f80,0x3f803f80,0x3f803f80,0x3f803f80,
0x3f803f80,0x3f803f80,0x3f803f80,0x3f803f80,0x3f803f80,0x3f803f80,0x3f803f80,0x3f803f80,0x3f803f80,0x3f803f80,0x3f803f80,0x3f803f80,
0x3f803f80,0x3f803f80,0x3f803f80,0x3f803f80,0x3f803f80,0x3f803f80,0x3f803f80,0x3f803f80,0x3f803f80,0x3f803f80,0x3f803f80,0x3f803f80,
0x3f803f80,0x3f803f80,0x3f803f80,0x3f803f80,0x3f803f80,0x3f803f80,0x3f803f80,0x3f803f80,0x3f803f80,0x3f803f80,0x3f803f80,0x3f803f80,
0x3f803f80,0x3f803f80,0x3f803f80,0x3f803f80,0x3f803f80,0x3f803f80,0x3f803f80,0x3f803f80,0x3f803f80,0x3f803f80,0x3f803f80,0x3f803f80,
0x3f803f80,0x3f803f80,0x3f803f80,0x3f803f80,0x3f803f80,0x3f803f80,0x3f803f80,0x3f803f80,0x3f803f80,0x3f803f80,0x3f803f80,0x3f803f80,
0x3f803f80,0x3f803f80,0x3f803f80,0x3f803f80,0x3f803f80,0x3f803f80,0x3f803f80,0x3f803f80,0x3f803f80,0x3f803f80,0x3f803f80,0x3f803f80,
0x3f803f80,0x3f803f80,0x3f803f80,0x3f803f80,0x3f803f80,0x3f803f80,0x3f803f80,0x3f803f80,0x3f803f80,0x3f803f80,0x3f803f80,0x3f803f80,
0x3f803f80,0x3f803f80,0x3f803f80,0x3f803f80,0x3f803f80,0x3f803f80,0x3f803f80,0x3f803f80,0x3f803f80,0x3f803f80,0x3f803f80,0x3f803f80,
0x3f803f80,0x3f803f80,0x3f803f80,0x3f803f80,0x3f803f80,0x3f803f80,0x3f803f80,0x3f803f80,0x3f803f80,0x3f803f80,0x3f803f80,0x3f803f80,
0x3f803f80,0x3f803f80,0x3f803f80,0x3f803f80,0x3f803f80,0x3f803f80,0x3f803f80,0x3f803f80,0x3f803f80,0x3f803f80,0x3f803f80,0x3f803f80,
0x3f803f80,0x3f803f80,0x3f803f80,0x3f803f80,0x3bf23bff,0x3ba53bd4,0x3b163b65,0x3a493ab6,0x3b7c3bfb,0x38bc3a60,0x2b43356a,0xb7f3b359,
0x3a933bf1,0x9cb63764,0xba9eb785,0xbb73bbf3,0x39463be2,0xb8cc28e8,0xbb42bbc2,0x3328b70a,0x374e3bcf,0xbbabb648,0xaec3baa9,0x3bfa3994,
0x33403bb7,0xbb85b9fc,0x3a64b0be,0x2c6a3b47,0xa4523b9a,0xb86abbae,0x3b6a3911,0xbbd0ad65,0xb4263b78,0x2adebbe6,0x30f03bfd,0xb5b1bbbc,
0x2f5925e4,0x34b73294,0x376f361a,0x38f3385a,0x35a52c9c,0x3a7338d6,0x3bfd3b87,0x3af13bc9,0x388e2fbd,0x3c003b18,0x387f3b10,0xb5d42f27,
0x3a04316c,0x3a673bfe,0xb6bb33d3,0xbbccbb2f,0x3b1e32f7,0x34933b5c,0xbbf5b86f,0x2d00b9bc,0x3bcb343e,0xb576394f,0xb8d1bbe9,0x3bfb36a4,
0x3c0034ff,0xbaac347b,0x3602ba31,0x32de3bf9,0x3bba35bc,0xbbfdb109,0x3be7aa7a,0xbb7a341a,0x394639cd,0x381538b2,0x358136dd,0x3153341a,
0xbb1eb9c9,0xbbf5bbdd,0xba39bb65,0xb4f3b889,0xb340b93c,0x3966340e,0x3bec3b87,0x37213a7e,0x3c003a4d,0x32193a21,0xbb5eb785,0xb894bbb0,
0xb426389e,0xbb37bb45,0x38b7b3d3,0x397d3bfc,0xbafebac1,0x3b13217f,0xadc93aa9,0xba49bb59,0x3979b7e8,0xb0d73b32,0xb6f4bbe9,0x3af139da,
0x38553b24,0xb9a1ba3d,0x3ab03911,0xbb73b759,0x3a043982,0x3ae13a7a,0x3b833b3a,0x3be33bbc,0x374e3986,0xae9131e8,0xb907b61a,0xbb9cba97,
0xbbcbba0d,0xb9e7bbbd,0x3074b56a,0x3b2a38ad,0x2452b8ee,0x3bda3924,0x363c3b10,0xba90b46f,0x3bba3a89,0xb6e836af,0xba76bbc2,0x39d2ac06,
0xb7c8384a,0xb77abc00,0x3bf8386f,0xb8f33654,0xb9d6baf4,0x3be836ff,0xbb3530be,0x37f3b974,0x3abab737,0xb9af3902,0x3865ba31,0xb5d43b1b,
0x32c62fbd,0x363134cf,0x38653785,0x398b38fd,0xb715b16c,0xbae1b970,0xbbfebbc2,0xba85bb92,0x392e32f7,0x3bf53b6c,0x37a63aa9,0xb7422311,
0xba81b43e,0xb9e7bbfc,0x380fb0be,0x3b963b7f,0x3b7134ff,0x32193b04,0xbc00b911,0x319eb929,0xbbefb5bc,0x36e8b8b2,0x382a3bfd,0xbbffb805,
0x3bf23676,0xbb1331e8,0x376fb9aa,0x2f8b3bde,0xbb7cb72c,0x3be8340e,0xbbfdaa16,0x3bb8b122,0xbbd2bbf1,0xbb60bba1,0xbab0bb10,0xb9c5ba41,
0x3b2c3be2,0x381539df,0xa94d33d3,0xb8a3b52f,0xba19bbcf,0x2e91b5f7,0x3b07386f,0x3b213c00,0x38a83bb7,0xb966aba7,0xbae5bbe9,0x3517b599,
0xb5dfbb9a,0x3bda37b2,0x1fdb3a31,0xbbe0ba1d,0x30293b78,0xbb37ba7a,0x3ad5aa7a,0xa7763aeb,0x2f59bb52,0x377a3bdd,0xbb16b9a6,0x3bf231cf,
0xb5a53b27,0x30d7bbbd,0x2b433bfe,0xb432bbe5,0x3a813a0d,0x3b3f3ae8,0x3bbf3b87,0x3bfb3be5,0xb5dfb8ee,0x3263ad97,0x399d3785,0x3bd03b01,
0xbbefba89,0xb958bb81,0x3389b3d3,0x3b7a394a,0xaf59384a,0xbbf7b9b8,0xb4c3baa9,0x3afb35eb,0x3b7c3af4,0xb825353a,0xb9f8bbe9,0x3a542884,
0x388eb737,0x360e3bf4,0xbbdcb911,0x398bb4db,0xb946bb4f,0x3bc03830,0xbb832a7a,0x38a3b8db,0xbb1e35c8,0x3a35b85f,0xb90739aa,0x3742bab6,
0xb8a8b93c,0xb6c6b80a,0xb402b56a,0xac6ab122,0xbb71ba4d,0xbbd7bbf8,0xb9b3bb10,0xb2deb7bd,0x3029389e,0xb9f4b58d,0xbbc6bbc2,0xb5b1ba00,
0x3bf23ac1,0x2dfb3999,0xbba3b86f,0xb7d2bb6f,0x35a5b7e8,0x3ad83b90,0xb95430be,0xb8e5bbff,0xba93bb24,0x3b682ef5,0xb2013a31,0xb9c5bb9f,
0xba043682,0x33ebbad1,0x35813bfd,0xba85ba5c,0x374e3b76,0xb90cbab3,0x3a3939a6,0xbb21b85a,0xb7c83b52,0x391bba9b,0xba2539aa,0x3afbb889,
0xb9793b27,0x3bc5b80a,0xbb8eaa16,0x38e538ad,0xbaba3af7,0x3b60ad97,0xb27cba2d,0xb98b3bb0,0xbb943ac4,0x3815358d,0x39e3bbea,0xba852c06,
0xbbf93a8c,0xae9139b8,0x3bacb874,0x3742bb59,0xbbe43a50,0xb9663b90,0x340233ba,0x3b96b974,0xbb573a11,0xbbda3bf4,0xb99d3b0d,0xb19e3759,
0xba5839cd,0xbb373ad1,0xbbc63b89,0xbbff3bee,0x3afe3676,0xba29b884,0x391f39a6,0xb7d2ba97,0x39d6372c,0xb3a2bae8,0xb5463bfe,0x3a54ba7e,
0x385537dd,0x3631bbf8,0xbbd63916,0x39c5346f,0x35233845,0x3ae1bb81,0xb96bb0a6,0xb8a33bfc,0x2d333899,0x3bf5b999,0x3487baa5,0xbb213654,
0xb13b38ea,0x39e7b53a,0x3bbfbbc3,0x3517b9da,0xb65f3937,0x32192ef5,0x39b3b790,0x3be0bb1b,0xb8e03982,0xb6e83830,0xb389355e,0xa7763042,
0xbb943682,0x3bebb371,0xbbfe2a7a,0x3bcc3042,0xad33bb76,0xb79b3bd4,0x3b07b9aa,0xbbfa32ad,0x3be4b50b,0xb6c6b8d6,0xb80f3bfe,0x3bfbb835,
0xb65f3bb5,0x3bd7b764,0x9fdbba2d,0xbbd03a41,0xba58330f,0xb9f43bfe,0x382a30a6,0x3b7abb92,0x3a45bbe1,0xadfbb648,0xbb163874,0xbafb3c00,
0x3699afef,0x3ad8b94f,0x3bfdbbc3,0x3a54bb7f,0xbbdf3bfa,0xbb683bae,0xba9e3b0d,0xb98b3a1d,0x35233b4f,0xb08dbbc8,0xa94d3bfd,0x3328bbee,
0xbbf935c8,0x3b0a3294,0xb7a6b9a6,0xad003bd3,0x313bbb98,0xbb3f3a60,0x3ae52a16,0xac6abace,0x3b57b44b,0x3263bb18,0xbc003916,0x32de38fd,
0xb8e03bce,0x3958a8e8,0x3ad5bbea,0xb5b1b52f,0xb8f83185,0xbbf73b5c,0xb76f3aa5,0x37d2a311,0x3b4abbf0,0x3825b9fc,0xab43b3ba,0xb8e53599,
0x31b6acce,0x360eb47b,0x387fb790,0x39c5b929,0x3a9337dd,0xb9a1b924,0x387f3a2d,0xb66bbb01,0xb946b845,0x308d3b45,0x36bbbbea,0xbac73a00,
0x374e3899,0x379bbc00,0xbbf53874,0x393335eb,0xb340b8ea,0xbb3f3b32,0x38d133ba,0x3941bbff,0xa4523937,0x3bd7b902,0x3602bb0d,0xbabd34db,
0x3426b982,0xb9583371,0xbbe73b89,0xb68d3a5c,0xb7c839c9,0x2dfb3294,0x391fb625,0x3bb3bab6,0x3979ba0d,0x3825b8d6,0x3546b6d2,0x3010b359,
0x388ebaf7,0xb9af3a21,0x3a9eb916,0xbb5437bd,0xba043ac4,0x3bebb6af,0xbb42b0a6,0x3840394a,0x3b1eba8c,0xbb0aa17f,0x2ec33aa5,0x3a15bb6f,
0xbbcb3a50,0x36c636ff,0x3a64bbc3,0xba09a884,0x3c00ba11,0x3263ba3d,0xbb6a3790,0xb8503b9f,0xbbba39cd,0xb9f43bc8,0x30f0355e,0x3b4cb8db,
0x3afeb986,0x3bf7bbd4,0x3a25bb63,0x3457b85a,0xb9d6393c,0xbad83a60,0xbb8e3b3d,0xbbef3bc9,0x33403b98,0xa9b1bbed,0xb0743bfe,0x3517bbc9,
0x3c00b44b,0xbaa2b4cf,0x363c3a2d,0x319ebbf3,0x3426bbce,0xbb8b39df,0x3a7630a6,0x2776bb2f,0xbafe3185,0xb4b73b6c,0x3bf8b874,0xaf8bb994,
0xb9793bf0,0x38bc2ba7,0x3b35bbc3,0xb432b6a4,0x3855acce,0x3c00bb04,0x3865bb0d,0xb66bad65,0x3b94bbff,0x38ccba7a,0x294db55e,0xb840341a,
0xad33a5e4,0xb49331e8,0xb7a63625,0xb9333889,0x3bcbb50b,0xbbfe305b,0x3bec2a16,0xbb96b359,0x2452bbb5,0xb87a3ba1,0x3b5eb916,0xbbe02f27,
0xbbba330f,0x35523970,0x38b7bbea,0xbbff370a,0xb7c83be1,0x3ba5b5f7,0x2dc9baa5,0xbbf239bc,0x39d6afef,0x3a73bbfc,0xb6f4b3ba,0xbbb83b47,
0x3ababbfa,0x1cb6b7b2,0xbab03790,0xbb543bf9,0xb52326ad,0xba6738b2,0xbbfe3b89,0xbac73bbc,0xbbf93bff,0xbbab3bdd,0xbb073b63,0xba153a97,
0xb8f83986,0xb77a385f,0xb4c33625,0xaf8b32ad,0xb699393c,0x30d7305b,0x3954b6d2,0x3bb8bace,0xb1b638ee,0x39afb4cf,0x3bdcbba7,0x366bba41,
0x2c38389e,0x3bebb970,0x3581bade,0xbac7352f,0x34e7384a,0x3b0abb6c,0xb907b24b,0xb9333c00,0x383a37e8,0x36c6bbfc,0xbbec38c1,0x39413599,
0x39c03737,0xb263bb04,0xb63c3bf6,0x3abdba1d,0x3aee3682,0xb9f4b8b2,0x38b739f0,0xb68dbaeb,0xba4539c9,0xbb133ab3,0xbba33b63,0xbbf23bd3,
0xbb4a3a0d,0xbbe83bed,0xb9f83b3d,0xb4323835,0xbbdf3a4d,0xb9a13ba1,0x320134ab,0x3b54b8fd,0xbbfc3a89,0xb08d39df,0x3b83b81a,0x3840bb92,
0xbb9e3ac1,0x379b35f7,0x3a39bbd8,0xba15a311,0xbacb3af4,0x3b3faba7,0xb074ba6f,0xba093b7f,0xb9903b24,0x3bd7b7b2,0xbb5eae5f,0x38503929,
0xb7fe3b4f,0x3958ba7a,0xba76395d,0x3b4cb805,0x2c3826ad,0x33ebb109,0x36bbb55e,0x38a3b805,0x3b9ebbff,0x390cba9b,0x2ec3b625,0xb74231cf,
0xb83a2c9c,0xbbfe3ae8,0xb8d13b3d,0x35173122,0xb9903bf1,0x387a2d97,0x3b6abba7,0xb19eb7bd,0x3aeeb16c,0x3552bb81,0xbbe7381a,0x27763a00,
0x3463bbcf,0xbba539b8,0x3a25324b,0x2f8bbb6f,0xbbff343e,0x3a73353a,0xb546ba6f,0xb4323bff,0x32c63b9a,0x9cb6bbf4,0xb27c3bf6,0x366bbb9f,
0xbbfc3bff,0xbbc03be6,0xbb423b89,0xba853aeb,0x34e7a5e4,0x3a35b884,0x3bf5bb63,0x3b21bbde,0x3acbbbfb,0x29b1b80a,0xba6436d2,0xbb963be5,
0xb9c02fbd,0xbaa23bf8,0x360234ab,0x3be0bb01,0xb7fe3be2,0x3b8bb58d,0x30f0bade,0xbbff394a,0x3bb2b2f7,0xb4b7b999,0xb91f3bd8,0x3bf2b5eb,
0x281fbbb7,0xb8bc3b90,0x3b8eb8c1,0xbbb82884,0xbbd234ff,0x3c00aef5,0xbbd6ae5f,0x3b5434db,0xbaba3a4d,0xbb683b18,0xbbd63ba7,0xbc003bf3,
0x3b94ba89,0x3bc0bbfe,0x396bbade,0x3153b70a,0xbbf93ac1,0xb90c3b5c,0x3487324b,0x3b9cb994,0x3be4baf4,0x29b1b94f,0xbbbf38c1,0xb7213b47,
0xbb573b24,0x387a347b,0x39b3bbf6,0xba902d65,0x3a58bb4f,0xbb8b3109,0x338939f0,0x397dbbbc,0xb8f83b76,0x3ba5b884,0xbba39648,0x38f33889,
0x3699bb98,0xb8bc3ae8,0x39f8b9eb,0xbaf138ad,0x3855b8ee,0x360eb764,0x327cb4ab,0x251baf27,0xb523389e,0x33eb28e8,0x39e3b81a,0x3be3bb2f,
0x2d33b84a,0xba353648,0xbbac3bd8,0xb4f339bc,0x313b37e8,0x3bfeb9fc,0x3402ba6f,0xbb2a36a4,0xb65fb737,0xbaa23bae,0x399d2e5f,0x3894bbf9,
0x38e03682,0x3552bbe6,0xbbc6395d,0x39d2341a,0xba45b5c8,0x34b73a9b,0x34c3bc00,0xba493a97,0x3b4a350b,0xba73b80a,0x39543962,0xb7f3ba7e,
0xbbe43bfb,0xbb853bbd,0xbae53b3d,0xba093a7e,0xb65f2fbd,0xbaac3924,0xbc003ba7,0xbabd3bb0,0x3a58bbe2,0xaadeb6af,0xbad5381a,0xbb4c3bfc,
0x3a45b2f7,0x3a29bc00,0xb76fb24b,0xbbb33b59,0xb6993bb7,0x3bc5b6ff,0x2b43ba6f,0xbbef39da,0xbbdf34ff,0x36313902,0x387fbbf6,0xbc003759,
0xac38bb78,0xb8153bc8,0x3b42b95d,0xbbe33042,0x3b9eb676,0xbbf53294,0x3bf51648,0xbb9cb2ad,0xb13b2c9c,0xb576340e,0xb80f36d2,0xb94138ad,
0x3b57bbf1,0x386aba21,0x1fdbb4ab,0xb850346f,0x38e0b16c,0x3bfdbb45,0x382abade,0xb68dac06,0xb8f83bcf,0x391ba17f,0x3b16bbd8,0xb457b654,
0xbb4a343e,0xb3a23b32,0x3bfdb8c1,0xb010b974,0x31b6bb9a,0xbb603a3d,0x3a9e2e5f,0x251bbb1b,0x3bfcb5bc,0xbae1b371,0x36bb39f0,0x3153bbee,
0x34e73b52,0xae91bbd4,0xaec33c00,0x34f3bbd3,0x3bb235c8,0xbbf7b1e8,0x3bf81648,0xbbb331cf,0x3bff350b,0xbad8340e,0x36f4b9eb,0x30103be5,
0x3bd2344b,0xb60e3924,0xb865bbf6,0x3c0037bd,0x3b2c330f,0x33eb3b45,0xbbfeb8c7,0x3153b94a,0x3a193185,0x3a353c00,0xb7a63232,0xbb9cbb6f,
0x38a82fef,0x3bfe3b32,0x380f3adb,0xb7212884,0x35df2cce,0x3aa23902,0x3c003ba9,0x3a903b9f,0x302926ad,0x35523371,0x382a36dd,0x397d38db,
0xb4633b76,0x2dfbbbdd,0x2dc93c00,0xb457bbde,0xa81f3b98,0xb825bbbd,0x3b353962,0xbbefb122,0x32c63bb5,0xbb68ba21,0x3ab0ae2d,0xa51b3b01,
0x37153bce,0xbbc0b6af,0xa94dba6b,0x3be33a00,0x392e3be1,0xb90c217f,0xbb07bbd9,0x34f3b5eb,0x3a813bf0,0xa9b136ff,0xbae5b820,0xbb2abbff,
0x3b713bfa,0x387a3a3d,0x9fdb349f,0xb894b4db,0x3bef3bff,0x3b8b3bc8,0x3ad53b3a,0x39d23a5c,0x3b2cb5bc,0xba673830,0x396bb95d,0xb8403a5c,
0xb92ebb52,0x3bab385f,0xbbac9648,0x3933b85a,0xb8a8372c,0xb576bbed,0x3bbf3962,0xba093359,0x3b713af7,0xb86a34cf,0xb99dbbf6,0x3abd2f27,
0x3029b845,0x3bfd39df,0x33893a6b,0xbb4cb70a,0xbbf2ba8c,0xb91bbb6c,0x34c3b232,0x3bb339bc,0x35a538ea,0xb3a22ba7,0xb9f8b820,0xbbefbb47,
0x3a933a11,0x3b603b04,0x3bdc3ba9,0x3c003bf9,0x37153b78,0xb8ccbad1,0x39e339f0,0xbac7b8db,0x3a19b676,0xb4933ab3,0xb487bc00,0x3a153ab6,
0xba81bb27,0x3b85305b,0xb40239eb,0xb941bbc9,0xb5df37dd,0xbaacbba1,0x39b3ae2d,0x38503bf3,0x3bef3ac4,0x2ade3970,0xbbc6b8c7,0xb68dbb2f,
0xaf59b899,0x3a2935f7,0x3ba33bd9,0x34573994,0xbb7cba50,0xbbc5bbfc,0xb954badb,0xb010b6a4,0x388e3937,0x363137b2,0x3201349f,0xa51b2d65,
0xb1b63bb5,0x9cb6bbf8,0x32013bf6,0xb5d4bbb0,0xac38bbce,0x38cc3b81,0xbb83b8c7,0x3bcc2c06,0x34e73be1,0xbbabb999,0x3a39b232,0x2d003b59,
0xb83abbf0,0x3b85353a,0x30743adb,0xbbfbb974,0x39c03bfa,0xb86a2ef5,0xbb5ebba9,0x32deb759,0xbaeebbff,0xaadeb830,0x3a7636dd,0x3b7a3bee,
0x3bb23bff,0x391b3ab3,0x2dc9361a,0xb7d2b2ad,0xbbffbbfb,0xbbc5bbed,0xbb35bb87,0xba54bace,0xbbdfb44b,0x3c002d97,0xbbdc2e2d,0x3b73b46f,
0x3bfc330f,0xba67358d,0x3581ba6b,0x33283bfc,0xbb9eb185,0x3493b9b8,0x39073bd9,0xbbfab654,0x3acb2fef,0x35763b90,0xbbecb820,0x2c6ab9da,
0xb990acce,0xbaacbbf4,0x363cb49f,0x3bd03b1b,0x37fe26ad,0x3bfd3ad1,0x38b73b3a,0xb5b13042,0xb46325e4,0xba29b85f,0xbbf8bb65,0xbafbbbd3,
0x281fac9c,0x33a2305b,0x36f4356a,0x38e53835,0x383a3b27,0xb966ba60,0x3a643962,0xbb2ab835,0xb99037dd,0x3219bb18,0x36023bf6,0xba90ba41,
0xbaeebac4,0x3b3728e8,0xb0f03a6b,0xb9d2bb92,0x3463b899,0x3b133b5c,0xb91f3232,0xb8f3bc00,0x3bff3a50,0x30d739fc,0xbb8eb820,0xb7f3bb7f,
0x32c63937,0xb9a1b47b,0xbbd6bba9,0xb5d4ba1d,0xbb2cb9cd,0xbbebbbe6,0xb9e3bb3a,0xb328b805,0xb92eb9c9,0xb79bb884,0xb487b61a,0xad00b1cf,
0xbacb372c,0x39e7b8d6,0xb8d139eb,0x3721bace,0xb9c0baf7,0x3bda3764,0xbb6a2e2d,0x3894b8fd,0x37feb845,0x36e83bfe,0xbbe7b8c7,0x397db52f,
0x3bb23a8c,0xb77a3648,0xba25bbd9,0x3a492311,0xa81f38ea,0xbbe8b94f,0xb546badb,0x3af13599,0xbbd2ba11,0xb9afbbae,0x327cb49f,0x3b733929,
0xb715b982,0x308db109,0x396b36dd,0x3bcc3aeb,0x3a193986,0x3b0a3a9b,0x3bac3b65,0x3bfa3bde,0x30003000,0x30003000,0x30003000,0x30003000,
0x2f643000,0x2a1f2da8,0xaa1f0000,0xaf64ada8,0x2da83000,0xada80000,0xada8b000,0x2da88000,0x2a1f3000,0xaf64ada8,0x2f648000,0xaa1f2da8,
0x00003000,0x8000b000,0x00003000,0x8000b000,0xaa1f3000,0x2f64ada8,0xaf640000,0x2a1f2da8,0xada83000,0x2da88000,0x2da8b000,0xada80000,
0xaf643000,0xaa1f2da8,0x2a1f8000,0x2f64ada8,0x30003000,0x30003000,0x30003000,0x30003000,0xaf64b000,0xaa1fada8,0x2a1f8000,0x2f642da8,
0x2da83000,0xada80000,0xada8b000,0x2da88000,0xaa1fb000,0x2f642da8,0xaf640000,0x2a1fada8,0x00003000,0x8000b000,0x00003000,0x8000b000,
0x2a1fb000,0xaf642da8,0x2f648000,0xaa1fada8,0xada83000,0x2da88000,0x2da8b000,0xada80000,0x2f64b000,0x2a1fada8,0xaa1f0000,0xaf642da8,
0x80008000,0x80008000,0x80008000,0x80008000,0xaa1f8000,0xaf64ada8,0xaf64b000,0xaa1fada8,0xada88000,0xada8b000,0x2da88000,0x2da83000,
0xaf648000,0x2a1fada8,0x2a1f3000,0xaf64ada8,0xb0008000,0x30008000,0xb0008000,0x30008000,0xaf648000,0x2a1f2da8,0x2a1fb000,0xaf642da8,
0xada88000,0xada83000,0x2da88000,0x2da8b000,0xaa1f8000,0xaf642da8,0xaf643000,0xaa1f2da8,0x80008000,0x80008000,0x80008000,0x80008000,
0x2a1f8000,0x2f642da8,0x2f643000,0x2a1f2da8,0xada88000,0xada8b000,0x2da88000,0x2da83000,0x2f648000,0xaa1f2da8,0xaa1fb000,0x2f642da8,
0xb0008000,0x30008000,0xb0008000,0x30008000,0x2f648000,0xaa1fada8,0xaa1f3000,0x2f64ada8,0xada88000,0xada83000,0x2da88000,0x2da8b000,
0x2a1f8000,0x2f64ada8,0x2f64b000,0x2a1fada8,0xb0003000,0xb0003000,0xb0003000,0xb0003000,0xaf643000,0xaa1f2da8,0x2a1f0000,0x2f64ada8,
0xada83000,0x2da80000,0x2da8b000,0xada88000,0xaa1f3000,0x2f64ada8,0xaf648000,0x2a1f2da8,0x80003000,0x0000b000,0x80003000,0x0000b000,
0x2a1f3000,0xaf64ada8,0x2f640000,0xaa1f2da8,0x2da83000,0xada88000,0xada8b000,0x2da80000,0x2f643000,0x2a1f2da8,0xaa1f8000,0xaf64ada8,
0xb0003000,0xb0003000,0xb0003000,0xb0003000,0x2f64b000,0x2a1fada8,0xaa1f8000,0xaf642da8,0xada83000,0x2da80000,0x2da8b000,0xada88000,
0x2a1fb000,0xaf642da8,0x2f640000,0xaa1fada8,0x80003000,0x0000b000,0x80003000,0x0000b000,0xaa1fb000,0x2f642da8,0xaf648000,0x2a1fada8,
0x2da83000,0xada88000,0xada8b000,0x2da80000,0xaf64b000,0xaa1fada8,0x2a1f0000,0x2f642da8,0x80008000,0x80008000,0x80008000,0x80008000,
0x2a1f8000,0x2f64ada8,0x2f64b000,0x2a1fada8,0x2da88000,0x2da8b000,0xada88000,0xada83000,0x2f648000,0xaa1fada8,0xaa1f3000,0x2f64ada8,
0x30008000,0xb0008000,0x30008000,0xb0008000,0x2f648000,0xaa1f2da8,0xaa1fb000,0x2f642da8,0x2da88000,0x2da83000,0xada88000,0xada8b000,
0x2a1f8000,0x2f642da8,0x2f643000,0x2a1f2da8,0x80008000,0x80008000,0x80008000,0x80008000,0xaa1f8000,0xaf642da8,0xaf643000,0xaa1f2da8,
0x2da88000,0x2da8b000,0xada88000,0xada83000,0xaf648000,0x2a1f2da8,0x2a1fb000,0xaf642da8,0x30008000,0xb0008000,0x30008000,0xb0008000,
0xaf648000,0x2a1fada8,0x2a1f3000,0xaf64ada8,0x2da88000,0x2da83000,0xada88000,0xada8b000,0xaa1f8000,0xaf64ada8,0xaf64b000,0xaa1fada8,
0x00000000,0x00000000,0x00000000,0x00000000,0x2a1f0000,0x2f642da8,0x2f643000,0x2a1f2da8,0x2da80000,0x2da83000,0xada80000,0xada8b000,
0x2f640000,0xaa1f2da8,0xaa1fb000,0x2f642da8,0x30000000,0xb0000000,0x30000000,0xb0000000,0x2f640000,0xaa1fada8,0xaa1f3000,0x2f64ada8,
0x2da80000,0x2da8b000,0xada80000,0xada83000,0x2a1f0000,0x2f64ada8,0x2f64b000,0x2a1fada8,0x00000000,0x00000000,0x00000000,0x00000000,
0xaa1f0000,0xaf64ada8,0xaf64b000,0xaa1fada8,0x2da80000,0x2da83000,0xada80000,0xada8b000,0xaf640000,0x2a1fada8,0x2a1f3000,0xaf64ada8,
0x30000000,0xb0000000,0x30000000,0xb0000000,0xaf640000,0x2a1f2da8,0x2a1fb000,0xaf642da8,0x2da80000,0x2da8b000,0xada80000,0xada83000,
0xaa1f0000,0xaf642da8,0xaf643000,0xaa1f2da8,0x30003000,0x30003000,0x30003000,0x30003000,0x2f643000,0x2a1f2da8,0xaa1f0000,0xaf64ada8,
0x2da83000,0xada80000,0xada8b000,0x2da88000,0x2a1f3000,0xaf64ada8,0x2f648000,0xaa1f2da8,0x00003000,0x8000b000,0x00003000,0x8000b000,
0xaa1f3000,0x2f64ada8,0xaf640000,0x2a1f2da8,0xada83000,0x2da88000,0x2da8b000,0xada80000,0xaf643000,0xaa1f2da8,0x2a1f8000,0x2f64ada8,
0x30003000,0x30003000,0x30003000,0x30003000,0xaf64b000,0xaa1fada8,0x2a1f8000,0x2f642da8,0x2da83000,0xada80000,0xada8b000,0x2da88000,
0xaa1fb000,0x2f642da8,0xaf640000,0x2a1fada8,0x00003000,0x8000b000,0x00003000,0x8000b000,0x2a1fb000,0xaf642da8,0x2f648000,0xaa1fada8,
0xada83000,0x2da88000,0x2da8b000,0xada80000,0x2f64b000,0x2a1fada8,0xaa1f0000,0xaf642da8,0x00000000,0x00000000,0x00000000,0x00000000,
0xaa1f0000,0xaf642da8,0xaf643000,0xaa1f2da8,0xada80000,0xada83000,0x2da80000,0x2da8b000,0xaf640000,0x2a1f2da8,0x2a1fb000,0xaf642da8,
0xb0000000,0x30000000,0xb0000000,0x30000000,0xaf640000,0x2a1fada8,0x2a1f3000,0xaf64ada8,0xada80000,0xada8b000,0x2da80000,0x2da83000,
0xaa1f0000,0xaf64ada8,0xaf64b000,0xaa1fada8,0x00000000,0x00000000,0x00000000,0x00000000,0x2a1f0000,0x2f64ada8,0x2f64b000,0x2a1fada8,
0xada80000,0xada83000,0x2da80000,0x2da8b000,0x2f640000,0xaa1fada8,0xaa1f3000,0x2f64ada8,0xb0000000,0x30000000,0xb0000000,0x30000000,
0x2f640000,0xaa1f2da8,0xaa1fb000,0x2f642da8,0xada80000,0xada8b000,0x2da80000,0x2da83000,0x2a1f0000,0x2f642da8,0x2f643000,0x2a1f2da8,
0xb0003000,0xb0003000,0xb0003000,0xb0003000,0xaf643000,0xaa1f2da8,0x2a1f0000,0x2f64ada8,0xada83000,0x2da80000,0x2da8b000,0xada88000,
0xaa1f3000,0x2f64ada8,0xaf648000,0x2a1f2da8,0x80003000,0x0000b000,0x80003000,0x0000b000,0x2a1f3000,0xaf64ada8,0x2f640000,0xaa1f2da8,
0x2da83000,0xada88000,0xada8b000,0x2da80000,0x2f643000,0x2a1f2da8,0xaa1f8000,0xaf64ada8,0xb0003000,0xb0003000,0xb0003000,0xb0003000,
0x2f64b000,0x2a1fada8,0xaa1f8000,0xaf642da8,0xada83000,0x2da80000,0x2da8b000,0xada88000,0x2a1fb000,0xaf642da8,0x2f640000,0xaa1fada8,
0x80003000,0x0000b000,0x80003000,0x0000b000,0xaa1fb000,0x2f642da8,0xaf648000,0x2a1fada8,0x2da83000,0xada88000,0xada8b000,0x2da80000,
0xaf64b000,0xaa1fada8,0x2a1f0000,0x2f642da8};

constexpr int kThreads = 384;
constexpr int kCtas = 128;

constexpr uint32_t SM_BASE = 1024;
constexpr uint32_t QKV_STAGE = 32768;
constexpr uint32_t SLOT = 16384;
constexpr uint32_t SM_KV = 2 * SLOT;
constexpr uint32_t SM_SIG = 131072;
constexpr uint32_t SM_STG = 196608;
constexpr uint32_t SM_Q = SM_STG;
constexpr uint32_t SM_Y0 = 3 * SLOT;
constexpr uint32_t SM_YT = SM_STG + 16384;
constexpr uint32_t SM_TW = SM_STG + 24576, SM_ONES = SM_TW + 2048, SM_F1 = SM_ONES + 2048, SM_F2 = SM_F1 + 4096;
constexpr uint32_t SM_BAR = SM_F2 + 2048;
constexpr uint32_t SM_SC = SM_BAR + 640;
constexpr uint32_t SM_TOTAL = 232448;
constexpr uint32_t A_SLOTS = 0xA02B1, B_SLOTS = 0x97654;

enum Bar { B_QKV_EMPTY = 0, B_QKV_DONE = 4,
           B_OUT_EMPTY = 8,
           B_H_FULL = 16, B_YIN = 19, B_RDY0 = 21, B_RDY1 = 22, B_ZEROED = 23,
           B_OUT_FULL = 24, B_PREP_FULL = 29,
           B_Q_FULL = 32, B_OT_FREE = 36, B_Y_READY = 38, B_FLAGS1 = 39,
           B_SEG = 40, B_SIG_READY = 44,
           B_KVP = 48, B_O_WRITTEN = 49, B_SLOT_FREE = 51, B_CONV_DONE = 52,
           B_PREP_EMPTY = 56, B_KV_READY = 59,
           B_QKV_FULL = 64, B_STG_FREE = 68, B_FIRST = 69 };
constexpr uint32_t BAR_LOG2 = 0x13200044;

constexpr int KV_SLICE = 640;
constexpr int XCH_FLAG = 2 * SLOT + 17 * KV_SLICE;
constexpr int XCH_BYTES = 11 * 4096;

struct Params {
  CUtensorMap x, w, wk, wo, outa, k, v, q;
  const __nv_bfloat16* shift_k;
  const __nv_bfloat16* ssm_k;
  const __nv_bfloat16* ssm_d;
  const __nv_bfloat16* q_ptr;
  __nv_bfloat16* out_ptr;
  const __nv_bfloat16* wo_ptr;
  int zero;
};

__device__ __align__(128) uint8_t g_xch[kCtas][XCH_BYTES];
__device__ unsigned g_ready, g_epoch[kCtas];

#define TSTAMP(cond, i) do { } while (0)
#define GSTAMP(cond, i) do { } while (0)
#define LOOPSTAMP(id, cond, i) do { } while (0)

constexpr int kSpinLimit = 1 << 17;

DEVI void mbar_init(uint32_t a, uint32_t c) { asm volatile("mbarrier.init.shared::cta.b64 [%0], %1;" :: "r"(a), "r"(c) : "memory"); }
DEVI void mbar_expect(uint32_t a, uint32_t b) { asm volatile("mbarrier.arrive.expect_tx.shared::cta.b64 _, [%0], %1;" :: "r"(a), "r"(b) : "memory"); }
DEVI void mbar_arrive(uint32_t a) { asm volatile("mbarrier.arrive.shared::cta.b64 _, [%0];" :: "r"(a) : "memory"); }
DEVI void mbar_arrive_if(uint32_t a, bool pred) {
  asm volatile("{\n.reg .pred p;\nsetp.ne.b32 p, %1, 0;\n@p mbarrier.arrive.shared::cta.b64 _, [%0];\n}" :: "r"(a), "r"((int)pred) : "memory");
}
DEVI void mbar_wait(uint32_t a, uint32_t parity) {
  asm volatile("{\n.reg .pred p;\n.reg .u32 n;\nmov.u32 n, 0;\nW_LOOP:\n"
               "mbarrier.try_wait.parity.shared::cta.b64 p, [%0], %1;\nadd.u32 n, n, 1;\n"
               "setp.lt.and.u32 p, n, %2, !p;\n@p bra W_LOOP;\n}"
               :: "r"(a), "r"(parity), "n"(kSpinLimit) : "memory");
}
DEVI bool mbar_test(uint32_t a, uint32_t parity) {
  uint32_t ok;
  asm volatile("{\n.reg .pred p;\nmbarrier.test_wait.parity.shared::cta.b64 p, [%1], %2;\nselp.u32 %0, 1, 0, p;\n}" : "=r"(ok) : "r"(a), "r"(parity) : "memory");
  return ok;
}
DEVI bool elect() {
  uint32_t ok;
  asm volatile("{\n.reg .pred p;\nelect.sync _|p, 0xffffffff;\nselp.u32 %0, 1, 0, p;\n}" : "=r"(ok));
  return ok;
}
DEVI void flag_wait(const unsigned* p, unsigned target) {
  int n = 0; unsigned v;
  do {
    asm volatile("ld.acquire.gpu.global.u32 %0, [%1];" : "=r"(v) : "l"(p) : "memory");
  } while ((int)(v - target) < 0 && ++n < kSpinLimit);
}
DEVI uint32_t clock32() { uint32_t t; asm volatile("mov.u32 %0, %%clock;" : "=r"(t) :: "memory"); return t; }
DEVI void delay(uint32_t cycles) { const uint32_t t = clock32(); while (clock32() - t < cycles) { } }
DEVI void st_relaxed(void* p, uint32_t v) { asm volatile("st.relaxed.gpu.global.b32 [%0], %1;" :: "l"(p), "r"(v) : "memory"); }
DEVI uint32_t ld_relaxed(const void* p) { uint32_t v; asm volatile("ld.relaxed.gpu.global.b32 %0, [%1];" : "=r"(v) : "l"(p) : "memory"); return v; }
DEVI void ld_relaxed4(uint32_t* v, const void* p) {
  asm volatile("ld.relaxed.gpu.global.v4.b32 {%0,%1,%2,%3}, [%4];" : "=r"(v[0]), "=r"(v[1]), "=r"(v[2]), "=r"(v[3]) : "l"(p) : "memory");
}
template <int N> DEVI uint32_t umax(const uint32_t* v) {
  if constexpr (N == 1) return v[0];
  else if constexpr (N == 2) return max(v[0], v[1]);
  else if constexpr (N <= 6) return __vimax3_u32(v[0], v[1], umax<N - 2>(v + 2));
  else return __vimax3_u32(umax<N / 3 | 1>(v), umax<N / 3 | 1>(v + (N / 3 | 1)), umax<N - 2 * (N / 3 | 1)>(v + 2 * (N / 3 | 1)));
}
template <int N> DEVI bool all_arrived(const uint32_t* v) { return __all_sync(0xffffffffu, umax<N>(v) != 0xffffffffu); }
DEVI void flag_add(unsigned* p) {
  asm volatile("fence.release.gpu;\nred.relaxed.gpu.global.add.u32 [%0], 1;" :: "l"(p) : "memory");
}
DEVI void fence_async_smem() { asm volatile("fence.proxy.async.shared::cta;" ::: "memory"); }
DEVI void bar_sync(int id, int n) { asm volatile("bar.sync %0, %1;" :: "r"(id), "r"(n) : "memory"); }
DEVI void cluster_arrive() { asm volatile("barrier.cluster.arrive.relaxed.aligned;" ::: "memory"); }
DEVI void cluster_wait() { asm volatile("barrier.cluster.wait.aligned;" ::: "memory"); }
DEVI void wg_fence() { asm volatile("wgmma.fence.sync.aligned;" ::: "memory"); }
DEVI void wg_commit() { asm volatile("wgmma.commit_group.sync.aligned;" ::: "memory"); }
template <int N> DEVI void wg_wait() { asm volatile("wgmma.wait_group.sync.aligned %0;" :: "n"(N) : "memory"); }
template <int N> DEVI void pin(uint32_t* r) {
#pragma unroll
  for (int i = 0; i < N; i++) asm volatile("" : "+r"(r[i]) :: "memory");
}
template <int N> DEVI void pin(float* r) {
#pragma unroll
  for (int i = 0; i < N; i++) asm volatile("" : "+f"(r[i]) :: "memory");
}

DEVI void sched_fence(int zero, int id) { asm volatile("{\n.reg .pred p;\nsetp.eq.b32 p, %0, %1;\nS_LOOP:\n@p st.volatile.shared.b32 [%0], %0;\n@p bra S_LOOP;\n}" :: "r"(zero), "r"(id + 1) : "memory"); }
DEVI void pin_range(float* r, int i0, int i1) {
#pragma unroll
  for (int i = i0; i < i1; i++) asm volatile("" : "+f"(r[i]) :: "memory");
}
DEVI void keep(uint32_t& x) { asm volatile("" : "+r"(x) :: "memory"); }
DEVI void keep(int& x) { asm volatile("" : "+r"(x) :: "memory"); }
template <class T> DEVI void keep(T*& x) { asm volatile("" : "+l"(x) :: "memory"); }

DEVI void tma2d(uint32_t dst, const CUtensorMap* m, int c0, int c1, uint32_t bar) {
  asm volatile("cp.async.bulk.tensor.2d.shared::cluster.global.mbarrier::complete_tx::bytes [%0], [%1, {%3, %4}], [%2];"
               :: "r"(dst), "l"(m), "r"(bar), "r"(c0), "r"(c1) : "memory");
}
DEVI void tma2d_mc(uint32_t dst, const CUtensorMap* m, int c0, int c1, uint32_t bar) {
  asm volatile("cp.async.bulk.tensor.2d.shared::cluster.global.mbarrier::complete_tx::bytes.multicast::cluster [%0], [%1, {%3, %4}], [%2], %5;"
               :: "r"(dst), "l"(m), "r"(bar), "r"(c0), "r"(c1), "h"((uint16_t)3) : "memory");
}
DEVI void tma3d(uint32_t dst, const CUtensorMap* m, int c0, int c1, int c2, uint32_t bar) {
  asm volatile("cp.async.bulk.tensor.3d.shared::cluster.global.mbarrier::complete_tx::bytes [%0], [%1, {%3, %4, %5}], [%2];"
               :: "r"(dst), "l"(m), "r"(bar), "r"(c0), "r"(c1), "r"(c2) : "memory");
}
DEVI void tma3d_mc(uint32_t dst, const CUtensorMap* m, int c0, int c1, int c2, uint32_t bar) {
  asm volatile("cp.async.bulk.tensor.3d.shared::cluster.global.mbarrier::complete_tx::bytes.multicast::cluster [%0], [%1, {%3, %4, %5}], [%2], %6;"
               :: "r"(dst), "l"(m), "r"(bar), "r"(c0), "r"(c1), "r"(c2), "h"((uint16_t)3) : "memory");
}
DEVI void tma2d_store(const CUtensorMap* m, uint32_t src, int c0, int c1) {
  asm volatile("cp.async.bulk.tensor.2d.global.shared::cta.bulk_group [%0, {%2, %3}], [%1];" :: "l"(m), "r"(src), "r"(c0), "r"(c1) : "memory");
}
DEVI void bulk_load(uint32_t dst, const void* src, uint32_t bytes, uint32_t bar) {
  asm volatile("cp.async.bulk.shared::cluster.global.mbarrier::complete_tx::bytes [%0], [%1], %2, [%3];" :: "r"(dst), "l"(src), "r"(bytes), "r"(bar) : "memory");
}
DEVI void bulk_store(void* dst, uint32_t src, uint32_t bytes) {
  asm volatile("cp.async.bulk.global.shared::cta.bulk_group [%0], [%1], %2;" :: "l"(dst), "r"(src), "r"(bytes) : "memory");
}
DEVI uint32_t peer_addr(uint32_t a, int rank) { uint32_t r; asm("mapa.shared::cluster.u32 %0, %1, %2;" : "=r"(r) : "r"(a), "r"(rank)); return r; }
DEVI void bulk_to_peer(uint32_t dst, uint32_t src, uint32_t bytes, uint32_t bar, int rank) {
  asm volatile("cp.async.bulk.shared::cluster.shared::cta.mbarrier::complete_tx::bytes [%0], [%1], %2, [%3];"
               :: "r"(peer_addr(dst, rank)), "r"(src), "r"(bytes), "r"(peer_addr(bar, rank)) : "memory");
}
DEVI void l2_prefetch(const void* p, uint32_t bytes) {
  asm volatile("cp.async.bulk.prefetch.L2.global [%0], %1;" :: "l"(p), "r"(bytes) : "memory");
}
DEVI void l2_prefetch2d(const CUtensorMap* m, int c0, int c1) {
  asm volatile("cp.async.bulk.prefetch.tensor.2d.L2.global [%0, {%1, %2}];" :: "l"(m), "r"(c0), "r"(c1) : "memory");
}
DEVI void l2_prefetch3d(const CUtensorMap* m, int c0, int c1, int c2) {
  asm volatile("cp.async.bulk.prefetch.tensor.3d.L2.global [%0, {%1, %2, %3}];" :: "l"(m), "r"(c0), "r"(c1), "r"(c2) : "memory");
}
DEVI void bulk_commit() { asm volatile("cp.async.bulk.commit_group;" ::: "memory"); }
DEVI void bulk_wait_all() { asm volatile("cp.async.bulk.wait_group 0;" ::: "memory"); }
DEVI void bulk_wait_read() { asm volatile("cp.async.bulk.wait_group.read 0;" ::: "memory"); }
DEVI void prefetch_map(const CUtensorMap* m) { asm volatile("prefetch.tensormap [%0];" :: "l"(m) : "memory"); }
DEVI void arrive_both(uint32_t bar, int lane, bool pred = true) {
  asm volatile("{\n.reg .pred p;\n.reg .b32 r;\nsetp.ne.b32 p, %2, 0;\nmapa.shared::cluster.u32 r, %0, %1;\n@p mbarrier.arrive.shared::cluster.b64 _, [r];\n}"
               :: "r"(bar), "r"(lane & 1), "r"((int)(pred && lane < 2)) : "memory");
}

DEVI uint64_t make_desc(uint32_t off, uint32_t lbo, uint32_t sbo, uint32_t mode) {
  const uint32_t lo = (off >> 4) + (SM_BASE >> 4) + ((lbo >> 4) << 16), hi = (sbo >> 4) | (mode << 30);
  return ((uint64_t)hi << 32) | lo;
}
DEVI uint32_t pack_bf16(float lo, float hi) { uint32_t r; asm("cvt.rn.bf16x2.f32 %0, %1, %2;" : "=r"(r) : "f"(hi), "f"(lo)); return r; }
DEVI uint32_t pack_f16(float lo, float hi) { uint32_t r; asm("cvt.rn.f16x2.f32 %0, %1, %2;" : "=r"(r) : "f"(hi), "f"(lo)); return r; }
DEVI void stsm4(uint32_t addr, uint32_t r0, uint32_t r1, uint32_t r2, uint32_t r3) {
  asm volatile("stmatrix.sync.aligned.m8n8.x4.shared.b16 [%0], {%1,%2,%3,%4};" :: "r"(addr), "r"(r0), "r"(r1), "r"(r2), "r"(r3) : "memory");
}
DEVI void stsm2(uint32_t addr, uint32_t r0, uint32_t r1) {
  asm volatile("stmatrix.sync.aligned.m8n8.x2.shared.b16 [%0], {%1,%2};" :: "r"(addr), "r"(r0), "r"(r1) : "memory");
}
DEVI void stsm4_t(uint32_t addr, uint32_t r0, uint32_t r1, uint32_t r2, uint32_t r3) {
  asm volatile("stmatrix.sync.aligned.m8n8.x4.trans.shared.b16 [%0], {%1,%2,%3,%4};" :: "r"(addr), "r"(r0), "r"(r1), "r"(r2), "r"(r3) : "memory");
}
DEVI void ldsm4(uint32_t* r, uint32_t addr) {
  asm volatile("ldmatrix.sync.aligned.m8n8.x4.shared.b16 {%0,%1,%2,%3}, [%4];" : "=r"(r[0]), "=r"(r[1]), "=r"(r[2]), "=r"(r[3]) : "r"(addr) : "memory");
}
DEVI void ldsm4_t(uint32_t* r, uint32_t addr) {
  asm volatile("ldmatrix.sync.aligned.m8n8.x4.trans.shared.b16 {%0,%1,%2,%3}, [%4];" : "=r"(r[0]), "=r"(r[1]), "=r"(r[2]), "=r"(r[3]) : "r"(addr) : "memory");
}
DEVI uint32_t lds32(uint32_t a) { uint32_t v; asm volatile("ld.shared.b32 %0, [%1];" : "=r"(v) : "r"(a) : "memory"); return v; }
DEVI uint4 lds128(uint32_t a) {
  uint4 v; asm volatile("ld.shared.v4.b32 {%0,%1,%2,%3}, [%4];" : "=r"(v.x), "=r"(v.y), "=r"(v.z), "=r"(v.w) : "r"(a) : "memory"); return v;
}
DEVI uint32_t bmul2(uint32_t a, uint32_t b) { uint32_t r; asm("mul.rn.bf16x2 %0, %1, %2;" : "=r"(r) : "r"(a), "r"(b)); return r; }
DEVI uint32_t bfma2(uint32_t a, uint32_t b, uint32_t c) { uint32_t r; asm("fma.rn.bf16x2 %0, %1, %2, %3;" : "=r"(r) : "r"(a), "r"(b), "r"(c)); return r; }
DEVI float bf_lo(uint32_t w) { return __uint_as_float(w << 16); }
DEVI float bf_hi(uint32_t w) { return __uint_as_float(w & 0xffff0000u); }
DEVI uint32_t elu1(float a0, float a1) {
  constexpr float L = 1.4426950408889634f;
  float e0, e1;
  asm("ex2.approx.ftz.f32 %0, %1;" : "=f"(e0) : "f"(-fabsf(fmaf(a0, L, -L))));
  asm("ex2.approx.ftz.f32 %0, %1;" : "=f"(e1) : "f"(-fabsf(fmaf(a1, L, -L))));
  return pack_bf16(fmaxf(e0, a0), fmaxf(e1, a1));
}
DEVI float rcp(float x) { float r; asm("rcp.approx.ftz.f32 %0, %1;" : "=f"(r) : "f"(x)); return r; }
DEVI uint32_t add_eps(uint32_t x) { uint32_t r; asm("add.rn.bf16x2 %0, %1, %2;" : "=r"(r) : "r"(x), "r"(0x35863586u)); return r; }

#define S1SS 0
DEVI uint32_t hmul(uint32_t a, uint32_t b) { uint32_t r; asm("mul.rn.f16x2 %0, %1, %2;" : "=r"(r) : "r"(a), "r"(b)); return r; }
DEVI uint32_t hfma(uint32_t a, uint32_t b, uint32_t c) { uint32_t r; asm("fma.rn.f16x2 %0, %1, %2, %3;" : "=r"(r) : "r"(a), "r"(b), "r"(c)); return r; }
DEVI uint32_t hneg(uint32_t a) { uint32_t r; asm("neg.f16x2 %0, %1;" : "=r"(r) : "r"(a)); return r; }
DEVI uint32_t hadd(uint32_t a, uint32_t b) { uint32_t r; asm("add.rn.f16x2 %0, %1, %2;" : "=r"(r) : "r"(a), "r"(b)); return r; }
DEVI uint32_t hsub(uint32_t a, uint32_t b) { uint32_t r; asm("sub.rn.f16x2 %0, %1, %2;" : "=r"(r) : "r"(a), "r"(b)); return r; }
struct Cx { uint32_t re, im; };
DEVI Cx cmul(Cx a, Cx b) { return {hfma(a.re, b.re, hneg(hmul(a.im, b.im))), hfma(a.re, b.im, hmul(a.im, b.re))}; }
DEVI Cx cfma(Cx a, Cx b, Cx c) { return {hfma(a.re, b.re, hfma(hneg(a.im), b.im, c.re)), hfma(a.re, b.im, hfma(a.im, b.re, c.im))}; }
DEVI Cx rot(Cx a, Cx t) {
  const uint32_t x = hfma(hneg(t.re), a.im, a.re), y = hfma(t.im, x, a.im);
  return {hfma(hneg(t.re), y, x), y};
}
struct Fft {
  uint32_t fa[8];
  Cx tw[2];
  uint32_t vld;
  uint64_t dF2a, dF2b;
  uint32_t vst;
  DEVI void stage1(uint32_t* d1, uint32_t slot) const {
    wg_fence();
    fft1_init(d1, fa[0], fa[1], fa[2], fa[3], make_desc(slot, 4096, 1024, 1));
    fft1_acc(d1, fa[4], fa[5], fa[6], fa[7], make_desc(slot + 2048, 4096, 1024, 1));
    wg_commit();
  }
  DEVI void stage2(uint32_t* d, const Cx* t) const {
    wg_fence();
    fft2_init(d, t[0].re, t[1].re, t[2].re, t[3].re, dF2a);
    fft2_acc(d, t[0].im, t[1].im, t[2].im, t[3].im, dF2b);
    wg_commit();
  }
  template <int PR> DEVI void fwd(const uint32_t* d1, uint32_t* d2) const {
    Cx t[4];
#pragma unroll
    for (int e = 0; e < 4; e++) {
      const int j = 8 * (PR & 1) + 4 * (e >> 1) + 2 * (PR >> 1) + (e & 1);
      t[e] = rot({d1[2 * j], d1[2 * j + 1]}, tw[e >> 1]);
    }
    stage2(d2 + 8 * PR, t);
  }
  static DEVI Cx U(const uint32_t* d2, int p, int hi) { return {d2[16 * (p >> 1) + 2 * hi + (p & 1)], d2[16 * (p >> 1) + 4 + 2 * hi + (p & 1)]}; }
  static DEVI Cx H(const uint32_t* d2, int p, int hi) { return U(d2 + 8, p, hi); }
  DEVI void prod01(const uint32_t* d2, Cx* p1, uint32_t* d3) const {
    Cx z[4];
#pragma unroll
    for (int hi = 0; hi < 2; hi++) {
      const Cx p0 = cmul(H(d2, 0, hi), U(d2, 0, hi));
      p1[hi] = cfma(H(d2, 1, hi), U(d2, 0, hi), cmul(H(d2, 0, hi), U(d2, 1, hi)));
      z[2 * hi] = {p0.im, p0.re};
      z[2 * hi + 1] = {hsub(p1[hi].im, p0.re), hadd(p1[hi].re, p0.im)};
    }
    stage2(d3, z);
  }
  DEVI void prod23(const uint32_t* d2, const Cx* p1, uint32_t* d3) const {
    Cx z[4];
#pragma unroll
    for (int hi = 0; hi < 2; hi++) {
      const Cx p2 = cfma(H(d2, 2, hi), U(d2, 0, hi), cfma(H(d2, 0, hi), U(d2, 2, hi), cmul(H(d2, 1, hi), U(d2, 1, hi))));
      const Cx z3 = cfma(H(d2, 3, hi), U(d2, 0, hi), cfma(H(d2, 2, hi), U(d2, 1, hi),
                    cfma(H(d2, 1, hi), U(d2, 2, hi), cfma(H(d2, 0, hi), U(d2, 3, hi), {p2.im, hneg(p2.re)}))));
      z[2 * hi] = {hsub(p2.im, p1[hi].re), hadd(p2.re, p1[hi].im)};
      z[2 * hi + 1] = {z3.im, z3.re};
    }
    stage2(d3 + 8, z);
  }
  template <int PB> DEVI void inv(const uint32_t* d3, uint32_t slot) const {
    Cx v[4];
#pragma unroll
    for (int e = 0; e < 4; e++) {
      const int r = 8 * PB + 2 * (e & 1) + (e >> 1);
      v[e] = rot({d3[r], d3[r + 4]}, tw[e & 1]);
    }
    stsm4(slot + (vst ^ (PB * 64)), v[0].im, v[1].im, v[2].im, v[3].im);
    stsm4(slot + 1024 + (vst ^ (PB * 64)), v[0].re, v[1].re, v[2].re, v[3].re);
  }
  DEVI void last_load(uint32_t* a, uint32_t slot, int wg) const {
    bar_sync(2 + wg, 128);
#pragma unroll
    for (int ks = 0; ks < 4; ks++) ldsm4_t(a + 4 * ks, vld + slot + ks * 2048);
  }
  DEVI void last_mma(float* dy, const uint32_t* a) const {
    wg_fence();
    fft3_init(dy, a[0], a[1], a[2], a[3], make_desc(SM_F1, 128, 1024, 0));
#pragma unroll
    for (int ks = 1; ks < 4; ks++) fft3_acc(dy, a[4 * ks], a[4 * ks + 1], a[4 * ks + 2], a[4 * ks + 3], make_desc(SM_F1 + ks * 256, 128, 1024, 0));
    wg_commit();
  }
  DEVI void last(float* dy, uint32_t slot, int wg) const { uint32_t a[16]; last_load(a, slot, wg); last_mma(dy, a); }
  static DEVI void store_y(const float* dy, uint32_t a) {
    stsm4_t(a, pack_bf16(dy[0], dy[1]), pack_bf16(dy[2], dy[3]), pack_bf16(dy[4], dy[5]), pack_bf16(dy[6], dy[7]));
    stsm4_t(a + 512, pack_bf16(dy[8], dy[9]), pack_bf16(dy[10], dy[11]), pack_bf16(dy[12], dy[13]), pack_bf16(dy[14], dy[15]));
  }
};
DEVI uint32_t normalize(uint32_t* x, uint32_t dst) {
  uint32_t m = x[0];
#pragma unroll
  for (int i = 1; i < 32; i++) asm("max.xorsign.abs.bf16x2 %0, %0, %1;" : "+r"(m) : "r"(x[i]));
  const uint32_t e = min(__reduce_max_sync(0xffffffffu, max(m & 0x7fffu, (m >> 16) & 0x7fffu)) >> 7, 252u);
  if (e > 140) {
#pragma unroll
    for (int i = 0; i < 32; i++) x[i] = bmul2(x[i], 15u * 0x00800080u);
  }
  const uint32_t sc = (e > 140 ? 253u - e : 141u - e) * 0x00800080u;
#pragma unroll
  for (int i = 0; i < 8; i++) {
    uint32_t y[4];
#pragma unroll
    for (int n = 0; n < 4; n++) {
      const uint32_t w = bmul2(x[4 * i + n], sc);
      y[n] = (w & 0x7fff7fffu) * 7u + w;
    }
    stsm4((dst ^ ((i >> 1) << 4)) + (i & 1) * 2048, y[0], y[1], y[2], y[3]);
  }
  return e;
}
#define RFENCE 1
#define UDESC 1
#define QF 0
#define KF 1
#define LATE 0
#define PPACE2 PPACE
#define PPACE3 (LATE ? 1 : PPACE)
#define C1DELAY 200
#define SAMP 128
#define PD1 600
#define PD2 500
#define SPLIT0 1
#define NSL 2
#define FW 3
#define PD3 900
#define ORS 1
#define UTV 1
constexpr int UT = UTV;
#define TREL 15
#define PHL 0
#define CS 3
#define PRE 3
#define QD 4
#define TAIL 3
#define DBG 0
#define XPF 3
#define PSTART 5
#define HSTART 3
#define PF0 28
#define PPACE 80
#define FDELAY 100
#define PH0 2
#define QA 2
#define QB 3
#define QC 2
#define S1POS 2

__global__ void __cluster_dims__(2, 1, 1) __launch_bounds__(kThreads, 1)
fused_kernel(const __grid_constant__ Params P) {
  extern __shared__ __align__(1024) uint8_t smem[];
  if (threadIdx.x == 0) { prefetch_map(&P.x); prefetch_map(&P.w); prefetch_map(&P.wk); prefetch_map(blockIdx.x & 1 ? &P.v : &P.k); }
  const uint32_t sb = __shfl_sync(0xffffffffu, (uint32_t)__cvta_generic_to_shared(smem), 0);
  const int tid = threadIdx.x, lane = tid & 31;
  const int warp = __shfl_sync(0xffffffffu, tid >> 5, 0);
  const int bc = blockIdx.x >> 1, late = ((bc - 36) * 37) >> 8;
  const int rp = bc < 4 ? 0 : bc < 36 ? (bc - 4) & 7 : bc - 35 - 7 * late, j = bc < 4 ? 4 + bc : bc < 36 ? (bc - 4) >> 3 : 4 + late;
  const int rho = blockIdx.x & 1, cl = 8 * rp + j, cta = 2 * cl + rho, r = rp * 2 + rho;
  auto bar = [&](int i) { return sb + SM_BAR + 8u * i; };
  TSTAMP(tid == 0, 0); GSTAMP(tid == 0, 30);
  auto load_stage = [&](int it) {
    const uint32_t st = sb + (it & 3) * QKV_STAGE, fb = bar(B_QKV_FULL + (it & 3));
    mbar_expect(fb, QKV_STAGE);
    tma2d_mc(st + 24576 + rho * 4096, &P.wk, 1024 + 128 * j + 64 * rho, 32 * it, fb);
    tma3d_mc(st + 8192 + rho * 8192, &P.w, 0, 32 * it, 32 * rho + 2 * j, fb);
    tma2d(st, &P.x, 32 * it, 128 * r, fb);
  };
  if (warp == 8 && elect()) {
    mbar_init(bar(SPLIT0 ? B_FIRST : B_QKV_FULL), 1);
    mbar_expect(bar(SPLIT0 ? B_FIRST : B_QKV_FULL), SPLIT0 ? 16384 : QKV_STAGE);
    tma2d(sb, &P.x, 0, 128 * r, bar(SPLIT0 ? B_FIRST : B_QKV_FULL));
    tma3d(sb + 24576, &P.w, 0, 0, 16 + 2 * j, bar(SPLIT0 ? B_FIRST : B_QKV_FULL));
    if (SPLIT0) { mbar_init(bar(B_QKV_FULL), 1); mbar_expect(bar(B_QKV_FULL), 16384); }
    tma3d(sb + 8192, &P.w, 0, 0, 2 * j, bar(B_QKV_FULL));
    tma3d(sb + 16384, &P.w, 0, 0, 32 + 2 * j, bar(B_QKV_FULL));
    for (int i = 1; i < 5; i++) mbar_init(bar(B_QKV_FULL + i), 1);
    asm volatile("fence.mbarrier_init.release.cluster;" ::: "memory");
  }
  LOOPSTAMP(3, tid == 256, 13);
  __syncwarp();
  cluster_arrive();

  if (warp < 8) {
    asm volatile("setmaxnreg.inc.sync.aligned.u32 224;");
    const int wg = warp >> 2, wq = warp & 3;
    const int never = __shfl_sync(0xffffffffu, P.zero, 0);
    const uint32_t orow = wq * 2048 + (lane & 15) * 128, ox = ((lane >> 4) ^ (lane & 7)) << 4;
    float aq[64];
    Fft F;
    uint32_t a1[32];
    {
      float ak[64], avq[128];
      auto k_step = [&](uint32_t st, int kk, int acc) {
        mma_tn(ak, make_desc(st + 24576 + wg * 4096 + kk * 2048, 4096, 1024, 1), make_desc(st + kk * 32, 16, 512, 2), acc);
      };
      auto vq_step = [&](uint32_t st, int kk, int acc) {
        mma_nt256(avq, make_desc(st + wg * 4096 + kk * 32, 16, 512, 2), make_desc(st + 8192 + kk * 2048, 4096, 1024, 1), acc);
      };
#pragma unroll
      for (int i = 0; i < 64; i++) { ak[i] = 1.f; avq[i] = 1.f; avq[64 + i] = 0.f; }
      pin<64>(ak); pin<128>(avq);
      cluster_wait();
      cluster_arrive();
      cluster_wait();
      LOOPSTAMP(3, tid == 0, 17);
      if (SPLIT0) {
        mbar_wait(bar(B_FIRST), 0);
        TSTAMP(tid == 0, 1);
        wg_fence();
        k_step(0, 0, 1); k_step(0, 1, 1);
        wg_commit();
        mbar_wait(bar(B_QKV_FULL), 0);
        wg_fence();
        vq_step(0, 0, 1); vq_step(0, 1, 1);
        wg_commit();
      }
#pragma unroll 1
      for (int it = SPLIT0; it < 29; ++it) {
        mbar_wait(bar(B_QKV_FULL + (it & 3)), (it >> 2) & 1);
        TSTAMP(tid == 0 && it == 0, 1); TSTAMP(tid == 0 && it == 4, 6); TSTAMP(tid == 0 && it == 12, 29); TSTAMP(tid == 0 && it == 20, 27); LOOPSTAMP(1, tid == 0 && it < 27, 1 + it); LOOPSTAMP(3, tid == 0 && it < 12, 1 + it);
        const uint32_t st = (it & 3) * QKV_STAGE;
        wg_fence();
        k_step(st, 0, 1);
        wg_commit();
        wg_wait<1>();
        arrive_both(bar(B_QKV_EMPTY + ((it - 1) & 3)), lane, SPLIT0 || it > 0);
        wg_fence();
        vq_step(st, 0, 1);
        k_step(st, 1, 1);
        vq_step(st, 1, 1);
        wg_commit();
      }
#pragma unroll 1
      for (int s = 1; s < 4; ++s) {
        mbar_wait(bar(B_QKV_FULL + s), 1);
        wg_fence();
        k_step(s * QKV_STAGE, 0, 1);
        k_step(s * QKV_STAGE, 1, 1);
        wg_commit();
      }
      uint32_t pk[32];
      auto phi_k = [&](int i0, int i1) {
#pragma unroll
        for (int i = i0; i < i1; i++) { pk[i] = elu1(ak[2 * i], ak[2 * i + 1]); asm volatile("" : "+r"(pk[i]) :: "memory"); }
        if (KF) sched_fence(never, i0);
      };
#pragma unroll
      for (int n = 0; n < 6; n++) {
        wg_fence();
        vq_step((1 + (n >> 1)) * QKV_STAGE, n & 1, 1);
        wg_commit();
        if (n == 0) {
          wg_wait<1>();
          pin<64>(ak);
          TSTAMP(tid == 0, 2);
          bar_sync(1, 256);
        }
        phi_k(n ? PH0 + (32 - PHL - PH0) * (n - 1) / 5 : 0, PH0 + (32 - PHL - PH0) * n / 5);
      }
      mbar_wait(bar(B_SIG_READY), 0);
      if (!S1SS) ldsm4_t(F.fa, sb + SM_F1 + (lane >> 4) * 1024 + wq * 256 + (lane & 15) * 16);
      if (!S1SS) ldsm4_t(F.fa + 4, sb + SM_F1 + 2048 + (lane >> 4) * 1024 + wq * 256 + (lane & 15) * 16);
      const uint4 tw = lds128(sb + SM_TW + (tid & 127) * 16);
      F.tw[0] = {tw.x, tw.y}; F.tw[1] = {tw.z, tw.w};
      F.vld = sb + ((lane >> 4) * 8 + (lane & 7)) * 128 + (((2 * wq + ((lane >> 3) & 1)) ^ (lane & 7)) << 4);
      F.dF2a = make_desc(SM_F2, 128, 512, 0) + (UDESC ? (uint64_t)never * 0x100000001ull : 0); F.dF2b = F.dF2a + 16;
      F.vst = sb + (16 * wq + (lane & 7)) * 128 + (((lane >> 3) ^ (lane & 7)) << 4);
      wg_wait<0>();
      pin<128>(avq);
      if (S1POS == 0) F.stage1(a1, SM_SIG + wg * 8192);
      arrive_both(bar(B_QKV_DONE), lane);
      TSTAMP(tid == 0, 3);
#pragma unroll
      for (int t = 0; t < 8; t++) {
        const float* b = avq + 64 + 8 * t;
        if (S1POS == 3 && t == 4) F.stage1(a1, SM_SIG + wg * 8192);
        stsm4(sb + (t >> 2) * SLOT + wg * 8192 + orow + (ox ^ ((t & 3) << 5)), pack_bf16(b[0], b[1]), pack_bf16(b[2], b[3]), pack_bf16(b[4], b[5]), pack_bf16(b[6], b[7]));
      }
#pragma unroll
      for (int i = 0; i < 64; i++) aq[i] = avq[i];
      if (S1POS == 4) F.stage1(a1, SM_SIG + wg * 8192);
      if (PHL) { sched_fence(never, 90); phi_k(32 - PHL, 32); }
      fence_async_smem();
      bar_sync(1, 256);
      float dkv[36];
#pragma unroll
      for (int ks = 0; ks < 8; ks++) {
        const uint32_t va = wg * SLOT + ks * 2048;
        const uint64_t db = make_desc(va, SM_ONES - va, 1024, 1);
        uint32_t a[4];
        pin<4>(pk + 4 * ks);
#pragma unroll
        for (int i = 0; i < 4; i++) a[i] = add_eps(pk[4 * ks + i]);
        wg_fence();
        if (ks == 0) mma_kv_init(dkv, a[0], a[1], a[2], a[3], db);
        else mma_kv_acc(dkv, a[0], a[1], a[2], a[3], db);
      }
      wg_commit();
      uint8_t* box = g_xch[warp * 16 + j] + 2 * SLOT + r * KV_SLICE + lane * 16;
      uint8_t* zbox = box + (lane & 1) * 8 * XCH_BYTES + 512 + (lane & 28) - lane * 16;
      keep(box); keep(zbox);
      if (S1POS == 1) F.stage1(a1, SM_SIG + wg * 8192);
      mbar_wait(bar(B_ZEROED), 0);
      wg_wait<S1POS == 1>();
      pin<36>(dkv);
      if (S1POS == 2) F.stage1(a1, SM_SIG + wg * 8192);
      TSTAMP(tid == 0, 4);
      auto put = [&](const float* d) {
#pragma unroll
        for (int m = 0; m < 2; m++)
          asm volatile("st.relaxed.gpu.global.v4.b32 [%0], {%1,%2,%3,%4};" :: "l"(box + m * 8 * XCH_BYTES), "r"(pack_bf16(d[2 * m], d[2 * m + 1])),
                       "r"(pack_bf16(d[2 * m + 4], d[2 * m + 5])), "r"(pack_bf16(d[2 * m + 8], d[2 * m + 9])), "r"(pack_bf16(d[2 * m + 12], d[2 * m + 13])) : "memory");
      };
      if (wq < 2) put(dkv); else put(dkv + 16);
      asm volatile("{\n.reg .pred p;\nsetp.eq.b32 p, %2, 0;\n@p st.relaxed.gpu.global.b32 [%0], %1;\n}" :: "l"(zbox), "f"(lane & 1 ? dkv[34] : dkv[32]), "r"(lane & 2) : "memory");
      __syncwarp();
      mbar_arrive_if(bar(B_KVP), lane == 0);
      TSTAMP(tid == 0, 5);
    }

    uint32_t pq[32];
    auto phi_q = [&](int i0, int i1) {
      pin_range(aq, 2 * i0, 2 * i1);
#pragma unroll
      for (int i = i0; i < i1; i++) { pq[i] = add_eps(elu1(aq[2 * i], aq[2 * i + 1])); keep(pq[i]); }
      if (QF && i1 > i0) sched_fence(never, 40 + i0);
    };
    uint32_t a2[32];
    float by[16];
    auto conv_pair = [&](uint32_t sa, uint32_t ya, uint32_t first) {
      const uint32_t sc = sa + SLOT;
      uint32_t b1[32], b2[32], a3[16], b3[16];
      float ay[16];
      Cx pa[2], pb[2];
      F.stage1(b1, sc);
      F.prod01(a2, pa, a3);
      F.prod23(a2, pa, a3);
      uint32_t va[16];
      wg_wait<1>(); pin<32>(b1); pin<8>(a3);
      if (CS == 0) {
        F.inv<0>(a3, sa);
        F.fwd<0>(b1, b2);
        wg_wait<1>(); pin<8>(a3 + 8);
        F.inv<1>(a3, sa);
        F.fwd<1>(b1, b2); F.fwd<2>(b1, b2); F.fwd<3>(b1, b2);
        F.last(ay, sa, wg);
        wg_wait<3>(); pin<16>(b2);
        F.prod01(b2, pb, b3);
        wg_wait<2>(); pin<16>(b2 + 16);
      } else if (CS == 1) {
        F.inv<0>(a3, sa);
        F.fwd<0>(b1, b2);
        wg_wait<1>(); pin<8>(a3 + 8);
        F.inv<1>(a3, sa);
        F.fwd<1>(b1, b2); F.fwd<2>(b1, b2); F.fwd<3>(b1, b2);
        F.last_load(va, sa, wg);
        wg_wait<2>(); pin<16>(b2);
        F.prod01(b2, pb, b3);
        F.last_mma(ay, va);
        wg_wait<2>(); pin<16>(b2 + 16);
      } else if (CS == 2) {
        F.fwd<0>(b1, b2); F.fwd<1>(b1, b2);
        F.inv<0>(a3, sa);
        wg_wait<2>(); pin<8>(a3 + 8);
        F.inv<1>(a3, sa);
        F.fwd<2>(b1, b2); F.fwd<3>(b1, b2);
        F.last_load(va, sa, wg);
        wg_wait<2>(); pin<16>(b2);
        F.prod01(b2, pb, b3);
        F.last_mma(ay, va);
        wg_wait<2>(); pin<16>(b2 + 16);
      } else if (CS == 3) {
        F.fwd<0>(b1, b2); F.fwd<1>(b1, b2);
        F.inv<0>(a3, sa);
        F.fwd<2>(b1, b2);
        wg_wait<3>(); pin<8>(a3 + 8);
        F.inv<1>(a3, sa);
        F.fwd<3>(b1, b2);
        F.last_load(va, sa, wg);
        wg_wait<2>(); pin<16>(b2);
        F.prod01(b2, pb, b3);
        F.last_mma(ay, va);
        wg_wait<2>(); pin<16>(b2 + 16);
      } else {
        F.fwd<0>(b1, b2); F.fwd<1>(b1, b2); F.fwd<2>(b1, b2); F.fwd<3>(b1, b2);
        wg_wait<4>(); pin<8>(a3 + 8);
        F.inv<0>(a3, sa);
        F.inv<1>(a3, sa);
        wg_wait<2>(); pin<16>(b2);
        F.prod01(b2, pb, b3);
        F.last(ay, sa, wg);
        wg_wait<2>(); pin<16>(b2 + 16);
      }
      F.prod23(b2, pb, b3);
      mbar_wait(bar(B_RDY1), first);
      wg_wait<1>(); pin<8>(b3); pin<16>(ay);
      mbar_arrive_if(bar(B_SLOT_FREE), lane == 0);
      F.inv<0>(b3, sc);
      Fft::store_y(ay, ya);
      wg_wait<0>(); pin<8>(b3 + 8);
      F.inv<1>(b3, sc);
    };
    const bool ylocal = (wq >> 1) == rho;
    const uint32_t yoff = sb + (wq & 1) * 1024 + ((lane ^ wg ^ (2 * rho)) << 4);
    const uint32_t ya0 = yoff + (ylocal ? SM_Y0 + wg * 8192 : SM_YT + wg * 4096), ya1 = (yoff ^ 64) + (ylocal ? SM_SIG + wg * 8192 : SM_YT + wg * 4096);
    auto pair_done = [&](uint32_t ya, int seg) {
      pin<16>(by);
      Fft::store_y(by, (ya ^ 32) + 2048);
      if (!RFENCE) fence_async_smem();
      __syncwarp();
      mbar_arrive_if(bar(B_SEG + 2 * seg + wg), lane == 0);
    };
    const uint32_t s0 = SM_SIG + wg * 8192, s1 = s0 + 2 * SLOT;
    phi_q(0, QA);
    wg_wait<0>(); pin<32>(a1);
    bar_sync(2 + wg, 128);
    F.fwd<0>(a1, a2); phi_q(QA, QA + QB);
    F.fwd<1>(a1, a2); phi_q(QA + QB, QA + 2 * QB);
    F.fwd<2>(a1, a2); phi_q(QA + 2 * QB, QA + 3 * QB);
    F.fwd<3>(a1, a2);
    phi_q(QA + 3 * QB, QA + 3 * QB + QC);
    wg_wait<0>(); pin<32>(a2);
#pragma unroll 1
    for (uint32_t sa = s0;; sa += 2 * SLOT + P.zero) {
    conv_pair(sa, sa == s1 ? ya1 : ya0, sa != s1);
    if (sa == s1) break;
    if (PRE & 1) {
      F.stage1(a1, s1);
      phi_q(QA + 3 * QB + QC, QA + 3 * QB + QC + QD);
      F.last(by, s0 + SLOT, wg);
      phi_q(QA + 3 * QB + QC + QD, 32);
      wg_wait<0>();
    } else {
      F.last(by, s0 + SLOT, wg);
      F.stage1(a1, s1);
      phi_q(QA + 3 * QB + QC, 32);
      wg_wait<1>();
    }
    pair_done(ya0, 0);
    TSTAMP(tid == 0, 7); TSTAMP(tid == 128, 10);
    {
      float dn[4][20];
      wg_wait<0>(); pin<32>(a1);
      bar_sync(2 + wg, 128);
      if (FW > 0) F.fwd<0>(a1, a2);
      if (FW > 1) F.fwd<1>(a1, a2);
      if (FW > 2) F.fwd<2>(a1, a2);
      if (FW > 3) F.fwd<3>(a1, a2);
      mbar_wait(bar(B_KV_READY), 0);
      TSTAMP(tid == 0, 8);
      auto head_mma = [&](int h) {
        wg_fence();
        const uint64_t db = make_desc(SM_KV + h * 2560, 640, 128, 0);
        const uint32_t* a = pq + 8 * h;
        mma_o_init(dn[h], a[0], a[1], a[2], a[3], db);
        mma_o_acc(dn[h], a[4], a[5], a[6], a[7], db + (1280 >> 4));
        wg_commit();
      };
      auto head_store = [&](int h) {
        pin<20>(dn[h]);
        const float i0 = rcp(dn[h][16] + 1e-6f), i1 = rcp(dn[h][18] + 1e-6f);
        const uint32_t p0 = pack_bf16(i0, i0), p1 = pack_bf16(i1, i1);
#pragma unroll
        for (int hf = 0; hf < 2; hf++) {
          const float* a = dn[h] + 8 * hf;
          const uint32_t dst = sb + (h >> 1) * SLOT + wg * 8192 + orow + (ox ^ (((h & 1) * 2 + hf) << 5));
          uint32_t o[4];
#pragma unroll
          for (int i = 0; i < 4; i++) o[i] = bmul2(pack_bf16(a[2 * i], a[2 * i + 1]), i & 1 ? p1 : p0);
          stsm4(dst, o[0], o[1], o[2], o[3]);
          if (ORS)
#pragma unroll
            for (int i = 0; i < 4; i++) pq[8 * h + 4 * hf + i] = o[i];
        }
        if (h & 1) { if (!RFENCE) fence_async_smem(); __syncwarp(); mbar_arrive_if(bar(B_O_WRITTEN + (h >> 1)), lane == 0); }
      };
      head_mma(0); head_mma(1);
      wg_wait<1>(); head_store(0);
      mbar_wait(bar(B_KV_READY + 1), 0);
      head_mma(2);
      wg_wait<1>(); head_store(1);
      head_mma(3);
      if (FW < 1) F.fwd<0>(a1, a2);
      if (FW < 2) F.fwd<1>(a1, a2);
      wg_wait<1 + (FW < 1) + (FW < 2)>(); head_store(2);
      if (FW < 3) F.fwd<2>(a1, a2);
      if (FW < 4) F.fwd<3>(a1, a2);
      wg_wait<4 - FW>(); head_store(3);
      TSTAMP(tid == 0, 9);
      wg_wait<0>();
      pin<32>(a2);
    }
    }
    if (!(PRE & 2)) F.last(by, s1 + SLOT, wg);

    float acc[64];
    auto stage_mma = [&](int s, int kk, int accumulate) {
      mma_nt(acc, make_desc(((A_SLOTS >> (4 * s)) & 15) * SLOT + wg * 8192 + kk * 32, 16, 1024, 1),
             make_desc(((B_SLOTS >> (4 * s)) & 15) * SLOT + kk * 2048, 8192, 1024, 1), accumulate);
    };
    {
      auto own_mma = [&](int n) {
        const uint64_t db = make_desc((4 + (n >> 2)) * SLOT + (n & 3) * 2048, 8192, 1024, 1);
        if (!ORS) stage_mma(n >> 2, n & 3, n);
        else if (n == 0) mma_own_init(acc, pq[0], pq[1], pq[2], pq[3], db);
        else mma_own_acc(acc, pq[4 * n], pq[4 * n + 1], pq[4 * n + 2], pq[4 * n + 3], db);
      };
      mbar_wait(bar(B_OUT_FULL), 0);
      wg_fence();
      own_mma(0); own_mma(1);
      wg_commit();
      if (PRE & 2) {
        F.last(by, s1 + SLOT, wg);
        wg_fence();
        own_mma(2);
        wg_commit();
      }
      wg_wait<1>();
      mbar_arrive_if(bar(B_CONV_DONE), lane == 0);
      cluster_arrive();
      wg_fence();
      if (!(PRE & 2)) own_mma(2);
      own_mma(3);
      wg_commit();
      pair_done(ya1, 1);
      TSTAMP(tid == 0, 11); TSTAMP(tid == 128, 12);
      if (ORS) {
        mbar_wait(bar(B_OUT_FULL + 1), 0);
        wg_fence();
        own_mma(4);
        wg_commit();
        wg_wait<1>();
        arrive_both(bar(B_OUT_EMPTY), lane);
        wg_fence();
        own_mma(5); own_mma(6); own_mma(7);
        wg_commit();
      }
      int s = 1 + ORS, sprev = ORS;
      uint32_t ph = 0;
#pragma unroll 1
      for (int ks = 1 + ORS; ks < 12; ++ks) {
        mbar_wait(bar(B_OUT_FULL + s), ph);
        LOOPSTAMP(2, tid == 0, 1 + ks);
        TSTAMP(tid == 0 && ks == 2, 13); TSTAMP(tid == 0 && ks == 9, 14);
        wg_fence();
        stage_mma(s, 0, 1);
        wg_commit();
        wg_wait<1>();
        arrive_both(bar(B_OUT_EMPTY + sprev), lane);
        wg_fence();
#pragma unroll
        for (int kk = 1; kk < 4; kk++) stage_mma(s, kk, 1);
        wg_commit();
        sprev = s;
        if (++s == 5) { s = 0; ph ^= 1; }
      }
#pragma unroll UT
      for (int ks = 12; ks < 16; ++ks) {
        asm volatile("{\n.reg .pred p;\nsetp.ne.b32 p, %0, 0;\n@p bar.sync 1, 256;\n}" :: "r"((int)(ks == 16 - TAIL && wg)) : "memory");
        mbar_wait(bar(B_OUT_FULL + s), ks == 15);
        wg_fence();
#pragma unroll
        for (int kk = 0; kk < 4; kk++) stage_mma(s, kk, 1);
        wg_commit();
        asm volatile("{\n.reg .pred p;\nsetp.ne.b32 p, %0, 0;\n@p bar.arrive 1, 256;\n}" :: "r"((int)(TAIL && ks == TREL && !wg)) : "memory");
        if (++s == 5) s = 0;
      }
    }
    wg_wait<0>(); pin<64>(acc);
    TSTAMP(tid == 0, 15); TSTAMP(tid == 128, 16);
#pragma unroll
    for (int hf = 0; hf < 2; hf++) {
      const uint32_t dst = sb + hf * SLOT + wg * 8192;
#pragma unroll
      for (int t = 0; t < 4; t++) {
        const float* a = acc + 32 * hf + 8 * t;
        stsm4(dst + orow + (ox ^ (t << 5)), pack_bf16(a[0], a[1]), pack_bf16(a[2], a[3]), pack_bf16(a[4], a[5]), pack_bf16(a[6], a[7]));
      }
      fence_async_smem();
      __syncwarp();
      if ((!(DBG & 4) || wg) && elect()) { tma2d_store(&P.outa, dst + wq * 2048, 128 * j + 64 * hf, 128 * r + 16 * warp); bulk_commit(); }
    }
    const bool stale = __any_sync(0xffffffffu, acc[0] != acc[0] || acc[2] != acc[2] || (DBG & 256));
    if (elect()) bulk_wait_read();
    TSTAMP(tid == 128, 17);
    __syncwarp();
    cluster_wait();
    TSTAMP(tid == 128, 28); GSTAMP(tid == 128, 31);
    if (stale) {
      __threadfence();
#pragma unroll
      for (int i = 0; i < 64; i++) acc[i] = 0.f;
      const int row = warp * 16 + (lane >> 2);
#pragma unroll 1
      for (int k = 0; k < 1024; k += 2) {
        const uint8_t* src = g_xch[r * 8 + (k >> 7)] + ((k >> 6) & 1) * SLOT + row * 128 + ((((k >> 3) ^ row) & 7) << 4) + (k & 7) * 2;
        uint32_t a[2];
        int n = 0;
        do { a[0] = ld_relaxed(src); a[1] = ld_relaxed(src + 1024); } while (!all_arrived<2>(a) && ++n < kSpinLimit);
#pragma unroll 1
        for (int e = 0; e < 2; e++) {
          const float a0 = e ? bf_hi(a[0]) : bf_lo(a[0]), a1 = e ? bf_hi(a[1]) : bf_lo(a[1]);
          const uint32_t* wrow = reinterpret_cast<const uint32_t*>(P.wo_ptr + (k + e) * 1024 + 128 * j) + (lane & 3);
#pragma unroll
          for (int i = 0; i < 16; i++) {
            const uint32_t w = __ldg(wrow + 4 * i);
            acc[4 * i] += a0 * bf_lo(w); acc[4 * i + 1] += a0 * bf_hi(w);
            acc[4 * i + 2] += a1 * bf_lo(w); acc[4 * i + 3] += a1 * bf_hi(w);
          }
        }
      }
      uint32_t* op = reinterpret_cast<uint32_t*>(P.out_ptr + (128 * r + row) * 2048 + 128 * j) + (lane & 3);
#pragma unroll
      for (int i = 0; i < 32; i++) op[(i & 1) * 8192 + (i >> 1) * 4] = pack_bf16(acc[2 * i], acc[2 * i + 1]);
    }
  } else {
    asm volatile("setmaxnreg.dec.sync.aligned.u32 56;");
    if (warp == 8) {
      cluster_wait();
      cluster_arrive();
      LOOPSTAMP(3, tid == 256, 15);
#pragma unroll 1
      for (int it = 1; it < 4; it++) if (elect()) load_stage(it);
      LOOPSTAMP(3, tid == 256, 16);
      __syncwarp();
      cluster_wait();
    } else {
      if (elect()) {
#pragma unroll 1
        for (int g = warp - 9; g < 8; g += 3)
          for (int i = 0; i < 8; i++) mbar_init(bar(8 * g + i), 1u << ((BAR_LOG2 >> (4 * g)) & 7));
        if (warp == 11) for (int i = 0; i < 6; i++) mbar_expect(bar(B_H_FULL + i), i < 2 ? 12288 : i < 5 ? 8192 : 16);
        asm volatile("fence.mbarrier_init.release.cluster;" ::: "memory");
      }
      LOOPSTAMP(3, tid == 288, 14);
      __syncwarp();
      cluster_wait();
      cluster_arrive();
#pragma unroll
      for (int i = 0; i < 3; i++) asm volatile("st.shared.v4.b32 [%0], {%1,%1,%1,%1};" :: "r"(sb + SM_F1 + i * 1536 + (tid - 288) * 16), "r"(0xffffffffu) : "memory");
      fence_async_smem();
      asm volatile("bar.arrive 5, 128;" ::: "memory");
      if ((sb & 0xffffff) != SM_BASE) __trap();
      cluster_wait();
    }
    auto chunk = [&](int ks) { const int c = ks >= 9, t = ks - 2 - 7 * c; return ks < 2 ? 2 * j + ks : 2 * (t + (t >= j)) + c; };
    auto load_q = [&](int n) {
      mbar_expect(bar(B_Q_FULL + (n & 3)), 4096);
      tma2d(sb + SM_Q + (n & 3) * 4096, &P.q, cl * 16, rho * 1024 + n * 128, bar(B_Q_FULL + (n & 3)));
    };
    auto load_wo = [&](uint32_t dst, int c, uint32_t bytes, uint32_t fb) {
      mbar_expect(fb, bytes);
      tma2d_mc(dst + rho * 8192, &P.wo, 128 * j + 64 * rho, c * 64, fb);
    };
    uint8_t* const xch = g_xch[r * 8 + j];
    if (warp == 8) {
      int ck = 0, cw = 0, cph = 1;
      const CUtensorMap* kvmap = rho ? &P.v : &P.k;
#pragma unroll 1
      for (int it = 4 - XPF; it < 32 || (ck < 20 && it < kSpinLimit); ++it) {
        if (it >= 4 && it < 32) {
          mbar_wait(bar(B_QKV_EMPTY + (it & 3)), ((it >> 2) - 1) & 1);
          if (elect()) load_stage(it);
          LOOPSTAMP(3, lane == 0 && it < 12, 15 + it);
        }
        if (it < 32 - XPF) {
          if (((it + XPF) & 7) == rp && elect()) {
            l2_prefetch2d(&P.wk, 1024 + 128 * j + 64 * rho, 32 * (it + XPF));
            l2_prefetch3d(&P.w, 0, 32 * (it + XPF), 32 * rho + 2 * j);
          }
          if (((it + XPF) & 7) == j && elect()) l2_prefetch2d(&P.x, 32 * (it + XPF), 128 * r);
        }
        const int n = it - HSTART;
        if (n >= 0 && n < 8) {
          if (elect()) bulk_load(sb + SM_SIG + n * 8192 + 4096, P.ssm_k + (size_t)(cta * 8 + n) * 2048, 4096, bar(B_H_FULL + (n >= 3) + (n >= 6)));
        } else if (n >= 8 && n < 19) {
          if (n == 8) bar_sync(5, 128);
          if (elect()) bulk_store(xch + (n - 8) * 4096, sb + SM_F1, 4096);
        } else if (it >= PF0 && it < PF0 + 4) {
          if (elect()) l2_prefetch(it < PF0 + 2 ? P.wo_ptr + cta * 8192 + (it - PF0) * 4096 : P.q_ptr + (512 + (it - PF0 - 2) * 1024 + cta * 4) * 1024, 8192);
        }
        if (ck < 16 && it >= PSTART && __all_sync(0xffffffffu, mbar_test(bar(B_PREP_EMPTY + cw), cph))) {
          if (elect()) {
            mbar_expect(bar(B_PREP_FULL + cw), 8704);
            tma3d_mc(sb + SM_STG + cw * 8704 + rho * 4608, kvmap, cl * 16, ck * 8 - 1 + rho, 0, bar(B_PREP_FULL + cw));
          }
          ++ck;
          if (++cw == 3) { cw = 0; cph ^= 1; }
        } else if (ck >= 16 && ck < 20 && __all_sync(0xffffffffu, mbar_test(bar(B_STG_FREE), 0))) {
          if (elect()) load_q(ck - 16);
          ++ck;
        }
      }
      if (elect()) {
        bulk_commit();
        bulk_wait_read();
        mbar_expect(bar(B_SIG_READY), 10240);
        bulk_load(sb + SM_TW, g_tables, 10240, bar(B_SIG_READY));
        flag_add(&g_ready);
        prefetch_map(&P.wo); prefetch_map(&P.outa); prefetch_map(&P.q);
        const unsigned epoch = ld_relaxed(&g_epoch[cta]) + 1;
        g_epoch[cta] = epoch;
        flag_wait(&g_ready, kCtas * epoch);
        mbar_arrive(bar(B_ZEROED));
      }
      __syncwarp();
      mbar_wait(bar(B_QKV_DONE), 0);
#pragma unroll 1
      for (int ks = 0; ks < 4; ++ks) if (elect()) load_wo(sb + (4 + ks) * SLOT, chunk(ks), ks < 2 ? SLOT : 2 * SLOT, bar(B_OUT_FULL + ks));
    } else {
      const int at = tid - 288, aw = warp - 9, ch0 = cta * 8;
      {
        const uint32_t stg = sb + SM_STG + aw * 8704, pf = bar(B_PREP_FULL + aw), pe = bar(B_PREP_EMPTY + aw);
        const uint4 wv = __ldg(reinterpret_cast<const uint4*>(P.shift_k + (ch0 + 2 * (lane & 3)) * 4));
        const float skip = __bfloat162float(P.ssm_d[ch0 + (lane & 7)]);
        const uint32_t w0 = __byte_perm(wv.x, wv.z, 0x5410), w1 = __byte_perm(wv.x, wv.z, 0x7632);
        const uint32_t w2 = __byte_perm(wv.y, wv.w, 0x5410), w3 = __byte_perm(wv.y, wv.w, 0x7632);
        auto swz32 = [](uint32_t a) { return a ^ ((a >> 3) & 16); };
        const uint32_t kl = (lane >> 3) * 288 + (lane & 7) * 32 + rho * 16;
        const uint32_t ka = stg + swz32(kl + 32), kh = stg + swz32(kl + 12 * 288), va = stg + 4608 + swz32(lane * 32 + rho * 16);
        const uint32_t ua = sb + SM_SIG + (lane & 7) * 8192 + (((lane >> 3) ^ (lane & 7)) << 4);
        uint32_t eh = 0;
#pragma unroll 1
        for (int ck = aw, rd = 0; rd < 9; ck += 3, ++rd) {
          if (rd == 6) {
            bar_sync(4, 96);
            if (at == 64) mbar_arrive(bar(B_STG_FREE));
          }
          const int c = rd < 6 ? ck : ck - 18;
          if (c < 8) {
            uint32_t x[32], dst = sb + SM_SIG + c * 8192;
            if (rd < 6) {
              mbar_wait(bar(B_H_FULL + rd), 0);
#pragma unroll
              for (int i = 0; i < 8; i++) ldsm4(x + 4 * i, dst + 4096 + i * 512 + lane * 16);
              const float d = __shfl_sync(0xffffffffu, skip, c);
              if (lane == 0) x[0] = pack_bf16(bf_lo(x[0]) + d, bf_hi(x[0]));
              dst += 4096 + (lane >> 1) * 128 + ((((lane & 1) * 4) ^ ((lane >> 1) & 7)) << 4);
            } else {
#pragma unroll
              for (int i = 0; i < 8; i++) ldsm4_t(x + 4 * i, dst + i * 512 + ((lane ^ c) << 4));
              dst += (lane >> 4) * 1024 + (lane & 7) * 128 + ((((lane >> 1) & 4) ^ (lane & 7)) << 4);
            }
            const uint32_t e = normalize(x, dst);
            if (rd < 6) {
              eh |= e << (8 * rd);
            } else {
              const int f = min(max((int)(e + (eh & 255)) - 125, 0), 254);
              eh >>= 8;
              if (lane == 0) asm volatile("st.shared.b16 [%0], %1;" :: "r"(sb + SM_SC + rho * 16 + 2 * c), "h"((uint16_t)(f << 7)) : "memory");
            }
          }
          if (ck < 16) {
            mbar_wait(pf, rd & 1);
            uint32_t k[20], v[16];
            ldsm4(k, kh);
#pragma unroll
            for (int m = 0; m < 4; m++) { ldsm4(k + 4 + 4 * m, (ka ^ ((m & 1) << 4)) + m * 1152); ldsm4(v + 4 * m, va + m * 1024); }
            arrive_both(pe + ((k[3] | k[4] | k[8] | k[12] | k[16] | v[0] | v[4] | v[8] | v[12]) & P.zero), lane, ck < 13);
#pragma unroll
            for (int m = 0; m < 4; m++) {
              uint32_t u[4];
#pragma unroll
              for (int n = 0; n < 4; n++) {
                const uint32_t* kk = k + 4 + 4 * m + n;
                u[n] = bmul2(bfma2(kk[0], w0, bfma2(kk[-1], w1, bfma2(kk[-2], w2, bmul2(kk[-3], w3)))), v[4 * m + n]);
              }
              stsm4_t((ua ^ (m << 6)) + ck * 256, u[0], u[1], u[2], u[3]);
            }
          }
        }
        fence_async_smem();
        __syncwarp();
        if (lane == 0) mbar_arrive(bar(B_SIG_READY));
        bar_sync(4, 96);
        if (at == 32) {
          const uint4 s = lds128(sb + SM_SC + rho * 16);
          asm volatile("st.async.weak.shared::cluster.mbarrier::complete_tx::bytes.v4.b32 [%0], {%1,%2,%3,%4}, [%5];"
                       :: "r"(peer_addr(sb + SM_SC + rho * 16, rho ^ 1)), "r"(s.x), "r"(s.y), "r"(s.z), "r"(s.w), "r"(peer_addr(bar(B_RDY0), rho ^ 1)) : "memory");
        }
        TSTAMP(at == 0, 20); LOOPSTAMP(4, at == 0, 22);
      }
    }
    __syncwarp();
    {
      const int a4 = warp - 8;
      const uint8_t* part = xch + 2 * SLOT + (lane >> 3) * 4 * KV_SLICE + (a4 * 8 + (lane & 7)) * 16;
      const uint8_t* zpart = xch + 2 * SLOT + (lane & 15) * KV_SLICE + 512 + (a4 * 2 + (lane >> 4)) * 4;
      uint8_t* red = xch + 2 * SLOT + 16 * KV_SLICE + (a4 * 8 + (lane & 7)) * 16 + (lane >> 3) * 4;
      uint8_t* zred = xch + 2 * SLOT + 16 * KV_SLICE + 512 + (a4 * 2 + (lane >> 4)) * 4;
      const uint8_t* all = g_xch[a4 * 32 + j] + 2 * SLOT + 16 * KV_SLICE + lane * 16;
      const uint8_t* zall = all + 512 + (lane & 28) - lane * 16;
      keep(part); keep(zpart); keep(red); keep(zred); keep(all); keep(zall);
      uint32_t v[20];
      int n = 0;
      mbar_wait(bar(B_KVP), 0);
      if (NSL & 1) __nanosleep(PD1); else delay(PD1);
      auto load1 = [&](uint32_t* d) {
#pragma unroll
        for (int i = 0; i < 4; i++) ld_relaxed4(d + 4 * i, part + i * KV_SLICE);
        d[16] = ld_relaxed(zpart);
      };
      do load1(v); while (!all_arrived<17>(v) && ++n < kSpinLimit);
      TSTAMP(tid == 288, 21);
      float lo[4], hi[4], z = __uint_as_float(v[16]);
#pragma unroll
      for (int b = 0; b < 4; b++) {
        lo[b] = (bf_lo(v[b]) + bf_lo(v[4 + b])) + (bf_lo(v[8 + b]) + bf_lo(v[12 + b]));
        hi[b] = (bf_hi(v[b]) + bf_hi(v[4 + b])) + (bf_hi(v[8 + b]) + bf_hi(v[12 + b]));
      }
      const bool u16 = lane & 16, u8 = lane & 8;
#pragma unroll
      for (int b = 0; b < 2; b++) {
        lo[b] = (u16 ? lo[b + 2] : lo[b]) + __shfl_xor_sync(0xffffffffu, u16 ? lo[b] : lo[b + 2], 16);
        hi[b] = (u16 ? hi[b + 2] : hi[b]) + __shfl_xor_sync(0xffffffffu, u16 ? hi[b] : hi[b + 2], 16);
      }
      const float l = (u8 ? lo[1] : lo[0]) + __shfl_xor_sync(0xffffffffu, u8 ? lo[0] : lo[1], 8);
      const float h = (u8 ? hi[1] : hi[0]) + __shfl_xor_sync(0xffffffffu, u8 ? hi[0] : hi[1], 8);
      st_relaxed(red, pack_bf16(l, h));
#pragma unroll
      for (int o = 8; o; o >>= 1) z += __shfl_xor_sync(0xffffffffu, z, o);
      if ((lane & 15) == 0) st_relaxed(zred, pack_bf16(z, z));
      TSTAMP(tid == 288, 22);
      n = 0;
      if (NSL & 1) __nanosleep(PD2); else delay(PD2);
      auto load2 = [&](uint32_t* d) {
#pragma unroll
        for (int i = 0; i < 4; i++) {
          ld_relaxed4(d + 4 * i, all + i * 8 * XCH_BYTES);
          d[16 + i] = ld_relaxed(zall + i * 8 * XCH_BYTES);
        }
      };
      do load2(v); while (!all_arrived<20>(v) && ++n < kSpinLimit);
#pragma unroll
      for (int i = 0; i < 4; i++) {
        const uint32_t dst = sb + SM_KV + (a4 * 4 + i) * 640;
        stsm4(dst + lane * 16, v[4 * i], v[4 * i + 1], v[4 * i + 2], v[4 * i + 3]);
        asm volatile("st.shared.b32 [%0], %1;" :: "r"(dst + 512 + lane * 4), "r"(v[16 + i]) : "memory");
      }
      fence_async_smem();
      __syncwarp();
      if (lane == 0) mbar_arrive(bar(B_KV_READY + (a4 >> 1)));
      TSTAMP(tid == 288, 23);
    }
    if (warp != 10) cluster_arrive();
    if (warp == 8) {
      int s = 4;
      uint32_t ph = 1;
#pragma unroll 1
      for (int ks = 4; ks < 16; ++ks) {
        uint32_t fb = bar(B_OUT_FULL + s), dst = sb + ((B_SLOTS >> (4 * s)) & 15) * SLOT;
        int c = chunk(ks);
        keep(fb); keep(dst); keep(c);
        mbar_wait(bar(ks == 4 ? B_RDY1 : B_OUT_EMPTY + s), ks == 4 ? 0 : ph);
        if (elect()) load_wo(dst, c, 2 * SLOT, fb);
        if (++s == 5) { s = 0; ph ^= 1; }
      }
    } else {
      auto wait_chunks = [&](unsigned mask) {
        unsigned ready;
        int n = 0;
        do {
          ready = __ballot_sync(0xffffffffu, ld_relaxed(g_xch[r * 8 + ((lane >> 1) & 7)] + XCH_FLAG) + 1 > (lane & 1));
        } while ((~ready & mask) && ++n < kSpinLimit);
        return ready;
      };
      if (warp == 9) {
        if (elect()) {
#pragma unroll 1
          for (int c = 0; c < 2; c++) {
            mbar_wait(bar(B_O_WRITTEN + c), 0);
            TSTAMP(c == 0, 19);
            fence_async_smem();
            bulk_store(xch + c * SLOT, sb + c * SLOT, SLOT);
            bulk_commit();
            bulk_wait_read();
            mbar_arrive(bar(B_OT_FREE + c));
            delay(FDELAY);
            st_relaxed(xch + XCH_FLAG, c);
            if (!c) delay(C1DELAY);
            TSTAMP(c == 1, 25);
          }
        }
        __syncwarp();
        wait_chunks(0xaaaa);
        if (lane == 0) mbar_arrive(bar(B_FLAGS1));
      } else if (warp == 10) {
        mbar_wait(bar(B_RDY0), 0);
        mbar_wait(bar(B_QKV_DONE), 0);
#pragma unroll 1
        for (int n = 0; n < 4; n++) {
          const int w = n & 1;
          if (n == 2) for (int i = 0; i < 4; i++) mbar_wait(bar(B_Q_FULL + i), 0);
          mbar_wait(bar(B_SEG + n), 0);
          if (RFENCE) fence_async_smem();
          if (elect()) bulk_to_peer(sb + (n < 2 ? SM_Y0 : SM_SIG) + w * 8192 + 4096, sb + SM_YT + w * 4096, 4096, bar(B_YIN + (n >> 1)), rho ^ 1);
          if (w) {
            mbar_wait(bar(B_YIN + (n >> 1)), 0);
            if (lane == 0) asm volatile("mbarrier.arrive.shared::cluster.b64 _, [%0];" :: "r"(n < 2 ? peer_addr(bar(B_RDY1), rho ^ 1) : bar(B_Y_READY)) : "memory");
          }
        }
        __syncwarp();
        cluster_arrive();
        TSTAMP(lane == 0, 26);
      } else {
        mbar_wait(bar(B_OUT_FULL), 0);
        mbar_wait(bar(B_OUT_FULL + 1), 0);
        mbar_wait(bar(B_O_WRITTEN), 0);
        if (PD3) delay(PD3);
        unsigned ready = 0;
        int s = 2;
        uint32_t ph = 1;
#pragma unroll 1
        for (int ks = 2; ks < 16; ++ks) {
          const int c = chunk(ks);
          uint32_t fb = bar(B_OUT_FULL + s), dst = sb + ((A_SLOTS >> (4 * s)) & 15) * SLOT;
          uint8_t* src = g_xch[r * 8 + (c >> 1)] + (c & 1) * SLOT;
          keep(fb); keep(dst); keep(src);
          if (ks < 5 || ks == 9) {
            const unsigned need = ks < 4 ? 1u << c : 0x5555u;
            if (ks == 9) mbar_wait(bar(B_FLAGS1), 0);
            else if (~ready & need) ready = wait_chunks(need);
          }
          constexpr uint64_t kFirst = (B_O_WRITTEN + 1) | B_OT_FREE << 8 | B_SLOT_FREE << 16 | (B_OT_FREE + 1) << 24 | (uint64_t)B_CONV_DONE << 32;
          mbar_wait(bar(ks < 7 ? (int)(kFirst >> (8 * ks - 16)) & 255 : B_OUT_EMPTY + s), ks < 7 ? ks == 4 : ph);
          if (elect()) bulk_load(dst, src, SLOT, fb);
          TSTAMP(ks == 2 && lane == 0, 18); LOOPSTAMP(2, lane == 0, 11 + ks);
          if (++s == 5) { s = 0; ph ^= 1; }
        }
      }
    }
    if (LATE || warp == 9 || warp == 10) {
      const int yc = (lane & 1) + ((lane >> 2) & 2) + (lane & 2) * 2, ysrc = (lane >> 2) & 1;
      const uint32_t ya = sb + (yc & 4 ? SM_SIG : SM_Y0) + (yc & 1) * 8192 + (yc & 2) * 1024 + (ysrc ^ rho) * 4096 +
                          (lane >> 4) * 128 + ((yc ^ (2 * ysrc)) << 4);
      uint32_t s0, s1;
      mbar_wait(bar(B_Y_READY), 0);
      asm volatile("ld.shared.v2.b32 {%0,%1}, [%2];" : "=r"(s0), "=r"(s1) : "r"(sb + SM_SC + (lane & 3) * 8) : "memory");
#pragma unroll 1
      for (int n = warp == 8 ? 6 : warp == 11 ? 7 : warp - 9; n < 8; n += LATE && n >= 4 ? 8 : 2) {
        __nv_bfloat16* op = P.out_ptr + (rho * 1024 + n * 128 + (lane >> 2)) * 2048 + 1024 + cl * 16 + (lane & 3) * 4;
        const uint32_t qa = sb + SM_Q + (n & 3) * 4096 + lane * 8;
        if (n >= 4 && !(DBG & 1)) mbar_wait(bar(B_Q_FULL + (n & 3)), 1);
#pragma unroll 1
        for (int u0 = 0; u0 < (DBG & 2 ? 0 : 8); u0 += 2) {
          const uint32_t t0 = clock32();
          uint32_t y[2][4], q[2][4];
#pragma unroll
          for (int u = 0; u < 2; u++) {
            ldsm4_t(y[u], (ya ^ ((u0 + u) << 4)) + n * 256);
#pragma unroll
            for (int m = 0; m < 2; m++)
              asm volatile("ld.shared.v2.b32 {%0,%1}, [%2];" : "=r"(q[u][2 * m]), "=r"(q[u][2 * m + 1]) : "r"(qa + (u0 + u) * 512 + m * 256) : "memory");
          }
#pragma unroll
          for (int u = 0; u < 2; u++)
#pragma unroll
            for (int m = 0; m < 2; m++)
              asm volatile("st.global.v2.b32 [%0], {%1,%2};" :: "l"(op + (u0 * 16 + u * 16 + m * 8) * 2048),
                           "r"(bmul2(q[u][2 * m], bmul2(y[u][2 * m], s0))), "r"(bmul2(q[u][2 * m + 1], bmul2(y[u][2 * m + 1], s1))) : "memory");
          if (NSL & 2) __nanosleep(PPACE); else while (clock32() - t0 < (n < 4 ? PPACE : n < 6 ? PPACE2 : PPACE3)) { }
        }
        __syncwarp();
        if (n < 4 && !(DBG & 1) && elect()) load_q(n + 4);
      }
      TSTAMP(tid == 320, 24); TSTAMP(tid == 352, 27);
    }
    __syncwarp();
    cluster_wait();
  }
}

typedef CUresult (*EncodeFn)(CUtensorMap*, CUtensorMapDataType, cuuint32_t, void*, const cuuint64_t*, const cuuint64_t*,
                             const cuuint32_t*, const cuuint32_t*, CUtensorMapInterleave, CUtensorMapSwizzle,
                             CUtensorMapL2promotion, CUtensorMapFloatOOBfill);

void encode(EncodeFn fn, CUtensorMap* m, const void* p, int rank, const cuuint64_t* dims, const cuuint64_t* strides,
            const cuuint32_t* box, CUtensorMapSwizzle sw) {
  const cuuint32_t es[3] = {1, 1, 1};
  fn(m, CU_TENSOR_MAP_DATA_TYPE_BFLOAT16, rank, const_cast<void*>(p), dims, strides, box, es, CU_TENSOR_MAP_INTERLEAVE_NONE, sw,
     CU_TENSOR_MAP_L2_PROMOTION_NONE, CU_TENSOR_MAP_FLOAT_OOB_FILL_NONE);
}
void encode2d(EncodeFn fn, CUtensorMap* m, const void* p, uint64_t cols, uint64_t rows, uint32_t bc, uint32_t br, CUtensorMapSwizzle sw) {
  const cuuint64_t dims[2] = {cols, rows}, strides[1] = {cols * 2};
  const cuuint32_t box[2] = {bc, br};
  encode(fn, m, p, 2, dims, strides, box, sw);
}
void encode3d(EncodeFn fn, CUtensorMap* m, const void* p, uint32_t nblk) {
  const cuuint64_t dims[3] = {1024, 128, 16}, strides[2] = {2048 * 16, 2048};
  const cuuint32_t box[3] = {16, nblk, 16};
  encode(fn, m, p, 3, dims, strides, box, CU_TENSOR_MAP_SWIZZLE_32B);
}

}

extern "C" void kernel_launch(void* const* d_in, const int* in_sizes, int n_in, void* d_out, int out_size) {
  static EncodeFn fn = nullptr;
  if (!fn) {
    cudaDriverEntryPointQueryResult qr;
    cudaGetDriverEntryPoint("cuTensorMapEncodeTiled", (void**)&fn, cudaEnableDefault, &qr);
    cudaFuncSetAttribute(fused_kernel, cudaFuncAttributeMaxDynamicSharedMemorySize, SM_TOTAL);
  }
  Params P;
  encode2d(fn, &P.x, d_in[0], 1024, 2048, 32, 128, CU_TENSOR_MAP_SWIZZLE_64B);
  {
    const cuuint64_t dims[3] = {64, 1024, 48}, strides[2] = {6144, 128};
    const cuuint32_t box[3] = {64, 32, 2};
    encode(fn, &P.w, d_in[1], 3, dims, strides, box, CU_TENSOR_MAP_SWIZZLE_128B);
  }
  encode2d(fn, &P.wk, d_in[1], 3072, 1024, 64, 32, CU_TENSOR_MAP_SWIZZLE_128B);
  encode2d(fn, &P.wo, d_in[2], 1024, 1024, 64, 64, CU_TENSOR_MAP_SWIZZLE_128B);
  encode2d(fn, &P.outa, d_out, 2048, 2048, 64, 16, CU_TENSOR_MAP_SWIZZLE_128B);
  encode3d(fn, &P.k, d_in[4], 9);
  encode3d(fn, &P.v, d_in[5], 8);
  encode2d(fn, &P.q, d_in[3], 1024, 2048, 16, 128, CU_TENSOR_MAP_SWIZZLE_NONE);
  P.shift_k = (const __nv_bfloat16*)d_in[6];
  P.ssm_k = (const __nv_bfloat16*)d_in[7];
  P.ssm_d = (const __nv_bfloat16*)d_in[8];
  P.zero = 0;
  P.q_ptr = (const __nv_bfloat16*)d_in[3];
  P.out_ptr = (__nv_bfloat16*)d_out;
  P.wo_ptr = (const __nv_bfloat16*)d_in[2];
  fused_kernel<<<kCtas, kThreads, SM_TOTAL>>>(P);
}
```

```cpp
#include <cuda.h>
#include <cuda_runtime.h>
#include <cuda_bf16.h>
#include <stdint.h>

#define DEVI __device__ __forceinline__

namespace {

DEVI void mma_nt(float* d, uint64_t da, uint64_t db) {
  asm volatile("wgmma.mma_async.sync.aligned.m64n128k16.f32.bf16.bf16 {%0, %1, %2, %3, %4, %5, %6, %7, %8, %9, %10, %11, %12, %13, %14, %15, %16, %17, %18, %19, %20, %21, %22, %23, %24, %25, %26, %27, %28, %29, %30, %31, %32, %33, %34, %35, %36, %37, %38, %39, %40, %41, %42, %43, %44, %45, %46, %47, %48, %49, %50, %51, %52, %53, %54, %55, %56, %57, %58, %59, %60, %61, %62, %63}, %64, %65, 1, 1, 1, 0, 1;\n"
    : "+f"(d[0]), "+f"(d[1]), "+f"(d[2]), "+f"(d[3]), "+f"(d[4]), "+f"(d[5]), "+f"(d[6]), "+f"(d[7]), "+f"(d[8]), "+f"(d[9]), "+f"(d[10]), "+f"(d[11]), "+f"(d[12]), "+f"(d[13]), "+f"(d[14]), "+f"(d[15]), "+f"(d[16]), "+f"(d[17]), "+f"(d[18]), "+f"(d[19]), "+f"(d[20]), "+f"(d[21]), "+f"(d[22]), "+f"(d[23]), "+f"(d[24]), "+f"(d[25]), "+f"(d[26]), "+f"(d[27]), "+f"(d[28]), "+f"(d[29]), "+f"(d[30]), "+f"(d[31]), "+f"(d[32]), "+f"(d[33]), "+f"(d[34]), "+f"(d[35]), "+f"(d[36]), "+f"(d[37]), "+f"(d[38]), "+f"(d[39]), "+f"(d[40]), "+f"(d[41]), "+f"(d[42]), "+f"(d[43]), "+f"(d[44]), "+f"(d[45]), "+f"(d[46]), "+f"(d[47]), "+f"(d[48]), "+f"(d[49]), "+f"(d[50]), "+f"(d[51]), "+f"(d[52]), "+f"(d[53]), "+f"(d[54]), "+f"(d[55]), "+f"(d[56]), "+f"(d[57]), "+f"(d[58]), "+f"(d[59]), "+f"(d[60]), "+f"(d[61]), "+f"(d[62]), "+f"(d[63])
    : "l"(da), "l"(db));
}
DEVI void mma_tn(float* d, uint64_t da, uint64_t db) {
  asm volatile("wgmma.mma_async.sync.aligned.m64n128k16.f32.bf16.bf16 {%0, %1, %2, %3, %4, %5, %6, %7, %8, %9, %10, %11, %12, %13, %14, %15, %16, %17, %18, %19, %20, %21, %22, %23, %24, %25, %26, %27, %28, %29, %30, %31, %32, %33, %34, %35, %36, %37, %38, %39, %40, %41, %42, %43, %44, %45, %46, %47, %48, %49, %50, %51, %52, %53, %54, %55, %56, %57, %58, %59, %60, %61, %62, %63}, %64, %65, 1, 1, 1, 1, 0;\n"
    : "+f"(d[0]), "+f"(d[1]), "+f"(d[2]), "+f"(d[3]), "+f"(d[4]), "+f"(d[5]), "+f"(d[6]), "+f"(d[7]), "+f"(d[8]), "+f"(d[9]), "+f"(d[10]), "+f"(d[11]), "+f"(d[12]), "+f"(d[13]), "+f"(d[14]), "+f"(d[15]), "+f"(d[16]), "+f"(d[17]), "+f"(d[18]), "+f"(d[19]), "+f"(d[20]), "+f"(d[21]), "+f"(d[22]), "+f"(d[23]), "+f"(d[24]), "+f"(d[25]), "+f"(d[26]), "+f"(d[27]), "+f"(d[28]), "+f"(d[29]), "+f"(d[30]), "+f"(d[31]), "+f"(d[32]), "+f"(d[33]), "+f"(d[34]), "+f"(d[35]), "+f"(d[36]), "+f"(d[37]), "+f"(d[38]), "+f"(d[39]), "+f"(d[40]), "+f"(d[41]), "+f"(d[42]), "+f"(d[43]), "+f"(d[44]), "+f"(d[45]), "+f"(d[46]), "+f"(d[47]), "+f"(d[48]), "+f"(d[49]), "+f"(d[50]), "+f"(d[51]), "+f"(d[52]), "+f"(d[53]), "+f"(d[54]), "+f"(d[55]), "+f"(d[56]), "+f"(d[57]), "+f"(d[58]), "+f"(d[59]), "+f"(d[60]), "+f"(d[61]), "+f"(d[62]), "+f"(d[63])
    : "l"(da), "l"(db));
}
DEVI void mma_own_init(float* d, uint32_t a0, uint32_t a1, uint32_t a2, uint32_t a3, uint64_t db) {
  asm volatile("wgmma.mma_async.sync.aligned.m64n128k16.f32.bf16.bf16 {%0, %1, %2, %3, %4, %5, %6, %7, %8, %9, %10, %11, %12, %13, %14, %15, %16, %17, %18, %19, %20, %21, %22, %23, %24, %25, %26, %27, %28, %29, %30, %31, %32, %33, %34, %35, %36, %37, %38, %39, %40, %41, %42, %43, %44, %45, %46, %47, %48, %49, %50, %51, %52, %53, %54, %55, %56, %57, %58, %59, %60, %61, %62, %63}, {%64,%65,%66,%67}, %68, 0, 1, 1, 1;\n"
    : "=f"(d[0]), "=f"(d[1]), "=f"(d[2]), "=f"(d[3]), "=f"(d[4]), "=f"(d[5]), "=f"(d[6]), "=f"(d[7]), "=f"(d[8]), "=f"(d[9]), "=f"(d[10]), "=f"(d[11]), "=f"(d[12]), "=f"(d[13]), "=f"(d[14]), "=f"(d[15]), "=f"(d[16]), "=f"(d[17]), "=f"(d[18]), "=f"(d[19]), "=f"(d[20]), "=f"(d[21]), "=f"(d[22]), "=f"(d[23]), "=f"(d[24]), "=f"(d[25]), "=f"(d[26]), "=f"(d[27]), "=f"(d[28]), "=f"(d[29]), "=f"(d[30]), "=f"(d[31]), "=f"(d[32]), "=f"(d[33]), "=f"(d[34]), "=f"(d[35]), "=f"(d[36]), "=f"(d[37]), "=f"(d[38]), "=f"(d[39]), "=f"(d[40]), "=f"(d[41]), "=f"(d[42]), "=f"(d[43]), "=f"(d[44]), "=f"(d[45]), "=f"(d[46]), "=f"(d[47]), "=f"(d[48]), "=f"(d[49]), "=f"(d[50]), "=f"(d[51]), "=f"(d[52]), "=f"(d[53]), "=f"(d[54]), "=f"(d[55]), "=f"(d[56]), "=f"(d[57]), "=f"(d[58]), "=f"(d[59]), "=f"(d[60]), "=f"(d[61]), "=f"(d[62]), "=f"(d[63])
    : "r"(a0), "r"(a1), "r"(a2), "r"(a3), "l"(db));
}
DEVI void mma_own_acc(float* d, uint32_t a0, uint32_t a1, uint32_t a2, uint32_t a3, uint64_t db) {
  asm volatile("wgmma.mma_async.sync.aligned.m64n128k16.f32.bf16.bf16 {%0, %1, %2, %3, %4, %5, %6, %7, %8, %9, %10, %11, %12, %13, %14, %15, %16, %17, %18, %19, %20, %21, %22, %23, %24, %25, %26, %27, %28, %29, %30, %31, %32, %33, %34, %35, %36, %37, %38, %39, %40, %41, %42, %43, %44, %45, %46, %47, %48, %49, %50, %51, %52, %53, %54, %55, %56, %57, %58, %59, %60, %61, %62, %63}, {%64,%65,%66,%67}, %68, 1, 1, 1, 1;\n"
    : "+f"(d[0]), "+f"(d[1]), "+f"(d[2]), "+f"(d[3]), "+f"(d[4]), "+f"(d[5]), "+f"(d[6]), "+f"(d[7]), "+f"(d[8]), "+f"(d[9]), "+f"(d[10]), "+f"(d[11]), "+f"(d[12]), "+f"(d[13]), "+f"(d[14]), "+f"(d[15]), "+f"(d[16]), "+f"(d[17]), "+f"(d[18]), "+f"(d[19]), "+f"(d[20]), "+f"(d[21]), "+f"(d[22]), "+f"(d[23]), "+f"(d[24]), "+f"(d[25]), "+f"(d[26]), "+f"(d[27]), "+f"(d[28]), "+f"(d[29]), "+f"(d[30]), "+f"(d[31]), "+f"(d[32]), "+f"(d[33]), "+f"(d[34]), "+f"(d[35]), "+f"(d[36]), "+f"(d[37]), "+f"(d[38]), "+f"(d[39]), "+f"(d[40]), "+f"(d[41]), "+f"(d[42]), "+f"(d[43]), "+f"(d[44]), "+f"(d[45]), "+f"(d[46]), "+f"(d[47]), "+f"(d[48]), "+f"(d[49]), "+f"(d[50]), "+f"(d[51]), "+f"(d[52]), "+f"(d[53]), "+f"(d[54]), "+f"(d[55]), "+f"(d[56]), "+f"(d[57]), "+f"(d[58]), "+f"(d[59]), "+f"(d[60]), "+f"(d[61]), "+f"(d[62]), "+f"(d[63])
    : "r"(a0), "r"(a1), "r"(a2), "r"(a3), "l"(db));
}
DEVI void mma_nt256(float* d, uint64_t da, uint64_t db) {
  asm volatile("wgmma.mma_async.sync.aligned.m64n256k16.f32.bf16.bf16 {%0, %1, %2, %3, %4, %5, %6, %7, %8, %9, %10, %11, %12, %13, %14, %15, %16, %17, %18, %19, %20, %21, %22, %23, %24, %25, %26, %27, %28, %29, %30, %31, %32, %33, %34, %35, %36, %37, %38, %39, %40, %41, %42, %43, %44, %45, %46, %47, %48, %49, %50, %51, %52, %53, %54, %55, %56, %57, %58, %59, %60, %61, %62, %63, %64, %65, %66, %67, %68, %69, %70, %71, %72, %73, %74, %75, %76, %77, %78, %79, %80, %81, %82, %83, %84, %85, %86, %87, %88, %89, %90, %91, %92, %93, %94, %95, %96, %97, %98, %99, %100, %101, %102, %103, %104, %105, %106, %107, %108, %109, %110, %111, %112, %113, %114, %115, %116, %117, %118, %119, %120, %121, %122, %123, %124, %125, %126, %127}, %128, %129, 1, 1, 1, 0, 1;\n"
    : "+f"(d[0]), "+f"(d[1]), "+f"(d[2]), "+f"(d[3]), "+f"(d[4]), "+f"(d[5]), "+f"(d[6]), "+f"(d[7]), "+f"(d[8]), "+f"(d[9]), "+f"(d[10]), "+f"(d[11]), "+f"(d[12]), "+f"(d[13]), "+f"(d[14]), "+f"(d[15]), "+f"(d[16]), "+f"(d[17]), "+f"(d[18]), "+f"(d[19]), "+f"(d[20]), "+f"(d[21]), "+f"(d[22]), "+f"(d[23]), "+f"(d[24]), "+f"(d[25]), "+f"(d[26]), "+f"(d[27]), "+f"(d[28]), "+f"(d[29]), "+f"(d[30]), "+f"(d[31]), "+f"(d[32]), "+f"(d[33]), "+f"(d[34]), "+f"(d[35]), "+f"(d[36]), "+f"(d[37]), "+f"(d[38]), "+f"(d[39]), "+f"(d[40]), "+f"(d[41]), "+f"(d[42]), "+f"(d[43]), "+f"(d[44]), "+f"(d[45]), "+f"(d[46]), "+f"(d[47]), "+f"(d[48]), "+f"(d[49]), "+f"(d[50]), "+f"(d[51]), "+f"(d[52]), "+f"(d[53]), "+f"(d[54]), "+f"(d[55]), "+f"(d[56]), "+f"(d[57]), "+f"(d[58]), "+f"(d[59]), "+f"(d[60]), "+f"(d[61]), "+f"(d[62]), "+f"(d[63]), "+f"(d[64]), "+f"(d[65]), "+f"(d[66]), "+f"(d[67]), "+f"(d[68]), "+f"(d[69]), "+f"(d[70]), "+f"(d[71]), "+f"(d[72]), "+f"(d[73]), "+f"(d[74]), "+f"(d[75]), "+f"(d[76]), "+f"(d[77]), "+f"(d[78]), "+f"(d[79]), "+f"(d[80]), "+f"(d[81]), "+f"(d[82]), "+f"(d[83]), "+f"(d[84]), "+f"(d[85]), "+f"(d[86]), "+f"(d[87]), "+f"(d[88]), "+f"(d[89]), "+f"(d[90]), "+f"(d[91]), "+f"(d[92]), "+f"(d[93]), "+f"(d[94]), "+f"(d[95]), "+f"(d[96]), "+f"(d[97]), "+f"(d[98]), "+f"(d[99]), "+f"(d[100]), "+f"(d[101]), "+f"(d[102]), "+f"(d[103]), "+f"(d[104]), "+f"(d[105]), "+f"(d[106]), "+f"(d[107]), "+f"(d[108]), "+f"(d[109]), "+f"(d[110]), "+f"(d[111]), "+f"(d[112]), "+f"(d[113]), "+f"(d[114]), "+f"(d[115]), "+f"(d[116]), "+f"(d[117]), "+f"(d[118]), "+f"(d[119]), "+f"(d[120]), "+f"(d[121]), "+f"(d[122]), "+f"(d[123]), "+f"(d[124]), "+f"(d[125]), "+f"(d[126]), "+f"(d[127])
    : "l"(da), "l"(db));
}
DEVI void mma_kv_init(float* d, uint32_t a0, uint32_t a1, uint32_t a2, uint32_t a3, uint64_t db) {
  asm volatile("wgmma.mma_async.sync.aligned.m64n72k16.f32.bf16.bf16 {%0, %1, %2, %3, %4, %5, %6, %7, %8, %9, %10, %11, %12, %13, %14, %15, %16, %17, %18, %19, %20, %21, %22, %23, %24, %25, %26, %27, %28, %29, %30, %31, %32, %33, %34, %35}, {%36,%37,%38,%39}, %40, 0, 1, 1, 1;\n"
    : "=f"(d[0]), "=f"(d[1]), "=f"(d[2]), "=f"(d[3]), "=f"(d[4]), "=f"(d[5]), "=f"(d[6]), "=f"(d[7]), "=f"(d[8]), "=f"(d[9]), "=f"(d[10]), "=f"(d[11]), "=f"(d[12]), "=f"(d[13]), "=f"(d[14]), "=f"(d[15]), "=f"(d[16]), "=f"(d[17]), "=f"(d[18]), "=f"(d[19]), "=f"(d[20]), "=f"(d[21]), "=f"(d[22]), "=f"(d[23]), "=f"(d[24]), "=f"(d[25]), "=f"(d[26]), "=f"(d[27]), "=f"(d[28]), "=f"(d[29]), "=f"(d[30]), "=f"(d[31]), "=f"(d[32]), "=f"(d[33]), "=f"(d[34]), "=f"(d[35])
    : "r"(a0), "r"(a1), "r"(a2), "r"(a3), "l"(db));
}
DEVI void mma_kv_acc(float* d, uint32_t a0, uint32_t a1, uint32_t a2, uint32_t a3, uint64_t db) {
  asm volatile("wgmma.mma_async.sync.aligned.m64n72k16.f32.bf16.bf16 {%0, %1, %2, %3, %4, %5, %6, %7, %8, %9, %10, %11, %12, %13, %14, %15, %16, %17, %18, %19, %20, %21, %22, %23, %24, %25, %26, %27, %28, %29, %30, %31, %32, %33, %34, %35}, {%36,%37,%38,%39}, %40, 1, 1, 1, 1;\n"
    : "+f"(d[0]), "+f"(d[1]), "+f"(d[2]), "+f"(d[3]), "+f"(d[4]), "+f"(d[5]), "+f"(d[6]), "+f"(d[7]), "+f"(d[8]), "+f"(d[9]), "+f"(d[10]), "+f"(d[11]), "+f"(d[12]), "+f"(d[13]), "+f"(d[14]), "+f"(d[15]), "+f"(d[16]), "+f"(d[17]), "+f"(d[18]), "+f"(d[19]), "+f"(d[20]), "+f"(d[21]), "+f"(d[22]), "+f"(d[23]), "+f"(d[24]), "+f"(d[25]), "+f"(d[26]), "+f"(d[27]), "+f"(d[28]), "+f"(d[29]), "+f"(d[30]), "+f"(d[31]), "+f"(d[32]), "+f"(d[33]), "+f"(d[34]), "+f"(d[35])
    : "r"(a0), "r"(a1), "r"(a2), "r"(a3), "l"(db));
}
DEVI void mma_o_init(float* d, uint32_t a0, uint32_t a1, uint32_t a2, uint32_t a3, uint64_t db) {
  asm volatile("wgmma.mma_async.sync.aligned.m64n40k16.f32.bf16.bf16 {%0, %1, %2, %3, %4, %5, %6, %7, %8, %9, %10, %11, %12, %13, %14, %15, %16, %17, %18, %19}, {%20,%21,%22,%23}, %24, 0, 1, 1, 1;\n"
    : "=f"(d[0]), "=f"(d[1]), "=f"(d[2]), "=f"(d[3]), "=f"(d[4]), "=f"(d[5]), "=f"(d[6]), "=f"(d[7]), "=f"(d[8]), "=f"(d[9]), "=f"(d[10]), "=f"(d[11]), "=f"(d[12]), "=f"(d[13]), "=f"(d[14]), "=f"(d[15]), "=f"(d[16]), "=f"(d[17]), "=f"(d[18]), "=f"(d[19])
    : "r"(a0), "r"(a1), "r"(a2), "r"(a3), "l"(db));
}
DEVI void mma_o_acc(float* d, uint32_t a0, uint32_t a1, uint32_t a2, uint32_t a3, uint64_t db) {
  asm volatile("wgmma.mma_async.sync.aligned.m64n40k16.f32.bf16.bf16 {%0, %1, %2, %3, %4, %5, %6, %7, %8, %9, %10, %11, %12, %13, %14, %15, %16, %17, %18, %19}, {%20,%21,%22,%23}, %24, 1, 1, 1, 1;\n"
    : "+f"(d[0]), "+f"(d[1]), "+f"(d[2]), "+f"(d[3]), "+f"(d[4]), "+f"(d[5]), "+f"(d[6]), "+f"(d[7]), "+f"(d[8]), "+f"(d[9]), "+f"(d[10]), "+f"(d[11]), "+f"(d[12]), "+f"(d[13]), "+f"(d[14]), "+f"(d[15]), "+f"(d[16]), "+f"(d[17]), "+f"(d[18]), "+f"(d[19])
    : "r"(a0), "r"(a1), "r"(a2), "r"(a3), "l"(db));
}
DEVI void fft1_init(uint32_t* d, uint32_t a0, uint32_t a1, uint32_t a2, uint32_t a3, uint64_t db) {
  asm volatile("wgmma.mma_async.sync.aligned.m64n128k16.f16.f16.f16 {%0, %1, %2, %3, %4, %5, %6, %7, %8, %9, %10, %11, %12, %13, %14, %15, %16, %17, %18, %19, %20, %21, %22, %23, %24, %25, %26, %27, %28, %29, %30, %31}, {%32,%33,%34,%35}, %36, 0, 1, 1, 1;\n"
    : "=r"(d[0]), "=r"(d[1]), "=r"(d[2]), "=r"(d[3]), "=r"(d[4]), "=r"(d[5]), "=r"(d[6]), "=r"(d[7]), "=r"(d[8]), "=r"(d[9]), "=r"(d[10]), "=r"(d[11]), "=r"(d[12]), "=r"(d[13]), "=r"(d[14]), "=r"(d[15]), "=r"(d[16]), "=r"(d[17]), "=r"(d[18]), "=r"(d[19]), "=r"(d[20]), "=r"(d[21]), "=r"(d[22]), "=r"(d[23]), "=r"(d[24]), "=r"(d[25]), "=r"(d[26]), "=r"(d[27]), "=r"(d[28]), "=r"(d[29]), "=r"(d[30]), "=r"(d[31])
    : "r"(a0), "r"(a1), "r"(a2), "r"(a3), "l"(db));
}
DEVI void fft1_acc(uint32_t* d, uint32_t a0, uint32_t a1, uint32_t a2, uint32_t a3, uint64_t db) {
  asm volatile("wgmma.mma_async.sync.aligned.m64n128k16.f16.f16.f16 {%0, %1, %2, %3, %4, %5, %6, %7, %8, %9, %10, %11, %12, %13, %14, %15, %16, %17, %18, %19, %20, %21, %22, %23, %24, %25, %26, %27, %28, %29, %30, %31}, {%32,%33,%34,%35}, %36, 1, 1, 1, 1;\n"
    : "+r"(d[0]), "+r"(d[1]), "+r"(d[2]), "+r"(d[3]), "+r"(d[4]), "+r"(d[5]), "+r"(d[6]), "+r"(d[7]), "+r"(d[8]), "+r"(d[9]), "+r"(d[10]), "+r"(d[11]), "+r"(d[12]), "+r"(d[13]), "+r"(d[14]), "+r"(d[15]), "+r"(d[16]), "+r"(d[17]), "+r"(d[18]), "+r"(d[19]), "+r"(d[20]), "+r"(d[21]), "+r"(d[22]), "+r"(d[23]), "+r"(d[24]), "+r"(d[25]), "+r"(d[26]), "+r"(d[27]), "+r"(d[28]), "+r"(d[29]), "+r"(d[30]), "+r"(d[31])
    : "r"(a0), "r"(a1), "r"(a2), "r"(a3), "l"(db));
}
DEVI void fft2_init(uint32_t* d, uint32_t a0, uint32_t a1, uint32_t a2, uint32_t a3, uint64_t db) {
  asm volatile("wgmma.mma_async.sync.aligned.m64n32k16.f16.f16.f16 {%0, %1, %2, %3, %4, %5, %6, %7}, {%8,%9,%10,%11}, %12, 0, 1, 1, 0;\n"
    : "=r"(d[0]), "=r"(d[1]), "=r"(d[2]), "=r"(d[3]), "=r"(d[4]), "=r"(d[5]), "=r"(d[6]), "=r"(d[7])
    : "r"(a0), "r"(a1), "r"(a2), "r"(a3), "l"(db));
}
DEVI void fft2_acc(uint32_t* d, uint32_t a0, uint32_t a1, uint32_t a2, uint32_t a3, uint64_t db) {
  asm volatile("wgmma.mma_async.sync.aligned.m64n32k16.f16.f16.f16 {%0, %1, %2, %3, %4, %5, %6, %7}, {%8,%9,%10,%11}, %12, 1, 1, 1, 0;\n"
    : "+r"(d[0]), "+r"(d[1]), "+r"(d[2]), "+r"(d[3]), "+r"(d[4]), "+r"(d[5]), "+r"(d[6]), "+r"(d[7])
    : "r"(a0), "r"(a1), "r"(a2), "r"(a3), "l"(db));
}
DEVI void fft3_init(float* d, uint32_t a0, uint32_t a1, uint32_t a2, uint32_t a3, uint64_t db) {
  asm volatile("wgmma.mma_async.sync.aligned.m64n32k16.f32.f16.f16 {%0, %1, %2, %3, %4, %5, %6, %7, %8, %9, %10, %11, %12, %13, %14, %15}, {%16,%17,%18,%19}, %20, 0, 1, 1, 0;\n"
    : "=f"(d[0]), "=f"(d[1]), "=f"(d[2]), "=f"(d[3]), "=f"(d[4]), "=f"(d[5]), "=f"(d[6]), "=f"(d[7]), "=f"(d[8]), "=f"(d[9]), "=f"(d[10]), "=f"(d[11]), "=f"(d[12]), "=f"(d[13]), "=f"(d[14]), "=f"(d[15])
    : "r"(a0), "r"(a1), "r"(a2), "r"(a3), "l"(db));
}
DEVI void fft3_acc(float* d, uint32_t a0, uint32_t a1, uint32_t a2, uint32_t a3, uint64_t db) {
  asm volatile("wgmma.mma_async.sync.aligned.m64n32k16.f32.f16.f16 {%0, %1, %2, %3, %4, %5, %6, %7, %8, %9, %10, %11, %12, %13, %14, %15}, {%16,%17,%18,%19}, %20, 1, 1, 1, 0;\n"
    : "+f"(d[0]), "+f"(d[1]), "+f"(d[2]), "+f"(d[3]), "+f"(d[4]), "+f"(d[5]), "+f"(d[6]), "+f"(d[7]), "+f"(d[8]), "+f"(d[9]), "+f"(d[10]), "+f"(d[11]), "+f"(d[12]), "+f"(d[13]), "+f"(d[14]), "+f"(d[15])
    : "r"(a0), "r"(a1), "r"(a2), "r"(a3), "l"(db));
}

__device__ __align__(128) const uint32_t g_tables[2560] = {
0xa11ba1e4,0xa51ba5e4,0x18b61248,0x1cb61648,0x9f12a052,0xa311a452,0x1d7f1bdb,0x217f1fdb,0x9bdb9d7f,0x9fdba17f,0x20521f12,0x24522311,
0x924898b6,0x96489cb6,0x21e4211b,0x25e4251b,0xaa63ab5f,0xae5faf59,0x21e41bdb,0x25e41fdb,0xa86ba967,0xac6aad65,0x26e024e9,0x2ade28e8,
0xa4e9a6e0,0xa8e8aade,0x2967286b,0x2d652c6a,0x9bdba1e4,0x9fdba5e4,0x2b5f2a63,0x2f592e5f,0xadc2aea7,0xb1b6b294,0x254d1f12,0x294d2311,
0xabf6acde,0xafefb0d7,0x2a31286b,0x2e2d2c6a,0xa86baa31,0xac6aae2d,0x2cde2bf6,0x30d72fef,0x9f12a54d,0xa311a94d,0x2ea72dc2,0x329431b6,
0xb02cb0d2,0xb41ab4b7,0x27a9211b,0x2ba7251b,0xadc2af0c,0xb1b6b2f7,0x2c792a63,0x30742e5f,0xaa63ac79,0xae5fb074,0x2f0c2dc2,0x32f731b6,
0xa11ba7a9,0xa51baba7,0x30d2302c,0x34b7341a,0xb17ab257,0xb552b61a,0x290222ad,0x2d0026ad,0xaf8cb09f,0xb371b487,0x2ddc2c2e,0x31cf3029,
0xac2eaddc,0xb029b1cf,0x309f2f8c,0x34873371,0xa2ada902,0xa6adad00,0x3257317a,0x361a3552,0xb2cdb3e3,0xb682b76f,0x2a312420,0x2e2d281f,
0xb0acb1bb,0xb493b58d,0x2f3f2d2a,0x33283122,0xad2aaf3f,0xb122b328,0x31bb30ac,0x358d3493,0xa420aa31,0xa81fae2d,0x33e332cd,0x376f3682,
0xb413b4bc,0xb7a6b85a,0x2b5f24e9,0x2f5928e8,0xb194b2da,0xb56ab68d,0x30522e28,0x343e3219,0xae28b052,0xb219b43e,0x32da3194,0x368d356a,
0xa4e9ab5f,0xa8e8af59,0x34bc3413,0x385a37a6,0xb4c3b58c,0xb85fb8f3,0x2c4725b2,0x304229b1,0xb27eb3fd,0xb63cb785,0x31062f26,0x34e7330f,
0xaf26b106,0xb30fb4e7,0x33fd327e,0x3785363c,0xa5b2ac47,0xa9b1b042,0x358c34c3,0x38f3385f,0xb577b662,0xb8e5b982,0x2cde267b,0x30d72a7a,
0xb36bb493,0xb70ab83a,0x31bb3012,0x358d3402,0xb012b1bb,0xb402b58d,0x3493336b,0x383a370a,0xa67bacde,0xaa7ab0d7,0x36623577,0x398238e5,
0xb630b741,0xb962ba04,0x2d762744,0x316c2b43,0xb42eb52a,0xb7d2b8ad,0x32713092,0x3631347b,0xb092b271,0xb47bb631,0x352a342e,0x38ad37d2,
0xa744ad76,0xab43b16c,0x37413630,0x3a043962,0xb6eeb815,0xb9d6ba7a,0x2e0e2807,0x32012c06,0xb4a7b5c4,0xb84ab91b,0x33293113,0x36d234f3,
0xb113b329,0xb4f3b6d2,0x35c434a7,0x391b384a,0xa807ae0e,0xac06b201,0x381536ee,0x3a7a39d6,0xb7b4b88e,0xba41bae1,0x2ea7286b,0x32942c6a,
0xb523b662,0xb8a8b982,0x33e33194,0x376f356a,0xb194b3e3,0xb56ab76f,0x36623523,0x398238a8,0xa86baea7,0xac6ab294,0x388e37b4,0x3ae13a41,
0xb841b90f,0xbaa2bb3a,0x2f3f28d0,0x33282cce,0xb5a1b705,0xb902b9e3,0x344f3216,0x380535df,0xb216b44f,0xb5dfb805,0x370535a1,0x39e33902,
0xa8d0af3f,0xacceb328,0x390f3841,0x3b3a3aa2,0xb8acb997,0xbaf7bb83,0x2fd82935,0x33ba2d33,0xb621b7ac,0xb958ba3d,0x34ae3298,0x38503654,
0xb298b4ae,0xb654b850,0x37ac3621,0x3a3d3958,0xa935afd8,0xad33b3ba,0x399738ac,0x3b833af7,0xb91cba28,0xbb42bbbc,0x30392999,0x34262d97,
0xb6a4b82d,0xb9aaba90,0x350e331c,0x389936c6,0xb31cb50e,0xb6c6b899,0x382d36a4,0x3a9039aa,0xa999b039,0xad97b426,0x3a28391c,0x3bbc3b42,
0xb992bac3,0xbb81bbe3,0x308529fe,0x346f2dfb,0xb72ab886,0xb9f8badb,0x357033a0,0x38e03737,0xb3a0b570,0xb737b8e0,0x3886372a,0x3adb39f8,
0xa9feb085,0xadfbb46f,0x3ac33992,0x3be33b81,0x39cf3b16,0x3b9c3bf1,0xb0acaa31,0xb493ae2d,0x376f38b4,0x3a1d3afe,0xb5a1b3e3,0xb902b76f,
0x33e335a1,0x376f3902,0xb8b4b76f,0xbafeba1d,0x2a3130ac,0x2e2d3493,0xbb16b9cf,0xbbf1bb9c,0x39563a74,0x3b633bd2,0xb05fa9cc,0xb44badc9,
0x36e73859,0x39d23ab6,0xb53fb35e,0xb8bcb6ff,0x335e353f,0x36ff38bc,0xb859b6e7,0xbab6b9d2,0x29cc305f,0x2dc9344b,0xba74b956,0xbbd2bb63,
0x38e339de,0x3b1e3ba1,0xb012a967,0xb402ad65,0x36623801,0x39823a67,0xb4deb2da,0xb874b68d,0x32da34de,0x368d3874,0xb801b662,0xba67b982,
0x29673012,0x2d653402,0xb9deb8e3,0xbba1bb1e,0x38763952,0x3ace3b60,0xaf8ca902,0xb371ad00,0x35e13758,0x392e3a11,0xb47eb257,0xb82ab61a,
0x3257347e,0x361a382a,0xb758b5e1,0xba11b92e,0x29022f8c,0x2d003371,0xb952b876,0xbb60bace,0x380d38ce,0x3a733b10,0xaef3a89e,0xb2deac9c,
0x356236b3,0x38d639b3,0xb420b1d5,0xb7bdb5a5,0x31d53420,0x35a537bd,0xb6b3b562,0xb9b3b8d6,0x289e2ef3,0x2c9c32de,0xb8ceb80d,0xbb10ba73,
0x37503851,0x3a0d3ab0,0xae5aa839,0xb24bac38,0x34e53613,0x387a394f,0xb386b153,0xb721b52f,0x31533386,0x352f3721,0xb613b4e5,0xb94fb87a,
0x28392e5a,0x2c38324b,0xb851b750,0xbab0ba0d,0x368e37b4,0x399d3a41,0xadc2a7a9,0xb1b6aba7,0x346a3577,0x381a38e5,0xb2cdb0d2,0xb682b4b7,
0x30d232cd,0x34b73682,0xb577b46a,0xb8e5b81a,0x27a92dc2,0x2ba731b6,0xb7b4b68e,0xba41b99d,0x35d236d1,0x392439c5,0xad2aa6e0,0xb122aade,
0x33e334de,0x376f3874,0xb216b052,0xb5dfb43e,0x30523216,0x343e35df,0xb4deb3e3,0xb874b76f,0x26e02d2a,0x2ade3122,0xb6d1b5d2,0xb9c5b924,
0x351c35f6,0x38a3393c,0xac93a617,0xb08daa16,0x32f43448,0x36a437fe,0xb160afa5,0xb53ab389,0x2fa53160,0x3389353a,0xb448b2f4,0xb7feb6a4,
0x26172c93,0x2a16308d,0xb5f6b51c,0xb93cb8a3,0x346a3523,0x381a38a8,0xabf6a54d,0xafefa94d,0x3209336b,0x35d4370a,0xb0acaea7,0xb493b294,
0x2ea730ac,0x32943493,0xb36bb209,0xb70ab5d4,0x254d2bf6,0x294d2fef,0xb523b46a,0xb8a8b81a,0x33783456,0x3715380a,0xaac8a484,0xaec3a884,
0x3120324a,0x34ff360e,0xaff2ada9,0xb3d3b19e,0x2da92ff2,0x319e33d3,0xb24ab120,0xb60eb4ff,0x24842ac8,0x28842ec3,0xb456b378,0xb80ab715,
0x3223331c,0x35eb36c6,0xa999a376,0xad97a776,0x3039312d,0x3426350b,0xae8dacac,0xb27cb0a6,0x2cac2e8d,0x30a6327c,0xb12db039,0xb50bb426,
0x23762999,0x27762d97,0xb31cb223,0xb6c6b5eb,0x30d23194,0x34b7356a,0xa86ba1e4,0xac6aa5e4,0x2ea73012,0x32943402,0xad2aab5f,0xb122af59,
0x2b5f2d2a,0x2f593122,0xb012aea7,0xb402b294,0x21e4286b,0x25e42c6a,0xb194b0d2,0xb56ab4b7,0x2f0c3012,0x32f73402,0xa67ba052,0xaa7aa452,
0x2cde2df5,0x30d731e8,0xab91a967,0xaf8bad65,0x29672b91,0x2d652f8b,0xadf5acde,0xb1e8b0d7,0x2052267b,0x24522a7a,0xb012af0c,0xb402b2f7,
0x2c792d2a,0x30743122,0xa4209d7f,0xa81fa17f,0x2a312b91,0x2e2d2f8b,0xa8d0a6e0,0xacceaade,0x26e028d0,0x2ade2cce,0xab91aa31,0xaf8bae2d,
0x1d7f2420,0x217f281f,0xad2aac79,0xb122b074,0x27a9286b,0x2ba72c6a,0x9f1298b6,0xa3119cb6,0x254d267b,0x294d2a7a,0xa420a1e4,0xa81fa5e4,
0x21e42420,0x25e4281f,0xa67ba54d,0xaa7aa94d,0x18b61f12,0x1cb62311,0xa86ba7a9,0xac6aaba7,0x3f803f80,0x3f803f80,0x3f803f80,0x3f803f80,
0x3f803f80,0x3f803f80,0x3f803f80,0x3f803f80,0x3f803f80,0x3f803f80,0x3f803f80,0x3f803f80,0x3f803f80,0x3f803f80,0x3f803f80,0x3f803f80,
0x3f803f80,0x3f803f80,0x3f803f80,0x3f803f80,0x3f803f80,0x3f803f80,0x3f803f80,0x3f803f80,0x3f803f80,0x3f803f80,0x3f803f80,0x3f803f80,
0x3f803f80,0x3f803f80,0x3f803f80,0x3f803f80,0x3f803f80,0x3f803f80,0x3f803f80,0x3f803f80,0x3f803f80,0x3f803f80,0x3f803f80,0x3f803f80,
0x3f803f80,0x3f803f80,0x3f803f80,0x3f803f80,0x3f803f80,0x3f803f80,0x3f803f80,0x3f803f80,0x3f803f80,0x3f803f80,0x3f803f80,0x3f803f80,
0x3f803f80,0x3f803f80,0x3f803f80,0x3f803f80,0x3f803f80,0x3f803f80,0x3f803f80,0x3f803f80,0x3f803f80,0x3f803f80,0x3f803f80,0x3f803f80,
0x3f803f80,0x3f803f80,0x3f803f80,0x3f803f80,0x3f803f80,0x3f803f80,0x3f803f80,0x3f803f80,0x3f803f80,0x3f803f80,0x3f803f80,0x3f803f80,
0x3f803f80,0x3f803f80,0x3f803f80,0x3f803f80,0x3f803f80,0x3f803f80,0x3f803f80,0x3f803f80,0x3f803f80,0x3f803f80,0x3f803f80,0x3f803f80,
0x3f803f80,0x3f803f80,0x3f803f80,0x3f803f80,0x3f803f80,0x3f803f80,0x3f803f80,0x3f803f80,0x3f803f80,0x3f803f80,0x3f803f80,0x3f803f80,
0x3f803f80,0x3f803f80,0x3f803f80,0x3f803f80,0x3f803f80,0x3f803f80,0x3f803f80,0x3f803f80,0x3f803f80,0x3f803f80,0x3f803f80,0x3f803f80,
0x3f803f80,0x3f803f80,0x3f803f80,0x3f803f80,0x3f803f80,0x3f803f80,0x3f803f80,0x3f803f80,0x3f803f80,0x3f803f80,0x3f803f80,0x3f803f80,
0x3f803f80,0x3f803f80,0x3f803f80,0x3f803f80,0x3f803f80,0x3f803f80,0x3f803f80,0x3f803f80,0x3f803f80,0x3f803f80,0x3f803f80,0x3f803f80,
0x3f803f80,0x3f803f80,0x3f803f80,0x3f803f80,0x3f803f80,0x3f803f80,0x3f803f80,0x3f803f80,0x3f803f80,0x3f803f80,0x3f803f80,0x3f803f80,
0x3f803f80,0x3f803f80,0x3f803f80,0x3f803f80,0x3f803f80,0x3f803f80,0x3f803f80,0x3f803f80,0x3f803f80,0x3f803f80,0x3f803f80,0x3f803f80,
0x3f803f80,0x3f803f80,0x3f803f80,0x3f803f80,0x3f803f80,0x3f803f80,0x3f803f80,0x3f803f80,0x3f803f80,0x3f803f80,0x3f803f80,0x3f803f80,
0x3f803f80,0x3f803f80,0x3f803f80,0x3f803f80,0x3f803f80,0x3f803f80,0x3f803f80,0x3f803f80,0x3f803f80,0x3f803f80,0x3f803f80,0x3f803f80,
0x3f803f80,0x3f803f80,0x3f803f80,0x3f803f80,0x3f803f80,0x3f803f80,0x3f803f80,0x3f803f80,0x3f803f80,0x3f803f80,0x3f803f80,0x3f803f80,
0x3f803f80,0x3f803f80,0x3f803f80,0x3f803f80,0x3f803f80,0x3f803f80,0x3f803f80,0x3f803f80,0x3f803f80,0x3f803f80,0x3f803f80,0x3f803f80,
0x3f803f80,0x3f803f80,0x3f803f80,0x3f803f80,0x3f803f80,0x3f803f80,0x3f803f80,0x3f803f80,0x3f803f80,0x3f803f80,0x3f803f80,0x3f803f80,
0x3f803f80,0x3f803f80,0x3f803f80,0x3f803f80,0x3f803f80,0x3f803f80,0x3f803f80,0x3f803f80,0x3f803f80,0x3f803f80,0x3f803f80,0x3f803f80,
0x3f803f80,0x3f803f80,0x3f803f80,0x3f803f80,0x3f803f80,0x3f803f80,0x3f803f80,0x3f803f80,0x3f803f80,0x3f803f80,0x3f803f80,0x3f803f80,
0x3f803f80,0x3f803f80,0x3f803f80,0x3f803f80,0x3f803f80,0x3f803f80,0x3f803f80,0x3f803f80,0x3f803f80,0x3f803f80,0x3f803f80,0x3f803f80,
0x3f803f80,0x3f803f80,0x3f803f80,0x3f803f80,0x3f803f80,0x3f803f80,0x3f803f80,0x3f803f80,0x3f803f80,0x3f803f80,0x3f803f80,0x3f803f80,
0x3f803f80,0x3f803f80,0x3f803f80,0x3f803f80,0x3f803f80,0x3f803f80,0x3f803f80,0x3f803f80,0x3f803f80,0x3f803f80,0x3f803f80,0x3f803f80,
0x3f803f80,0x3f803f80,0x3f803f80,0x3f803f80,0x3f803f80,0x3f803f80,0x3f803f80,0x3f803f80,0x3f803f80,0x3f803f80,0x3f803f80,0x3f803f80,
0x3f803f80,0x3f803f80,0x3f803f80,0x3f803f80,0x3f803f80,0x3f803f80,0x3f803f80,0x3f803f80,0x3f803f80,0x3f803f80,0x3f803f80,0x3f803f80,
0x3f803f80,0x3f803f80,0x3f803f80,0x3f803f80,0x3f803f80,0x3f803f80,0x3f803f80,0x3f803f80,0x3f803f80,0x3f803f80,0x3f803f80,0x3f803f80,
0x3f803f80,0x3f803f80,0x3f803f80,0x3f803f80,0x3f803f80,0x3f803f80,0x3f803f80,0x3f803f80,0x3f803f80,0x3f803f80,0x3f803f80,0x3f803f80,
0x3f803f80,0x3f803f80,0x3f803f80,0x3f803f80,0x3f803f80,0x3f803f80,0x3f803f80,0x3f803f80,0x3f803f80,0x3f803f80,0x3f803f80,0x3f803f80,
0x3f803f80,0x3f803f80,0x3f803f80,0x3f803f80,0x3f803f80,0x3f803f80,0x3f803f80,0x3f803f80,0x3f803f80,0x3f803f80,0x3f803f80,0x3f803f80,
0x3f803f80,0x3f803f80,0x3f803f80,0x3f803f80,0x3f803f80,0x3f803f80,0x3f803f80,0x3f803f80,0x3f803f80,0x3f803f80,0x3f803f80,0x3f803f80,
0x3f803f80,0x3f803f80,0x3f803f80,0x3f803f80,0x3f803f80,0x3f803f80,0x3f803f80,0x3f803f80,0x3f803f80,0x3f803f80,0x3f803f80,0x3f803f80,
0x3f803f80,0x3f803f80,0x3f803f80,0x3f803f80,0x3f803f80,0x3f803f80,0x3f803f80,0x3f803f80,0x3f803f80,0x3f803f80,0x3f803f80,0x3f803f80,
0x3f803f80,0x3f803f80,0x3f803f80,0x3f803f80,0x3f803f80,0x3f803f80,0x3f803f80,0x3f803f80,0x3f803f80,0x3f803f80,0x3f803f80,0x3f803f80,
0x3f803f80,0x3f803f80,0x3f803f80,0x3f803f80,0x3f803f80,0x3f803f80,0x3f803f80,0x3f803f80,0x3f803f80,0x3f803f80,0x3f803f80,0x3f803f80,
0x3f803f80,0x3f803f80,0x3f803f80,0x3f803f80,0x3f803f80,0x3f803f80,0x3f803f80,0x3f803f80,0x3f803f80,0x3f803f80,0x3f803f80,0x3f803f80,
0x3f803f80,0x3f803f80,0x3f803f80,0x3f803f80,0x3f803f80,0x3f803f80,0x3f803f80,0x3f803f80,0x3f803f80,0x3f803f80,0x3f803f80,0x3f803f80,
0x3f803f80,0x3f803f80,0x3f803f80,0x3f803f80,0x3f803f80,0x3f803f80,0x3f803f80,0x3f803f80,0x3f803f80,0x3f803f80,0x3f803f80,0x3f803f80,
0x3f803f80,0x3f803f80,0x3f803f80,0x3f803f80,0x3f803f80,0x3f803f80,0x3f803f80,0x3f803f80,0x3f803f80,0x3f803f80,0x3f803f80,0x3f803f80,
0x3f803f80,0x3f803f80,0x3f803f80,0x3f803f80,0x3f803f80,0x3f803f80,0x3f803f80,0x3f803f80,0x3f803f80,0x3f803f80,0x3f803f80,0x3f803f80,
0x3f803f80,0x3f803f80,0x3f803f80,0x3f803f80,0x3f803f80,0x3f803f80,0x3f803f80,0x3f803f80,0x3f803f80,0x3f803f80,0x3f803f80,0x3f803f80,
0x3f803f80,0x3f803f80,0x3f803f80,0x3f803f80,0x3f803f80,0x3f803f80,0x3f803f80,0x3f803f80,0x3f803f80,0x3f803f80,0x3f803f80,0x3f803f80,
0x3f803f80,0x3f803f80,0x3f803f80,0x3f803f80,0x3f803f80,0x3f803f80,0x3f803f80,0x3f803f80,0x3f803f80,0x3f803f80,0x3f803f80,0x3f803f80,
0x3f803f80,0x3f803f80,0x3f803f80,0x3f803f80,0x3bf23bff,0x3ba53bd4,0x3b163b65,0x3a493ab6,0x3b7c3bfb,0x38bc3a60,0x2b43356a,0xb7f3b359,
0x3a933bf1,0x9cb63764,0xba9eb785,0xbb73bbf3,0x39463be2,0xb8cc28e8,0xbb42bbc2,0x3328b70a,0x374e3bcf,0xbbabb648,0xaec3baa9,0x3bfa3994,
0x33403bb7,0xbb85b9fc,0x3a64b0be,0x2c6a3b47,0xa4523b9a,0xb86abbae,0x3b6a3911,0xbbd0ad65,0xb4263b78,0x2adebbe6,0x30f03bfd,0xb5b1bbbc,
0x2f5925e4,0x34b73294,0x376f361a,0x38f3385a,0x35a52c9c,0x3a7338d6,0x3bfd3b87,0x3af13bc9,0x388e2fbd,0x3c003b18,0x387f3b10,0xb5d42f27,
0x3a04316c,0x3a673bfe,0xb6bb33d3,0xbbccbb2f,0x3b1e32f7,0x34933b5c,0xbbf5b86f,0x2d00b9bc,0x3bcb343e,0xb576394f,0xb8d1bbe9,0x3bfb36a4,
0x3c0034ff,0xbaac347b,0x3602ba31,0x32de3bf9,0x3bba35bc,0xbbfdb109,0x3be7aa7a,0xbb7a341a,0x394639cd,0x381538b2,0x358136dd,0x3153341a,
0xbb1eb9c9,0xbbf5bbdd,0xba39bb65,0xb4f3b889,0xb340b93c,0x3966340e,0x3bec3b87,0x37213a7e,0x3c003a4d,0x32193a21,0xbb5eb785,0xb894bbb0,
0xb426389e,0xbb37bb45,0x38b7b3d3,0x397d3bfc,0xbafebac1,0x3b13217f,0xadc93aa9,0xba49bb59,0x3979b7e8,0xb0d73b32,0xb6f4bbe9,0x3af139da,
0x38553b24,0xb9a1ba3d,0x3ab03911,0xbb73b759,0x3a043982,0x3ae13a7a,0x3b833b3a,0x3be33bbc,0x374e3986,0xae9131e8,0xb907b61a,0xbb9cba97,
0xbbcbba0d,0xb9e7bbbd,0x3074b56a,0x3b2a38ad,0x2452b8ee,0x3bda3924,0x363c3b10,0xba90b46f,0x3bba3a89,0xb6e836af,0xba76bbc2,0x39d2ac06,
0xb7c8384a,0xb77abc00,0x3bf8386f,0xb8f33654,0xb9d6baf4,0x3be836ff,0xbb3530be,0x37f3b974,0x3abab737,0xb9af3902,0x3865ba31,0xb5d43b1b,
0x32c62fbd,0x363134cf,0x38653785,0x398b38fd,0xb715b16c,0xbae1b970,0xbbfebbc2,0xba85bb92,0x392e32f7,0x3bf53b6c,0x37a63aa9,0xb7422311,
0xba81b43e,0xb9e7bbfc,0x380fb0be,0x3b963b7f,0x3b7134ff,0x32193b04,0xbc00b911,0x319eb929,0xbbefb5bc,0x36e8b8b2,0x382a3bfd,0xbbffb805,
0x3bf23676,0xbb1331e8,0x376fb9aa,0x2f8b3bde,0xbb7cb72c,0x3be8340e,0xbbfdaa16,0x3bb8b122,0xbbd2bbf1,0xbb60bba1,0xbab0bb10,0xb9c5ba41,
0x3b2c3be2,0x381539df,0xa94d33d3,0xb8a3b52f,0xba19bbcf,0x2e91b5f7,0x3b07386f,0x3b213c00,0x38a83bb7,0xb966aba7,0xbae5bbe9,0x3517b599,
0xb5dfbb9a,0x3bda37b2,0x1fdb3a31,0xbbe0ba1d,0x30293b78,0xbb37ba7a,0x3ad5aa7a,0xa7763aeb,0x2f59bb52,0x377a3bdd,0xbb16b9a6,0x3bf231cf,
0xb5a53b27,0x30d7bbbd,0x2b433bfe,0xb432bbe5,0x3a813a0d,0x3b3f3ae8,0x3bbf3b87,0x3bfb3be5,0xb5dfb8ee,0x3263ad97,0x399d3785,0x3bd03b01,
0xbbefba89,0xb958bb81,0x3389b3d3,0x3b7a394a,0xaf59384a,0xbbf7b9b8,0xb4c3baa9,0x3afb35eb,0x3b7c3af4,0xb825353a,0xb9f8bbe9,0x3a542884,
0x388eb737,0x360e3bf4,0xbbdcb911,0x398bb4db,0xb946bb4f,0x3bc03830,0xbb832a7a,0x38a3b8db,0xbb1e35c8,0x3a35b85f,0xb90739aa,0x3742bab6,
0xb8a8b93c,0xb6c6b80a,0xb402b56a,0xac6ab122,0xbb71ba4d,0xbbd7bbf8,0xb9b3bb10,0xb2deb7bd,0x3029389e,0xb9f4b58d,0xbbc6bbc2,0xb5b1ba00,
0x3bf23ac1,0x2dfb3999,0xbba3b86f,0xb7d2bb6f,0x35a5b7e8,0x3ad83b90,0xb95430be,0xb8e5bbff,0xba93bb24,0x3b682ef5,0xb2013a31,0xb9c5bb9f,
0xba043682,0x33ebbad1,0x35813bfd,0xba85ba5c,0x374e3b76,0xb90cbab3,0x3a3939a6,0xbb21b85a,0xb7c83b52,0x391bba9b,0xba2539aa,0x3afbb889,
0xb9793b27,0x3bc5b80a,0xbb8eaa16,0x38e538ad,0xbaba3af7,0x3b60ad97,0xb27cba2d,0xb98b3bb0,0xbb943ac4,0x3815358d,0x39e3bbea,0xba852c06,
0xbbf93a8c,0xae9139b8,0x3bacb874,0x3742bb59,0xbbe43a50,0xb9663b90,0x340233ba,0x3b96b974,0xbb573a11,0xbbda3bf4,0xb99d3b0d,0xb19e3759,
0xba5839cd,0xbb373ad1,0xbbc63b89,0xbbff3bee,0x3afe3676,0xba29b884,0x391f39a6,0xb7d2ba97,0x39d6372c,0xb3a2bae8,0xb5463bfe,0x3a54ba7e,
0x385537dd,0x3631bbf8,0xbbd63916,0x39c5346f,0x35233845,0x3ae1bb81,0xb96bb0a6,0xb8a33bfc,0x2d333899,0x3bf5b999,0x3487baa5,0xbb213654,
0xb13b38ea,0x39e7b53a,0x3bbfbbc3,0x3517b9da,0xb65f3937,0x32192ef5,0x39b3b790,0x3be0bb1b,0xb8e03982,0xb6e83830,0xb389355e,0xa7763042,
0xbb943682,0x3bebb371,0xbbfe2a7a,0x3bcc3042,0xad33bb76,0xb79b3bd4,0x3b07b9aa,0xbbfa32ad,0x3be4b50b,0xb6c6b8d6,0xb80f3bfe,0x3bfbb835,
0xb65f3bb5,0x3bd7b764,0x9fdbba2d,0xbbd03a41,0xba58330f,0xb9f43bfe,0x382a30a6,0x3b7abb92,0x3a45bbe1,0xadfbb648,0xbb163874,0xbafb3c00,
0x3699afef,0x3ad8b94f,0x3bfdbbc3,0x3a54bb7f,0xbbdf3bfa,0xbb683bae,0xba9e3b0d,0xb98b3a1d,0x35233b4f,0xb08dbbc8,0xa94d3bfd,0x3328bbee,
0xbbf935c8,0x3b0a3294,0xb7a6b9a6,0xad003bd3,0x313bbb98,0xbb3f3a60,0x3ae52a16,0xac6abace,0x3b57b44b,0x3263bb18,0xbc003916,0x32de38fd,
0xb8e03bce,0x3958a8e8,0x3ad5bbea,0xb5b1b52f,0xb8f83185,0xbbf73b5c,0xb76f3aa5,0x37d2a311,0x3b4abbf0,0x3825b9fc,0xab43b3ba,0xb8e53599,
0x31b6acce,0x360eb47b,0x387fb790,0x39c5b929,0x3a9337dd,0xb9a1b924,0x387f3a2d,0xb66bbb01,0xb946b845,0x308d3b45,0x36bbbbea,0xbac73a00,
0x374e3899,0x379bbc00,0xbbf53874,0x393335eb,0xb340b8ea,0xbb3f3b32,0x38d133ba,0x3941bbff,0xa4523937,0x3bd7b902,0x3602bb0d,0xbabd34db,
0x3426b982,0xb9583371,0xbbe73b89,0xb68d3a5c,0xb7c839c9,0x2dfb3294,0x391fb625,0x3bb3bab6,0x3979ba0d,0x3825b8d6,0x3546b6d2,0x3010b359,
0x388ebaf7,0xb9af3a21,0x3a9eb916,0xbb5437bd,0xba043ac4,0x3bebb6af,0xbb42b0a6,0x3840394a,0x3b1eba8c,0xbb0aa17f,0x2ec33aa5,0x3a15bb6f,
0xbbcb3a50,0x36c636ff,0x3a64bbc3,0xba09a884,0x3c00ba11,0x3263ba3d,0xbb6a3790,0xb8503b9f,0xbbba39cd,0xb9f43bc8,0x30f0355e,0x3b4cb8db,
0x3afeb986,0x3bf7bbd4,0x3a25bb63,0x3457b85a,0xb9d6393c,0xbad83a60,0xbb8e3b3d,0xbbef3bc9,0x33403b98,0xa9b1bbed,0xb0743bfe,0x3517bbc9,
0x3c00b44b,0xbaa2b4cf,0x363c3a2d,0x319ebbf3,0x3426bbce,0xbb8b39df,0x3a7630a6,0x2776bb2f,0xbafe3185,0xb4b73b6c,0x3bf8b874,0xaf8bb994,
0xb9793bf0,0x38bc2ba7,0x3b35bbc3,0xb432b6a4,0x3855acce,0x3c00bb04,0x3865bb0d,0xb66bad65,0x3b94bbff,0x38ccba7a,0x294db55e,0xb840341a,
0xad33a5e4,0xb49331e8,0xb7a63625,0xb9333889,0x3bcbb50b,0xbbfe305b,0x3bec2a16,0xbb96b359,0x2452bbb5,0xb87a3ba1,0x3b5eb916,0xbbe02f27,
0xbbba330f,0x35523970,0x38b7bbea,0xbbff370a,0xb7c83be1,0x3ba5b5f7,0x2dc9baa5,0xbbf239bc,0x39d6afef,0x3a73bbfc,0xb6f4b3ba,0xbbb83b47,
0x3ababbfa,0x1cb6b7b2,0xbab03790,0xbb543bf9,0xb52326ad,0xba6738b2,0xbbfe3b89,0xbac73bbc,0xbbf93bff,0xbbab3bdd,0xbb073b63,0xba153a97,
0xb8f83986,0xb77a385f,0xb4c33625,0xaf8b32ad,0xb699393c,0x30d7305b,0x3954b6d2,0x3bb8bace,0xb1b638ee,0x39afb4cf,0x3bdcbba7,0x366bba41,
0x2c38389e,0x3bebb970,0x3581bade,0xbac7352f,0x34e7384a,0x3b0abb6c,0xb907b24b,0xb9333c00,0x383a37e8,0x36c6bbfc,0xbbec38c1,0x39413599,
0x39c03737,0xb263bb04,0xb63c3bf6,0x3abdba1d,0x3aee3682,0xb9f4b8b2,0x38b739f0,0xb68dbaeb,0xba4539c9,0xbb133ab3,0xbba33b63,0xbbf23bd3,
0xbb4a3a0d,0xbbe83bed,0xb9f83b3d,0xb4323835,0xbbdf3a4d,0xb9a13ba1,0x320134ab,0x3b54b8fd,0xbbfc3a89,0xb08d39df,0x3b83b81a,0x3840bb92,
0xbb9e3ac1,0x379b35f7,0x3a39bbd8,0xba15a311,0xbacb3af4,0x3b3faba7,0xb074ba6f,0xba093b7f,0xb9903b24,0x3bd7b7b2,0xbb5eae5f,0x38503929,
0xb7fe3b4f,0x3958ba7a,0xba76395d,0x3b4cb805,0x2c3826ad,0x33ebb109,0x36bbb55e,0x38a3b805,0x3b9ebbff,0x390cba9b,0x2ec3b625,0xb74231cf,
0xb83a2c9c,0xbbfe3ae8,0xb8d13b3d,0x35173122,0xb9903bf1,0x387a2d97,0x3b6abba7,0xb19eb7bd,0x3aeeb16c,0x3552bb81,0xbbe7381a,0x27763a00,
0x3463bbcf,0xbba539b8,0x3a25324b,0x2f8bbb6f,0xbbff343e,0x3a73353a,0xb546ba6f,0xb4323bff,0x32c63b9a,0x9cb6bbf4,0xb27c3bf6,0x366bbb9f,
0xbbfc3bff,0xbbc03be6,0xbb423b89,0xba853aeb,0x34e7a5e4,0x3a35b884,0x3bf5bb63,0x3b21bbde,0x3acbbbfb,0x29b1b80a,0xba6436d2,0xbb963be5,
0xb9c02fbd,0xbaa23bf8,0x360234ab,0x3be0bb01,0xb7fe3be2,0x3b8bb58d,0x30f0bade,0xbbff394a,0x3bb2b2f7,0xb4b7b999,0xb91f3bd8,0x3bf2b5eb,
0x281fbbb7,0xb8bc3b90,0x3b8eb8c1,0xbbb82884,0xbbd234ff,0x3c00aef5,0xbbd6ae5f,0x3b5434db,0xbaba3a4d,0xbb683b18,0xbbd63ba7,0xbc003bf3,
0x3b94ba89,0x3bc0bbfe,0x396bbade,0x3153b70a,0xbbf93ac1,0xb90c3b5c,0x3487324b,0x3b9cb994,0x3be4baf4,0x29b1b94f,0xbbbf38c1,0xb7213b47,
0xbb573b24,0x387a347b,0x39b3bbf6,0xba902d65,0x3a58bb4f,0xbb8b3109,0x338939f0,0x397dbbbc,0xb8f83b76,0x3ba5b884,0xbba39648,0x38f33889,
0x3699bb98,0xb8bc3ae8,0x39f8b9eb,0xbaf138ad,0x3855b8ee,0x360eb764,0x327cb4ab,0x251baf27,0xb523389e,0x33eb28e8,0x39e3b81a,0x3be3bb2f,
0x2d33b84a,0xba353648,0xbbac3bd8,0xb4f339bc,0x313b37e8,0x3bfeb9fc,0x3402ba6f,0xbb2a36a4,0xb65fb737,0xbaa23bae,0x399d2e5f,0x3894bbf9,
0x38e03682,0x3552bbe6,0xbbc6395d,0x39d2341a,0xba45b5c8,0x34b73a9b,0x34c3bc00,0xba493a97,0x3b4a350b,0xba73b80a,0x39543962,0xb7f3ba7e,
0xbbe43bfb,0xbb853bbd,0xbae53b3d,0xba093a7e,0xb65f2fbd,0xbaac3924,0xbc003ba7,0xbabd3bb0,0x3a58bbe2,0xaadeb6af,0xbad5381a,0xbb4c3bfc,
0x3a45b2f7,0x3a29bc00,0xb76fb24b,0xbbb33b59,0xb6993bb7,0x3bc5b6ff,0x2b43ba6f,0xbbef39da,0xbbdf34ff,0x36313902,0x387fbbf6,0xbc003759,
0xac38bb78,0xb8153bc8,0x3b42b95d,0xbbe33042,0x3b9eb676,0xbbf53294,0x3bf51648,0xbb9cb2ad,0xb13b2c9c,0xb576340e,0xb80f36d2,0xb94138ad,
0x3b57bbf1,0x386aba21,0x1fdbb4ab,0xb850346f,0x38e0b16c,0x3bfdbb45,0x382abade,0xb68dac06,0xb8f83bcf,0x391ba17f,0x3b16bbd8,0xb457b654,
0xbb4a343e,0xb3a23b32,0x3bfdb8c1,0xb010b974,0x31b6bb9a,0xbb603a3d,0x3a9e2e5f,0x251bbb1b,0x3bfcb5bc,0xbae1b371,0x36bb39f0,0x3153bbee,
0x34e73b52,0xae91bbd4,0xaec33c00,0x34f3bbd3,0x3bb235c8,0xbbf7b1e8,0x3bf81648,0xbbb331cf,0x3bff350b,0xbad8340e,0x36f4b9eb,0x30103be5,
0x3bd2344b,0xb60e3924,0xb865bbf6,0x3c0037bd,0x3b2c330f,0x33eb3b45,0xbbfeb8c7,0x3153b94a,0x3a193185,0x3a353c00,0xb7a63232,0xbb9cbb6f,
0x38a82fef,0x3bfe3b32,0x380f3adb,0xb7212884,0x35df2cce,0x3aa23902,0x3c003ba9,0x3a903b9f,0x302926ad,0x35523371,0x382a36dd,0x397d38db,
0xb4633b76,0x2dfbbbdd,0x2dc93c00,0xb457bbde,0xa81f3b98,0xb825bbbd,0x3b353962,0xbbefb122,0x32c63bb5,0xbb68ba21,0x3ab0ae2d,0xa51b3b01,
0x37153bce,0xbbc0b6af,0xa94dba6b,0x3be33a00,0x392e3be1,0xb90c217f,0xbb07bbd9,0x34f3b5eb,0x3a813bf0,0xa9b136ff,0xbae5b820,0xbb2abbff,
0x3b713bfa,0x387a3a3d,0x9fdb349f,0xb894b4db,0x3bef3bff,0x3b8b3bc8,0x3ad53b3a,0x39d23a5c,0x3b2cb5bc,0xba673830,0x396bb95d,0xb8403a5c,
0xb92ebb52,0x3bab385f,0xbbac9648,0x3933b85a,0xb8a8372c,0xb576bbed,0x3bbf3962,0xba093359,0x3b713af7,0xb86a34cf,0xb99dbbf6,0x3abd2f27,
0x3029b845,0x3bfd39df,0x33893a6b,0xbb4cb70a,0xbbf2ba8c,0xb91bbb6c,0x34c3b232,0x3bb339bc,0x35a538ea,0xb3a22ba7,0xb9f8b820,0xbbefbb47,
0x3a933a11,0x3b603b04,0x3bdc3ba9,0x3c003bf9,0x37153b78,0xb8ccbad1,0x39e339f0,0xbac7b8db,0x3a19b676,0xb4933ab3,0xb487bc00,0x3a153ab6,
0xba81bb27,0x3b85305b,0xb40239eb,0xb941bbc9,0xb5df37dd,0xbaacbba1,0x39b3ae2d,0x38503bf3,0x3bef3ac4,0x2ade3970,0xbbc6b8c7,0xb68dbb2f,
0xaf59b899,0x3a2935f7,0x3ba33bd9,0x34573994,0xbb7cba50,0xbbc5bbfc,0xb954badb,0xb010b6a4,0x388e3937,0x363137b2,0x3201349f,0xa51b2d65,
0xb1b63bb5,0x9cb6bbf8,0x32013bf6,0xb5d4bbb0,0xac38bbce,0x38cc3b81,0xbb83b8c7,0x3bcc2c06,0x34e73be1,0xbbabb999,0x3a39b232,0x2d003b59,
0xb83abbf0,0x3b85353a,0x30743adb,0xbbfbb974,0x39c03bfa,0xb86a2ef5,0xbb5ebba9,0x32deb759,0xbaeebbff,0xaadeb830,0x3a7636dd,0x3b7a3bee,
0x3bb23bff,0x391b3ab3,0x2dc9361a,0xb7d2b2ad,0xbbffbbfb,0xbbc5bbed,0xbb35bb87,0xba54bace,0xbbdfb44b,0x3c002d97,0xbbdc2e2d,0x3b73b46f,
0x3bfc330f,0xba67358d,0x3581ba6b,0x33283bfc,0xbb9eb185,0x3493b9b8,0x39073bd9,0xbbfab654,0x3acb2fef,0x35763b90,0xbbecb820,0x2c6ab9da,
0xb990acce,0xbaacbbf4,0x363cb49f,0x3bd03b1b,0x37fe26ad,0x3bfd3ad1,0x38b73b3a,0xb5b13042,0xb46325e4,0xba29b85f,0xbbf8bb65,0xbafbbbd3,
0x281fac9c,0x33a2305b,0x36f4356a,0x38e53835,0x383a3b27,0xb966ba60,0x3a643962,0xbb2ab835,0xb99037dd,0x3219bb18,0x36023bf6,0xba90ba41,
0xbaeebac4,0x3b3728e8,0xb0f03a6b,0xb9d2bb92,0x3463b899,0x3b133b5c,0xb91f3232,0xb8f3bc00,0x3bff3a50,0x30d739fc,0xbb8eb820,0xb7f3bb7f,
0x32c63937,0xb9a1b47b,0xbbd6bba9,0xb5d4ba1d,0xbb2cb9cd,0xbbebbbe6,0xb9e3bb3a,0xb328b805,0xb92eb9c9,0xb79bb884,0xb487b61a,0xad00b1cf,
0xbacb372c,0x39e7b8d6,0xb8d139eb,0x3721bace,0xb9c0baf7,0x3bda3764,0xbb6a2e2d,0x3894b8fd,0x37feb845,0x36e83bfe,0xbbe7b8c7,0x397db52f,
0x3bb23a8c,0xb77a3648,0xba25bbd9,0x3a492311,0xa81f38ea,0xbbe8b94f,0xb546badb,0x3af13599,0xbbd2ba11,0xb9afbbae,0x327cb49f,0x3b733929,
0xb715b982,0x308db109,0x396b36dd,0x3bcc3aeb,0x3a193986,0x3b0a3a9b,0x3bac3b65,0x3bfa3bde,0x30003000,0x30003000,0x30003000,0x30003000,
0x2f643000,0x2a1f2da8,0xaa1f0000,0xaf64ada8,0x2da83000,0xada80000,0xada8b000,0x2da88000,0x2a1f3000,0xaf64ada8,0x2f648000,0xaa1f2da8,
0x00003000,0x8000b000,0x00003000,0x8000b000,0xaa1f3000,0x2f64ada8,0xaf640000,0x2a1f2da8,0xada83000,0x2da88000,0x2da8b000,0xada80000,
0xaf643000,0xaa1f2da8,0x2a1f8000,0x2f64ada8,0x30003000,0x30003000,0x30003000,0x30003000,0xaf64b000,0xaa1fada8,0x2a1f8000,0x2f642da8,
0x2da83000,0xada80000,0xada8b000,0x2da88000,0xaa1fb000,0x2f642da8,0xaf640000,0x2a1fada8,0x00003000,0x8000b000,0x00003000,0x8000b000,
0x2a1fb000,0xaf642da8,0x2f648000,0xaa1fada8,0xada83000,0x2da88000,0x2da8b000,0xada80000,0x2f64b000,0x2a1fada8,0xaa1f0000,0xaf642da8,
0x80008000,0x80008000,0x80008000,0x80008000,0xaa1f8000,0xaf64ada8,0xaf64b000,0xaa1fada8,0xada88000,0xada8b000,0x2da88000,0x2da83000,
0xaf648000,0x2a1fada8,0x2a1f3000,0xaf64ada8,0xb0008000,0x30008000,0xb0008000,0x30008000,0xaf648000,0x2a1f2da8,0x2a1fb000,0xaf642da8,
0xada88000,0xada83000,0x2da88000,0x2da8b000,0xaa1f8000,0xaf642da8,0xaf643000,0xaa1f2da8,0x80008000,0x80008000,0x80008000,0x80008000,
0x2a1f8000,0x2f642da8,0x2f643000,0x2a1f2da8,0xada88000,0xada8b000,0x2da88000,0x2da83000,0x2f648000,0xaa1f2da8,0xaa1fb000,0x2f642da8,
0xb0008000,0x30008000,0xb0008000,0x30008000,0x2f648000,0xaa1fada8,0xaa1f3000,0x2f64ada8,0xada88000,0xada83000,0x2da88000,0x2da8b000,
0x2a1f8000,0x2f64ada8,0x2f64b000,0x2a1fada8,0xb0003000,0xb0003000,0xb0003000,0xb0003000,0xaf643000,0xaa1f2da8,0x2a1f0000,0x2f64ada8,
0xada83000,0x2da80000,0x2da8b000,0xada88000,0xaa1f3000,0x2f64ada8,0xaf648000,0x2a1f2da8,0x80003000,0x0000b000,0x80003000,0x0000b000,
0x2a1f3000,0xaf64ada8,0x2f640000,0xaa1f2da8,0x2da83000,0xada88000,0xada8b000,0x2da80000,0x2f643000,0x2a1f2da8,0xaa1f8000,0xaf64ada8,
0xb0003000,0xb0003000,0xb0003000,0xb0003000,0x2f64b000,0x2a1fada8,0xaa1f8000,0xaf642da8,0xada83000,0x2da80000,0x2da8b000,0xada88000,
0x2a1fb000,0xaf642da8,0x2f640000,0xaa1fada8,0x80003000,0x0000b000,0x80003000,0x0000b000,0xaa1fb000,0x2f642da8,0xaf648000,0x2a1fada8,
0x2da83000,0xada88000,0xada8b000,0x2da80000,0xaf64b000,0xaa1fada8,0x2a1f0000,0x2f642da8,0x80008000,0x80008000,0x80008000,0x80008000,
0x2a1f8000,0x2f64ada8,0x2f64b000,0x2a1fada8,0x2da88000,0x2da8b000,0xada88000,0xada83000,0x2f648000,0xaa1fada8,0xaa1f3000,0x2f64ada8,
0x30008000,0xb0008000,0x30008000,0xb0008000,0x2f648000,0xaa1f2da8,0xaa1fb000,0x2f642da8,0x2da88000,0x2da83000,0xada88000,0xada8b000,
0x2a1f8000,0x2f642da8,0x2f643000,0x2a1f2da8,0x80008000,0x80008000,0x80008000,0x80008000,0xaa1f8000,0xaf642da8,0xaf643000,0xaa1f2da8,
0x2da88000,0x2da8b000,0xada88000,0xada83000,0xaf648000,0x2a1f2da8,0x2a1fb000,0xaf642da8,0x30008000,0xb0008000,0x30008000,0xb0008000,
0xaf648000,0x2a1fada8,0x2a1f3000,0xaf64ada8,0x2da88000,0x2da83000,0xada88000,0xada8b000,0xaa1f8000,0xaf64ada8,0xaf64b000,0xaa1fada8,
0x00000000,0x00000000,0x00000000,0x00000000,0x2a1f0000,0x2f642da8,0x2f643000,0x2a1f2da8,0x2da80000,0x2da83000,0xada80000,0xada8b000,
0x2f640000,0xaa1f2da8,0xaa1fb000,0x2f642da8,0x30000000,0xb0000000,0x30000000,0xb0000000,0x2f640000,0xaa1fada8,0xaa1f3000,0x2f64ada8,
0x2da80000,0x2da8b000,0xada80000,0xada83000,0x2a1f0000,0x2f64ada8,0x2f64b000,0x2a1fada8,0x00000000,0x00000000,0x00000000,0x00000000,
0xaa1f0000,0xaf64ada8,0xaf64b000,0xaa1fada8,0x2da80000,0x2da83000,0xada80000,0xada8b000,0xaf640000,0x2a1fada8,0x2a1f3000,0xaf64ada8,
0x30000000,0xb0000000,0x30000000,0xb0000000,0xaf640000,0x2a1f2da8,0x2a1fb000,0xaf642da8,0x2da80000,0x2da8b000,0xada80000,0xada83000,
0xaa1f0000,0xaf642da8,0xaf643000,0xaa1f2da8,0x30003000,0x30003000,0x30003000,0x30003000,0x2f643000,0x2a1f2da8,0xaa1f0000,0xaf64ada8,
0x2da83000,0xada80000,0xada8b000,0x2da88000,0x2a1f3000,0xaf64ada8,0x2f648000,0xaa1f2da8,0x00003000,0x8000b000,0x00003000,0x8000b000,
0xaa1f3000,0x2f64ada8,0xaf640000,0x2a1f2da8,0xada83000,0x2da88000,0x2da8b000,0xada80000,0xaf643000,0xaa1f2da8,0x2a1f8000,0x2f64ada8,
0x30003000,0x30003000,0x30003000,0x30003000,0xaf64b000,0xaa1fada8,0x2a1f8000,0x2f642da8,0x2da83000,0xada80000,0xada8b000,0x2da88000,
0xaa1fb000,0x2f642da8,0xaf640000,0x2a1fada8,0x00003000,0x8000b000,0x00003000,0x8000b000,0x2a1fb000,0xaf642da8,0x2f648000,0xaa1fada8,
0xada83000,0x2da88000,0x2da8b000,0xada80000,0x2f64b000,0x2a1fada8,0xaa1f0000,0xaf642da8,0x00000000,0x00000000,0x00000000,0x00000000,
0xaa1f0000,0xaf642da8,0xaf643000,0xaa1f2da8,0xada80000,0xada83000,0x2da80000,0x2da8b000,0xaf640000,0x2a1f2da8,0x2a1fb000,0xaf642da8,
0xb0000000,0x30000000,0xb0000000,0x30000000,0xaf640000,0x2a1fada8,0x2a1f3000,0xaf64ada8,0xada80000,0xada8b000,0x2da80000,0x2da83000,
0xaa1f0000,0xaf64ada8,0xaf64b000,0xaa1fada8,0x00000000,0x00000000,0x00000000,0x00000000,0x2a1f0000,0x2f64ada8,0x2f64b000,0x2a1fada8,
0xada80000,0xada83000,0x2da80000,0x2da8b000,0x2f640000,0xaa1fada8,0xaa1f3000,0x2f64ada8,0xb0000000,0x30000000,0xb0000000,0x30000000,
0x2f640000,0xaa1f2da8,0xaa1fb000,0x2f642da8,0xada80000,0xada8b000,0x2da80000,0x2da83000,0x2a1f0000,0x2f642da8,0x2f643000,0x2a1f2da8,
0xb0003000,0xb0003000,0xb0003000,0xb0003000,0xaf643000,0xaa1f2da8,0x2a1f0000,0x2f64ada8,0xada83000,0x2da80000,0x2da8b000,0xada88000,
0xaa1f3000,0x2f64ada8,0xaf648000,0x2a1f2da8,0x80003000,0x0000b000,0x80003000,0x0000b000,0x2a1f3000,0xaf64ada8,0x2f640000,0xaa1f2da8,
0x2da83000,0xada88000,0xada8b000,0x2da80000,0x2f643000,0x2a1f2da8,0xaa1f8000,0xaf64ada8,0xb0003000,0xb0003000,0xb0003000,0xb0003000,
0x2f64b000,0x2a1fada8,0xaa1f8000,0xaf642da8,0xada83000,0x2da80000,0x2da8b000,0xada88000,0x2a1fb000,0xaf642da8,0x2f640000,0xaa1fada8,
0x80003000,0x0000b000,0x80003000,0x0000b000,0xaa1fb000,0x2f642da8,0xaf648000,0x2a1fada8,0x2da83000,0xada88000,0xada8b000,0x2da80000,
0xaf64b000,0xaa1fada8,0x2a1f0000,0x2f642da8};

constexpr int kThreads = 384;
constexpr int kCtas = 128;

constexpr uint32_t SM_BASE = 1024;
constexpr uint32_t QKV_STAGE = 32768;
constexpr uint32_t SLOT = 16384;
constexpr uint32_t SM_KV = 2 * SLOT;
constexpr uint32_t SM_SIG = 131072;
constexpr uint32_t SM_STG = 196608;
constexpr uint32_t SM_Q = SM_STG;
constexpr uint32_t SM_Y0 = 3 * SLOT;
constexpr uint32_t SM_YT = SM_STG + 16384;
constexpr uint32_t SM_TW = SM_STG + 24576, SM_ONES = SM_TW + 2048, SM_F1 = SM_ONES + 2048, SM_F2 = SM_F1 + 4096;
constexpr uint32_t SM_BAR = SM_F2 + 2048;
constexpr uint32_t SM_SC = SM_BAR + 640;
constexpr uint32_t SM_TOTAL = 232448;
constexpr uint32_t A_SLOTS = 0xA02B1, B_SLOTS = 0x97654;

enum Bar { B_QKV_EMPTY = 0, B_QKV_DONE = 4,
           B_OUT_EMPTY = 8,
           B_H_FULL = 16, B_YIN = 19, B_RDY0 = 21, B_Q_FULL = 22, B_ZEROED = 23,
           B_OUT_FULL = 24, B_PREP_FULL = 29,
           B_RDY1 = 32, B_STG_FREE = 33, B_OT_FREE = 36, B_Y_READY = 38, B_FLAGS1 = 39,
           B_SEG = 40, B_SIG_READY = 44,
           B_KVP = 48, B_O_WRITTEN = 49, B_SLOT_FREE = 51, B_CONV_DONE = 52,
           B_PREP_EMPTY = 56, B_KV_READY = 59,
           B_QKV_FULL = 64, B_FIRST = 68 };
constexpr uint32_t BAR_LOG2 = 0x13200044;

constexpr int KV_SLICE = 640;
constexpr int XCH_FLAG = 2 * SLOT + 17 * KV_SLICE;
constexpr int XCH_BYTES = 11 * 4096;

struct Params {
  CUtensorMap x, w, wk, wo, outa, k, v, q;
  const __nv_bfloat16* shift_k;
  const __nv_bfloat16* ssm_k;
  const __nv_bfloat16* ssm_d;
  const __nv_bfloat16* q_ptr;
  __nv_bfloat16* out_ptr;
  const __nv_bfloat16* wo_ptr;
  int zero;
};

__device__ __align__(128) uint8_t g_xch[kCtas][XCH_BYTES];
__device__ unsigned g_ready, g_epoch[kCtas];

#define TSTAMP(cond, i) do { } while (0)
#define GSTAMP(cond, i) do { } while (0)
#define LOOPSTAMP(id, cond, i) do { } while (0)

constexpr int kSpinLimit = 1 << 17;

DEVI void mbar_init(uint32_t a, uint32_t c) { asm volatile("mbarrier.init.shared::cta.b64 [%0], %1;" :: "r"(a), "r"(c) : "memory"); }
DEVI void mbar_expect(uint32_t a, uint32_t b) { asm volatile("mbarrier.arrive.expect_tx.shared::cta.b64 _, [%0], %1;" :: "r"(a), "r"(b) : "memory"); }
DEVI void mbar_arrive(uint32_t a) { asm volatile("mbarrier.arrive.shared::cta.b64 _, [%0];" :: "r"(a) : "memory"); }
DEVI void mbar_arrive_if(uint32_t a, bool pred) {
  asm volatile("{\n.reg .pred p;\nsetp.ne.b32 p, %1, 0;\n@p mbarrier.arrive.shared::cta.b64 _, [%0];\n}" :: "r"(a), "r"((int)pred) : "memory");
}
DEVI void mbar_wait(uint32_t a, uint32_t parity) {
  asm volatile("{\n.reg .pred p;\n.reg .u32 n;\nmov.u32 n, 0;\nW_LOOP:\n"
               "mbarrier.try_wait.parity.shared::cta.b64 p, [%0], %1;\nadd.u32 n, n, 1;\n"
               "setp.lt.and.u32 p, n, %2, !p;\n@p bra W_LOOP;\n}"
               :: "r"(a), "r"(parity), "n"(kSpinLimit) : "memory");
}
DEVI bool mbar_test(uint32_t a, uint32_t parity) {
  uint32_t ok;
  asm volatile("{\n.reg .pred p;\nmbarrier.test_wait.parity.shared::cta.b64 p, [%1], %2;\nselp.u32 %0, 1, 0, p;\n}" : "=r"(ok) : "r"(a), "r"(parity) : "memory");
  return ok;
}
DEVI bool elect() {
  uint32_t ok;
  asm volatile("{\n.reg .pred p;\nelect.sync _|p, 0xffffffff;\nselp.u32 %0, 1, 0, p;\n}" : "=r"(ok));
  return ok;
}
DEVI void flag_wait(const unsigned* p, unsigned target) {
  int n = 0; unsigned v;
  do {
    asm volatile("ld.acquire.gpu.global.u32 %0, [%1];" : "=r"(v) : "l"(p) : "memory");
  } while ((int)(v - target) < 0 && ++n < kSpinLimit);
}
DEVI uint32_t clock32() { uint32_t t; asm volatile("mov.u32 %0, %%clock;" : "=r"(t) :: "memory"); return t; }
DEVI void delay(uint32_t cycles) { const uint32_t t = clock32(); while (clock32() - t < cycles) { } }
DEVI void st_relaxed(void* p, uint32_t v) { asm volatile("st.relaxed.gpu.global.b32 [%0], %1;" :: "l"(p), "r"(v) : "memory"); }
DEVI uint32_t ld_relaxed(const void* p) { uint32_t v; asm volatile("ld.relaxed.gpu.global.b32 %0, [%1];" : "=r"(v) : "l"(p) : "memory"); return v; }
DEVI void ld_relaxed4(uint32_t* v, const void* p) {
  asm volatile("ld.relaxed.gpu.global.v4.b32 {%0,%1,%2,%3}, [%4];" : "=r"(v[0]), "=r"(v[1]), "=r"(v[2]), "=r"(v[3]) : "l"(p) : "memory");
}
template <int N> DEVI uint32_t umax(const uint32_t* v) {
  if constexpr (N == 1) return v[0];
  else if constexpr (N == 2) return max(v[0], v[1]);
  else if constexpr (N <= 6) return __vimax3_u32(v[0], v[1], umax<N - 2>(v + 2));
  else return __vimax3_u32(umax<N / 3 | 1>(v), umax<N / 3 | 1>(v + (N / 3 | 1)), umax<N - 2 * (N / 3 | 1)>(v + 2 * (N / 3 | 1)));
}
template <int N> DEVI bool all_arrived(const uint32_t* v) { return __all_sync(0xffffffffu, umax<N>(v) != 0xffffffffu); }
DEVI void flag_add(unsigned* p) {
  asm volatile("fence.release.gpu;\nred.relaxed.gpu.global.add.u32 [%0], 1;" :: "l"(p) : "memory");
}
DEVI void fence_async_smem() { asm volatile("fence.proxy.async.shared::cta;" ::: "memory"); }
DEVI void bar_sync(int id, int n) { asm volatile("bar.sync %0, %1;" :: "r"(id), "r"(n) : "memory"); }
DEVI void cluster_arrive() { asm volatile("barrier.cluster.arrive.relaxed.aligned;" ::: "memory"); }
DEVI void cluster_wait() { asm volatile("barrier.cluster.wait.aligned;" ::: "memory"); }
DEVI void wg_fence() { asm volatile("wgmma.fence.sync.aligned;" ::: "memory"); }
DEVI void wg_commit() { asm volatile("wgmma.commit_group.sync.aligned;" ::: "memory"); }
template <int N> DEVI void wg_wait() { asm volatile("wgmma.wait_group.sync.aligned %0;" :: "n"(N) : "memory"); }
template <int N> DEVI void pin(uint32_t* r) {
#pragma unroll
  for (int i = 0; i < N; i++) asm volatile("" : "+r"(r[i]) :: "memory");
}
template <int N> DEVI void pin(float* r) {
#pragma unroll
  for (int i = 0; i < N; i++) asm volatile("" : "+f"(r[i]) :: "memory");
}

DEVI void sched_fence(int zero, int id) { asm volatile("{\n.reg .pred p;\nsetp.eq.b32 p, %0, %1;\nS_LOOP:\n@p st.volatile.shared.b32 [%0], %0;\n@p bra S_LOOP;\n}" :: "r"(zero), "r"(id + 1) : "memory"); }
DEVI void pin_range(float* r, int i0, int i1) {
#pragma unroll
  for (int i = i0; i < i1; i++) asm volatile("" : "+f"(r[i]) :: "memory");
}
DEVI void keep(uint32_t& x) { asm volatile("" : "+r"(x) :: "memory"); }
DEVI void keep(int& x) { asm volatile("" : "+r"(x) :: "memory"); }
template <class T> DEVI void keep(T*& x) { asm volatile("" : "+l"(x) :: "memory"); }

DEVI void tma2d(uint32_t dst, const CUtensorMap* m, int c0, int c1, uint32_t bar) {
  asm volatile("cp.async.bulk.tensor.2d.shared::cluster.global.mbarrier::complete_tx::bytes [%0], [%1, {%3, %4}], [%2];"
               :: "r"(dst), "l"(m), "r"(bar), "r"(c0), "r"(c1) : "memory");
}
DEVI void tma2d_mc(uint32_t dst, const CUtensorMap* m, int c0, int c1, uint32_t bar) {
  asm volatile("cp.async.bulk.tensor.2d.shared::cluster.global.mbarrier::complete_tx::bytes.multicast::cluster [%0], [%1, {%3, %4}], [%2], %5;"
               :: "r"(dst), "l"(m), "r"(bar), "r"(c0), "r"(c1), "h"((uint16_t)3) : "memory");
}
DEVI void tma3d(uint32_t dst, const CUtensorMap* m, int c0, int c1, int c2, uint32_t bar) {
  asm volatile("cp.async.bulk.tensor.3d.shared::cluster.global.mbarrier::complete_tx::bytes [%0], [%1, {%3, %4, %5}], [%2];"
               :: "r"(dst), "l"(m), "r"(bar), "r"(c0), "r"(c1), "r"(c2) : "memory");
}
DEVI void tma3d_mc(uint32_t dst, const CUtensorMap* m, int c0, int c1, int c2, uint32_t bar) {
  asm volatile("cp.async.bulk.tensor.3d.shared::cluster.global.mbarrier::complete_tx::bytes.multicast::cluster [%0], [%1, {%3, %4, %5}], [%2], %6;"
               :: "r"(dst), "l"(m), "r"(bar), "r"(c0), "r"(c1), "r"(c2), "h"((uint16_t)3) : "memory");
}
DEVI void tma2d_store(const CUtensorMap* m, uint32_t src, int c0, int c1) {
  asm volatile("cp.async.bulk.tensor.2d.global.shared::cta.bulk_group [%0, {%2, %3}], [%1];" :: "l"(m), "r"(src), "r"(c0), "r"(c1) : "memory");
}
DEVI void bulk_load(uint32_t dst, const void* src, uint32_t bytes, uint32_t bar) {
  asm volatile("cp.async.bulk.shared::cluster.global.mbarrier::complete_tx::bytes [%0], [%1], %2, [%3];" :: "r"(dst), "l"(src), "r"(bytes), "r"(bar) : "memory");
}
DEVI void bulk_store(void* dst, uint32_t src, uint32_t bytes) {
  asm volatile("cp.async.bulk.global.shared::cta.bulk_group [%0], [%1], %2;" :: "l"(dst), "r"(src), "r"(bytes) : "memory");
}
DEVI uint32_t peer_addr(uint32_t a, int rank) { uint32_t r; asm("mapa.shared::cluster.u32 %0, %1, %2;" : "=r"(r) : "r"(a), "r"(rank)); return r; }
DEVI void bulk_to_peer(uint32_t dst, uint32_t src, uint32_t bytes, uint32_t bar, int rank) {
  asm volatile("cp.async.bulk.shared::cluster.shared::cta.mbarrier::complete_tx::bytes [%0], [%1], %2, [%3];"
               :: "r"(peer_addr(dst, rank)), "r"(src), "r"(bytes), "r"(peer_addr(bar, rank)) : "memory");
}
DEVI void l2_prefetch(const void* p, uint32_t bytes) {
  asm volatile("cp.async.bulk.prefetch.L2.global [%0], %1;" :: "l"(p), "r"(bytes) : "memory");
}
DEVI void l2_prefetch2d(const CUtensorMap* m, int c0, int c1) {
  asm volatile("cp.async.bulk.prefetch.tensor.2d.L2.global [%0, {%1, %2}];" :: "l"(m), "r"(c0), "r"(c1) : "memory");
}
DEVI void l2_prefetch3d(const CUtensorMap* m, int c0, int c1, int c2) {
  asm volatile("cp.async.bulk.prefetch.tensor.3d.L2.global [%0, {%1, %2, %3}];" :: "l"(m), "r"(c0), "r"(c1), "r"(c2) : "memory");
}
DEVI void bulk_commit() { asm volatile("cp.async.bulk.commit_group;" ::: "memory"); }
DEVI void bulk_wait_read() { asm volatile("cp.async.bulk.wait_group.read 0;" ::: "memory"); }
DEVI void prefetch_map(const CUtensorMap* m) { asm volatile("prefetch.tensormap [%0];" :: "l"(m) : "memory"); }
DEVI void arrive_both(uint32_t bar, int lane, bool pred = true) {
  asm volatile("{\n.reg .pred p;\n.reg .b32 r;\nsetp.ne.b32 p, %2, 0;\nmapa.shared::cluster.u32 r, %0, %1;\n@p mbarrier.arrive.shared::cluster.b64 _, [r];\n}"
               :: "r"(bar), "r"(lane & 1), "r"((int)(pred && lane < 2)) : "memory");
}

DEVI uint64_t make_desc(uint32_t off, uint32_t lbo, uint32_t sbo, uint32_t mode) {
  const uint32_t lo = (off >> 4) + (SM_BASE >> 4) + ((lbo >> 4) << 16), hi = (sbo >> 4) | (mode << 30);
  return ((uint64_t)hi << 32) | lo;
}
DEVI uint32_t pack_bf16(float lo, float hi) { uint32_t r; asm("cvt.rn.bf16x2.f32 %0, %1, %2;" : "=r"(r) : "f"(hi), "f"(lo)); return r; }
DEVI void stsm4(uint32_t addr, uint32_t r0, uint32_t r1, uint32_t r2, uint32_t r3) {
  asm volatile("stmatrix.sync.aligned.m8n8.x4.shared.b16 [%0], {%1,%2,%3,%4};" :: "r"(addr), "r"(r0), "r"(r1), "r"(r2), "r"(r3) : "memory");
}
DEVI void stsm4_t(uint32_t addr, uint32_t r0, uint32_t r1, uint32_t r2, uint32_t r3) {
  asm volatile("stmatrix.sync.aligned.m8n8.x4.trans.shared.b16 [%0], {%1,%2,%3,%4};" :: "r"(addr), "r"(r0), "r"(r1), "r"(r2), "r"(r3) : "memory");
}
DEVI void ldsm4(uint32_t* r, uint32_t addr) {
  asm volatile("ldmatrix.sync.aligned.m8n8.x4.shared.b16 {%0,%1,%2,%3}, [%4];" : "=r"(r[0]), "=r"(r[1]), "=r"(r[2]), "=r"(r[3]) : "r"(addr) : "memory");
}
DEVI void ldsm4_t(uint32_t* r, uint32_t addr) {
  asm volatile("ldmatrix.sync.aligned.m8n8.x4.trans.shared.b16 {%0,%1,%2,%3}, [%4];" : "=r"(r[0]), "=r"(r[1]), "=r"(r[2]), "=r"(r[3]) : "r"(addr) : "memory");
}
DEVI uint4 lds128(uint32_t a) {
  uint4 v; asm volatile("ld.shared.v4.b32 {%0,%1,%2,%3}, [%4];" : "=r"(v.x), "=r"(v.y), "=r"(v.z), "=r"(v.w) : "r"(a) : "memory"); return v;
}
DEVI uint32_t bmul2(uint32_t a, uint32_t b) { uint32_t r; asm("mul.rn.bf16x2 %0, %1, %2;" : "=r"(r) : "r"(a), "r"(b)); return r; }
DEVI uint32_t bfma2(uint32_t a, uint32_t b, uint32_t c) { uint32_t r; asm("fma.rn.bf16x2 %0, %1, %2, %3;" : "=r"(r) : "r"(a), "r"(b), "r"(c)); return r; }
DEVI float bf_lo(uint32_t w) { return __uint_as_float(w << 16); }
DEVI float bf_hi(uint32_t w) { return __uint_as_float(w & 0xffff0000u); }
DEVI uint32_t elu1(float a0, float a1) {
  constexpr float L = 1.4426950408889634f;
  float e0, e1;
  asm("ex2.approx.ftz.f32 %0, %1;" : "=f"(e0) : "f"(-fabsf(fmaf(a0, L, -L))));
  asm("ex2.approx.ftz.f32 %0, %1;" : "=f"(e1) : "f"(-fabsf(fmaf(a1, L, -L))));
  return pack_bf16(fmaxf(e0, a0), fmaxf(e1, a1));
}
DEVI float rcp(float x) { float r; asm("rcp.approx.ftz.f32 %0, %1;" : "=f"(r) : "f"(x)); return r; }
DEVI uint32_t add_eps(uint32_t x) { uint32_t r; asm("add.rn.bf16x2 %0, %1, %2;" : "=r"(r) : "r"(x), "r"(0x35863586u)); return r; }

DEVI uint32_t hmul(uint32_t a, uint32_t b) { uint32_t r; asm("mul.rn.f16x2 %0, %1, %2;" : "=r"(r) : "r"(a), "r"(b)); return r; }
DEVI uint32_t hfma(uint32_t a, uint32_t b, uint32_t c) { uint32_t r; asm("fma.rn.f16x2 %0, %1, %2, %3;" : "=r"(r) : "r"(a), "r"(b), "r"(c)); return r; }
DEVI uint32_t hneg(uint32_t a) { uint32_t r; asm("neg.f16x2 %0, %1;" : "=r"(r) : "r"(a)); return r; }
DEVI uint32_t hadd(uint32_t a, uint32_t b) { uint32_t r; asm("add.rn.f16x2 %0, %1, %2;" : "=r"(r) : "r"(a), "r"(b)); return r; }
DEVI uint32_t hsub(uint32_t a, uint32_t b) { uint32_t r; asm("sub.rn.f16x2 %0, %1, %2;" : "=r"(r) : "r"(a), "r"(b)); return r; }
struct Cx { uint32_t re, im; };
DEVI Cx cmul(Cx a, Cx b) { return {hfma(a.re, b.re, hneg(hmul(a.im, b.im))), hfma(a.re, b.im, hmul(a.im, b.re))}; }
DEVI Cx cfma(Cx a, Cx b, Cx c) { return {hfma(a.re, b.re, hfma(hneg(a.im), b.im, c.re)), hfma(a.re, b.im, hfma(a.im, b.re, c.im))}; }
DEVI Cx rot(Cx a, Cx t) {
  const uint32_t x = hfma(hneg(t.re), a.im, a.re), y = hfma(t.im, x, a.im);
  return {hfma(hneg(t.re), y, x), y};
}
struct Fft {
  uint32_t fa[8];
  Cx tw[2];
  uint32_t vld;
  uint64_t dF2a, dF2b;
  uint32_t vst;
  DEVI void stage1(uint32_t* d1, uint32_t slot) const {
    wg_fence();
    fft1_init(d1, fa[0], fa[1], fa[2], fa[3], make_desc(slot, 4096, 1024, 1));
    fft1_acc(d1, fa[4], fa[5], fa[6], fa[7], make_desc(slot + 2048, 4096, 1024, 1));
    wg_commit();
  }
  DEVI void stage2(uint32_t* d, const Cx* t) const {
    wg_fence();
    fft2_init(d, t[0].re, t[1].re, t[2].re, t[3].re, dF2a);
    fft2_acc(d, t[0].im, t[1].im, t[2].im, t[3].im, dF2b);
    wg_commit();
  }
  template <int PR> DEVI void fwd(const uint32_t* d1, uint32_t* d2) const {
    Cx t[4];
#pragma unroll
    for (int e = 0; e < 4; e++) {
      const int j = 8 * (PR & 1) + 4 * (e >> 1) + 2 * (PR >> 1) + (e & 1);
      t[e] = rot({d1[2 * j], d1[2 * j + 1]}, tw[e >> 1]);
    }
    stage2(d2 + 8 * PR, t);
  }
  static DEVI Cx U(const uint32_t* d2, int p, int hi) { return {d2[16 * (p >> 1) + 2 * hi + (p & 1)], d2[16 * (p >> 1) + 4 + 2 * hi + (p & 1)]}; }
  static DEVI Cx H(const uint32_t* d2, int p, int hi) { return U(d2 + 8, p, hi); }
  DEVI void prod01(const uint32_t* d2, Cx* p1, uint32_t* d3) const {
    Cx z[4];
#pragma unroll
    for (int hi = 0; hi < 2; hi++) {
      const Cx p0 = cmul(H(d2, 0, hi), U(d2, 0, hi));
      p1[hi] = cfma(H(d2, 1, hi), U(d2, 0, hi), cmul(H(d2, 0, hi), U(d2, 1, hi)));
      z[2 * hi] = {p0.im, p0.re};
      z[2 * hi + 1] = {hsub(p1[hi].im, p0.re), hadd(p1[hi].re, p0.im)};
    }
    stage2(d3, z);
  }
  DEVI void prod23(const uint32_t* d2, const Cx* p1, uint32_t* d3) const {
    Cx z[4];
#pragma unroll
    for (int hi = 0; hi < 2; hi++) {
      const Cx p2 = cfma(H(d2, 2, hi), U(d2, 0, hi), cfma(H(d2, 0, hi), U(d2, 2, hi), cmul(H(d2, 1, hi), U(d2, 1, hi))));
      const Cx z3 = cfma(H(d2, 3, hi), U(d2, 0, hi), cfma(H(d2, 2, hi), U(d2, 1, hi),
                    cfma(H(d2, 1, hi), U(d2, 2, hi), cfma(H(d2, 0, hi), U(d2, 3, hi), {p2.im, hneg(p2.re)}))));
      z[2 * hi] = {hsub(p2.im, p1[hi].re), hadd(p2.re, p1[hi].im)};
      z[2 * hi + 1] = {z3.im, z3.re};
    }
    stage2(d3 + 8, z);
  }
  template <int PB> DEVI void inv(const uint32_t* d3, uint32_t slot) const {
    Cx v[4];
#pragma unroll
    for (int e = 0; e < 4; e++) {
      const int r = 8 * PB + 2 * (e & 1) + (e >> 1);
      v[e] = rot({d3[r], d3[r + 4]}, tw[e & 1]);
    }
    stsm4(slot + (vst ^ (PB * 64)), v[0].im, v[1].im, v[2].im, v[3].im);
    stsm4(slot + 1024 + (vst ^ (PB * 64)), v[0].re, v[1].re, v[2].re, v[3].re);
  }
  DEVI void last_load(uint32_t* a, uint32_t slot, int wg) const {
    bar_sync(2 + wg, 128);
#pragma unroll
    for (int ks = 0; ks < 4; ks++) ldsm4_t(a + 4 * ks, vld + slot + ks * 2048);
  }
  DEVI void last_mma(float* dy, const uint32_t* a) const {
    wg_fence();
    fft3_init(dy, a[0], a[1], a[2], a[3], make_desc(SM_F1, 128, 1024, 0));
#pragma unroll
    for (int ks = 1; ks < 4; ks++) fft3_acc(dy, a[4 * ks], a[4 * ks + 1], a[4 * ks + 2], a[4 * ks + 3], make_desc(SM_F1 + ks * 256, 128, 1024, 0));
    wg_commit();
  }
  DEVI void last(float* dy, uint32_t slot, int wg) const { uint32_t a[16]; last_load(a, slot, wg); last_mma(dy, a); }
  static DEVI void store_y(const float* dy, uint32_t a) {
    stsm4_t(a, pack_bf16(dy[0], dy[1]), pack_bf16(dy[2], dy[3]), pack_bf16(dy[4], dy[5]), pack_bf16(dy[6], dy[7]));
    stsm4_t(a + 512, pack_bf16(dy[8], dy[9]), pack_bf16(dy[10], dy[11]), pack_bf16(dy[12], dy[13]), pack_bf16(dy[14], dy[15]));
  }
};
DEVI uint32_t normalize(uint32_t* x, uint32_t dst) {
  uint32_t m = x[0];
#pragma unroll
  for (int i = 1; i < 32; i++) asm("max.xorsign.abs.bf16x2 %0, %0, %1;" : "+r"(m) : "r"(x[i]));
  const uint32_t e = min(__reduce_max_sync(0xffffffffu, max(m & 0x7fffu, (m >> 16) & 0x7fffu)) >> 7, 252u);
  if (e > 140) {
#pragma unroll
    for (int i = 0; i < 32; i++) x[i] = bmul2(x[i], 15u * 0x00800080u);
  }
  const uint32_t sc = (e > 140 ? 253u - e : 141u - e) * 0x00800080u;
#pragma unroll
  for (int i = 0; i < 8; i++) {
    uint32_t y[4];
#pragma unroll
    for (int n = 0; n < 4; n++) {
      const uint32_t w = bmul2(x[4 * i + n], sc);
      y[n] = (w & 0x7fff7fffu) * 7u + w;
    }
    stsm4((dst ^ ((i >> 1) << 4)) + (i & 1) * 2048, y[0], y[1], y[2], y[3]);
  }
  return e;
}
#define XPF 3
#define HSTART 3
#define PSTART 5
#define PF0 28
#define PD1 600
#define PD2 500
#define PD3 900
#define FDELAY 100
#define C1DELAY 200
#define FORCE_REDO 0
static_assert(HSTART >= 4 - XPF && PF0 >= HSTART + 19 && PF0 <= 28, "producer schedule");

__global__ void __cluster_dims__(2, 1, 1) __launch_bounds__(kThreads, 1)
fused_kernel(const __grid_constant__ Params P) {
  extern __shared__ __align__(1024) uint8_t smem[];
  if (threadIdx.x == 0) { prefetch_map(&P.x); prefetch_map(&P.w); prefetch_map(&P.wk); prefetch_map(blockIdx.x & 1 ? &P.v : &P.k); }
  const uint32_t sb = __shfl_sync(0xffffffffu, (uint32_t)__cvta_generic_to_shared(smem), 0);
  const int tid = threadIdx.x, lane = tid & 31;
  const int warp = __shfl_sync(0xffffffffu, tid >> 5, 0);
  const int bc = blockIdx.x >> 1, late = ((bc - 36) * 37) >> 8;
  const int rp = bc < 4 ? 0 : bc < 36 ? (bc - 4) & 7 : bc - 35 - 7 * late, j = bc < 4 ? 4 + bc : bc < 36 ? (bc - 4) >> 3 : 4 + late;
  const int rho = blockIdx.x & 1, cl = 8 * rp + j, cta = 2 * cl + rho, r = rp * 2 + rho;
  auto bar = [&](int i) { return sb + SM_BAR + 8u * i; };
  TSTAMP(tid == 0, 0); GSTAMP(tid == 0, 30);
  auto load_stage = [&](int it) {
    const uint32_t st = sb + (it & 3) * QKV_STAGE, fb = bar(B_QKV_FULL + (it & 3));
    mbar_expect(fb, QKV_STAGE);
    tma2d_mc(st + 24576 + rho * 4096, &P.wk, 1024 + 128 * j + 64 * rho, 32 * it, fb);
    tma3d_mc(st + 8192 + rho * 8192, &P.w, 0, 32 * it, 32 * rho + 2 * j, fb);
    tma2d(st, &P.x, 32 * it, 128 * r, fb);
  };
  if (warp == 8 && elect()) {
    mbar_init(bar(B_FIRST), 1);
    mbar_expect(bar(B_FIRST), 16384);
    tma2d(sb, &P.x, 0, 128 * r, bar(B_FIRST));
    tma3d(sb + 24576, &P.w, 0, 0, 16 + 2 * j, bar(B_FIRST));
    mbar_init(bar(B_QKV_FULL), 1);
    mbar_expect(bar(B_QKV_FULL), 16384);
    tma3d(sb + 8192, &P.w, 0, 0, 2 * j, bar(B_QKV_FULL));
    tma3d(sb + 16384, &P.w, 0, 0, 32 + 2 * j, bar(B_QKV_FULL));
    for (int i = 1; i < 4; i++) mbar_init(bar(B_QKV_FULL + i), 1);
    asm volatile("fence.mbarrier_init.release.cluster;" ::: "memory");
  }
  LOOPSTAMP(3, tid == 256, 13);
  __syncwarp();
  cluster_arrive();

  if (warp < 8) {
    asm volatile("setmaxnreg.inc.sync.aligned.u32 224;");
    const int wg = warp >> 2, wq = warp & 3;
    const int zero = __shfl_sync(0xffffffffu, P.zero, 0);
    const uint32_t orow = wq * 2048 + (lane & 15) * 128, ox = ((lane >> 4) ^ (lane & 7)) << 4;
    float aq[64];
    Fft F;
    uint32_t a1[32];
    {
      float ak[64], avq[128];
      auto k_step = [&](uint32_t st, int kk) {
        mma_tn(ak, make_desc(st + 24576 + wg * 4096 + kk * 2048, 4096, 1024, 1), make_desc(st + kk * 32, 16, 512, 2));
      };
      auto vq_step = [&](uint32_t st, int kk) {
        mma_nt256(avq, make_desc(st + wg * 4096 + kk * 32, 16, 512, 2), make_desc(st + 8192 + kk * 2048, 4096, 1024, 1));
      };
#pragma unroll
      for (int i = 0; i < 64; i++) { ak[i] = 1.f; avq[i] = 1.f; avq[64 + i] = 0.f; }
      pin<64>(ak); pin<128>(avq);
      cluster_wait();
      cluster_arrive();
      cluster_wait();
      LOOPSTAMP(3, tid == 0, 17);
      mbar_wait(bar(B_FIRST), 0);
      TSTAMP(tid == 0, 1);
      wg_fence();
      k_step(0, 0); k_step(0, 1);
      wg_commit();
      mbar_wait(bar(B_QKV_FULL), 0);
      wg_fence();
      vq_step(0, 0); vq_step(0, 1);
      wg_commit();
#pragma unroll 1
      for (int it = 1; it < 29; ++it) {
        mbar_wait(bar(B_QKV_FULL + (it & 3)), (it >> 2) & 1);
        TSTAMP(tid == 0 && it == 4, 6); TSTAMP(tid == 0 && it == 12, 29); LOOPSTAMP(1, tid == 0 && it < 27, 1 + it); LOOPSTAMP(3, tid == 0 && it < 12, 1 + it);
        const uint32_t st = (it & 3) * QKV_STAGE;
        wg_fence();
        k_step(st, 0);
        wg_commit();
        wg_wait<1>();
        arrive_both(bar(B_QKV_EMPTY + ((it - 1) & 3)), lane);
        wg_fence();
        vq_step(st, 0);
        k_step(st, 1);
        vq_step(st, 1);
        wg_commit();
      }
#pragma unroll 1
      for (int s = 1; s < 4; ++s) {
        mbar_wait(bar(B_QKV_FULL + s), 1);
        wg_fence();
        k_step(s * QKV_STAGE, 0);
        k_step(s * QKV_STAGE, 1);
        wg_commit();
      }
      uint32_t pk[32];
      auto phi_k = [&](int i0, int i1) {
#pragma unroll
        for (int i = i0; i < i1; i++) { pk[i] = elu1(ak[2 * i], ak[2 * i + 1]); asm volatile("" : "+r"(pk[i]) :: "memory"); }
        sched_fence(zero, i0);
      };
#pragma unroll
      for (int n = 0; n < 6; n++) {
        wg_fence();
        vq_step((1 + (n >> 1)) * QKV_STAGE, n & 1);
        wg_commit();
        if (n == 0) {
          wg_wait<1>();
          pin<64>(ak);
          TSTAMP(tid == 0, 2);
          bar_sync(1, 256);
        }
        phi_k(n ? 6 * n - 4 : 0, 6 * n + 2);
      }
      mbar_wait(bar(B_SIG_READY), 0);
      ldsm4_t(F.fa, sb + SM_F1 + (lane >> 4) * 1024 + wq * 256 + (lane & 15) * 16);
      ldsm4_t(F.fa + 4, sb + SM_F1 + 2048 + (lane >> 4) * 1024 + wq * 256 + (lane & 15) * 16);
      const uint4 tw = lds128(sb + SM_TW + (tid & 127) * 16);
      F.tw[0] = {tw.x, tw.y}; F.tw[1] = {tw.z, tw.w};
      F.vld = sb + ((lane >> 4) * 8 + (lane & 7)) * 128 + (((2 * wq + ((lane >> 3) & 1)) ^ (lane & 7)) << 4);
      F.dF2a = make_desc(SM_F2, 128, 512, 0) + (uint64_t)zero * 0x100000001ull;
      F.dF2b = F.dF2a + 16;
      F.vst = sb + (16 * wq + (lane & 7)) * 128 + (((lane >> 3) ^ (lane & 7)) << 4);
      wg_wait<0>();
      pin<128>(avq);
      arrive_both(bar(B_QKV_DONE), lane);
      TSTAMP(tid == 0, 3);
#pragma unroll
      for (int t = 0; t < 8; t++) {
        const float* b = avq + 64 + 8 * t;
        stsm4(sb + (t >> 2) * SLOT + wg * 8192 + orow + (ox ^ ((t & 3) << 5)), pack_bf16(b[0], b[1]), pack_bf16(b[2], b[3]), pack_bf16(b[4], b[5]), pack_bf16(b[6], b[7]));
      }
#pragma unroll
      for (int i = 0; i < 64; i++) aq[i] = avq[i];
      fence_async_smem();
      bar_sync(1, 256);
      float dkv[36];
#pragma unroll
      for (int ks = 0; ks < 8; ks++) {
        const uint32_t va = wg * SLOT + ks * 2048;
        const uint64_t db = make_desc(va, SM_ONES - va, 1024, 1);
        uint32_t a[4];
        pin<4>(pk + 4 * ks);
#pragma unroll
        for (int i = 0; i < 4; i++) a[i] = add_eps(pk[4 * ks + i]);
        wg_fence();
        if (ks == 0) mma_kv_init(dkv, a[0], a[1], a[2], a[3], db);
        else mma_kv_acc(dkv, a[0], a[1], a[2], a[3], db);
      }
      wg_commit();
      uint8_t* box = g_xch[warp * 16 + j] + 2 * SLOT + r * KV_SLICE + lane * 16;
      uint8_t* zbox = box + (lane & 1) * 8 * XCH_BYTES + 512 + (lane & 28) - lane * 16;
      keep(box); keep(zbox);
      mbar_wait(bar(B_ZEROED), 0);
      wg_wait<0>();
      pin<36>(dkv);
      F.stage1(a1, SM_SIG + wg * 8192);
      TSTAMP(tid == 0, 4);
      auto put = [&](const float* d) {
#pragma unroll
        for (int m = 0; m < 2; m++)
          asm volatile("st.relaxed.gpu.global.v4.b32 [%0], {%1,%2,%3,%4};" :: "l"(box + m * 8 * XCH_BYTES), "r"(pack_bf16(d[2 * m], d[2 * m + 1])),
                       "r"(pack_bf16(d[2 * m + 4], d[2 * m + 5])), "r"(pack_bf16(d[2 * m + 8], d[2 * m + 9])), "r"(pack_bf16(d[2 * m + 12], d[2 * m + 13])) : "memory");
      };
      if (wq < 2) put(dkv); else put(dkv + 16);
      asm volatile("{\n.reg .pred p;\nsetp.eq.b32 p, %2, 0;\n@p st.relaxed.gpu.global.b32 [%0], %1;\n}" :: "l"(zbox), "f"(lane & 1 ? dkv[34] : dkv[32]), "r"(lane & 2) : "memory");
      __syncwarp();
      mbar_arrive_if(bar(B_KVP), lane == 0);
      TSTAMP(tid == 0, 5);
    }

    uint32_t pq[32];
    auto phi_q = [&](int i0, int i1) {
      pin_range(aq, 2 * i0, 2 * i1);
#pragma unroll
      for (int i = i0; i < i1; i++) { pq[i] = add_eps(elu1(aq[2 * i], aq[2 * i + 1])); keep(pq[i]); }
    };
    uint32_t a2[32];
    float by[16];
    auto conv_pair = [&](uint32_t sa, uint32_t ya, uint32_t first) {
      const uint32_t sc = sa + SLOT;
      uint32_t b1[32], b2[32], a3[16], b3[16];
      float ay[16];
      Cx pa[2], pb[2];
      F.stage1(b1, sc);
      F.prod01(a2, pa, a3);
      F.prod23(a2, pa, a3);
      uint32_t va[16];
      wg_wait<1>(); pin<32>(b1); pin<8>(a3);
      F.fwd<0>(b1, b2); F.fwd<1>(b1, b2);
      F.inv<0>(a3, sa);
      F.fwd<2>(b1, b2);
      wg_wait<3>(); pin<8>(a3 + 8);
      F.inv<1>(a3, sa);
      F.fwd<3>(b1, b2);
      F.last_load(va, sa, wg);
      wg_wait<2>(); pin<16>(b2);
      F.prod01(b2, pb, b3);
      F.last_mma(ay, va);
      wg_wait<2>(); pin<16>(b2 + 16);
      F.prod23(b2, pb, b3);
      mbar_wait(bar(B_RDY1), first);
      wg_wait<1>(); pin<8>(b3); pin<16>(ay);
      mbar_arrive_if(bar(B_SLOT_FREE), lane == 0);
      F.inv<0>(b3, sc);
      Fft::store_y(ay, ya);
      wg_wait<0>(); pin<8>(b3 + 8);
      F.inv<1>(b3, sc);
    };
    const bool ylocal = (wq >> 1) == rho;
    const uint32_t yoff = sb + (wq & 1) * 1024 + ((lane ^ wg ^ (2 * rho)) << 4);
    const uint32_t ya0 = yoff + (ylocal ? SM_Y0 + wg * 8192 : SM_YT + wg * 4096), ya1 = (yoff ^ 64) + (ylocal ? SM_SIG + wg * 8192 : SM_YT + wg * 4096);
    auto pair_done = [&](uint32_t ya, int seg) {
      pin<16>(by);
      Fft::store_y(by, (ya ^ 32) + 2048);
      __syncwarp();
      mbar_arrive_if(bar(B_SEG + 2 * seg + wg), lane == 0);
    };
    const uint32_t s0 = SM_SIG + wg * 8192, s1 = s0 + 2 * SLOT;
    phi_q(0, 2);
    wg_wait<0>(); pin<32>(a1);
    bar_sync(2 + wg, 128);
    F.fwd<0>(a1, a2); phi_q(2, 5);
    F.fwd<1>(a1, a2); phi_q(5, 8);
    F.fwd<2>(a1, a2); phi_q(8, 11);
    F.fwd<3>(a1, a2); phi_q(11, 13);
    wg_wait<0>(); pin<32>(a2);
#pragma unroll 1
    for (uint32_t sa = s0;; sa += 2 * SLOT + P.zero) {
      conv_pair(sa, sa == s1 ? ya1 : ya0, sa != s1);
      if (sa == s1) break;
      F.stage1(a1, s1);
      phi_q(13, 17);
      F.last(by, s0 + SLOT, wg);
      phi_q(17, 32);
      wg_wait<0>();
      pair_done(ya0, 0);
      TSTAMP(tid == 0, 7);
      float dn[4][20];
      pin<32>(a1);
      bar_sync(2 + wg, 128);
      F.fwd<0>(a1, a2); F.fwd<1>(a1, a2); F.fwd<2>(a1, a2);
      mbar_wait(bar(B_KV_READY), 0);
      TSTAMP(tid == 0, 8);
      auto head_mma = [&](int h) {
        wg_fence();
        const uint64_t db = make_desc(SM_KV + h * 2560, 640, 128, 0);
        const uint32_t* a = pq + 8 * h;
        mma_o_init(dn[h], a[0], a[1], a[2], a[3], db);
        mma_o_acc(dn[h], a[4], a[5], a[6], a[7], db + (1280 >> 4));
        wg_commit();
      };
      auto head_store = [&](int h) {
        pin<20>(dn[h]);
        const float i0 = rcp(dn[h][16] + 1e-6f), i1 = rcp(dn[h][18] + 1e-6f);
        const uint32_t p0 = pack_bf16(i0, i0), p1 = pack_bf16(i1, i1);
#pragma unroll
        for (int hf = 0; hf < 2; hf++) {
          const float* a = dn[h] + 8 * hf;
          const uint32_t dst = sb + (h >> 1) * SLOT + wg * 8192 + orow + (ox ^ (((h & 1) * 2 + hf) << 5));
          uint32_t o[4];
#pragma unroll
          for (int i = 0; i < 4; i++) o[i] = bmul2(pack_bf16(a[2 * i], a[2 * i + 1]), i & 1 ? p1 : p0);
          stsm4(dst, o[0], o[1], o[2], o[3]);
#pragma unroll
          for (int i = 0; i < 4; i++) pq[8 * h + 4 * hf + i] = o[i];
        }
        if (h & 1) { __syncwarp(); mbar_arrive_if(bar(B_O_WRITTEN + (h >> 1)), lane == 0); }
      };
      head_mma(0); head_mma(1);
      wg_wait<1>(); head_store(0);
      mbar_wait(bar(B_KV_READY + 1), 0);
      head_mma(2);
      wg_wait<1>(); head_store(1);
      head_mma(3);
      wg_wait<1>(); head_store(2);
      F.fwd<3>(a1, a2);
      wg_wait<1>(); head_store(3);
      wg_wait<0>();
      pin<32>(a2);
    }

    float acc[64];
    auto stage_mma = [&](int s, int kk) {
      mma_nt(acc, make_desc(((A_SLOTS >> (4 * s)) & 15) * SLOT + wg * 8192 + kk * 32, 16, 1024, 1),
             make_desc(((B_SLOTS >> (4 * s)) & 15) * SLOT + kk * 2048, 8192, 1024, 1));
    };
    {
      auto own_mma = [&](int n) {
        const uint64_t db = make_desc((4 + (n >> 2)) * SLOT + (n & 3) * 2048, 8192, 1024, 1);
        if (n == 0) mma_own_init(acc, pq[0], pq[1], pq[2], pq[3], db);
        else mma_own_acc(acc, pq[4 * n], pq[4 * n + 1], pq[4 * n + 2], pq[4 * n + 3], db);
      };
      mbar_wait(bar(B_OUT_FULL), 0);
      wg_fence();
      own_mma(0); own_mma(1);
      wg_commit();
      F.last(by, s1 + SLOT, wg);
      wg_fence();
      own_mma(2);
      wg_commit();
      wg_wait<1>();
      mbar_arrive_if(bar(B_CONV_DONE), lane == 0);
      cluster_arrive();
      wg_fence();
      own_mma(3);
      wg_commit();
      pair_done(ya1, 1);
      mbar_wait(bar(B_OUT_FULL + 1), 0);
      wg_fence();
      own_mma(4);
      wg_commit();
      wg_wait<1>();
      arrive_both(bar(B_OUT_EMPTY), lane);
      wg_fence();
      own_mma(5); own_mma(6); own_mma(7);
      wg_commit();
      int s = 2, sprev = 1;
      uint32_t ph = 0;
#pragma unroll 1
      for (int ks = 2; ks < 12; ++ks) {
        mbar_wait(bar(B_OUT_FULL + s), ph);
        LOOPSTAMP(2, tid == 0, 1 + ks);
        TSTAMP(tid == 0 && ks == 2, 13); TSTAMP(tid == 0 && ks == 9, 14);
        wg_fence();
        stage_mma(s, 0);
        wg_commit();
        wg_wait<1>();
        arrive_both(bar(B_OUT_EMPTY + sprev), lane);
        wg_fence();
#pragma unroll
        for (int kk = 1; kk < 4; kk++) stage_mma(s, kk);
        wg_commit();
        sprev = s;
        if (++s == 5) { s = 0; ph ^= 1; }
      }
#pragma unroll 1
      for (int ks = 12; ks < 16; ++ks) {
        asm volatile("{\n.reg .pred p;\nsetp.ne.b32 p, %0, 0;\n@p bar.sync 1, 256;\n}" :: "r"((int)(ks == 13 && wg)) : "memory");
        mbar_wait(bar(B_OUT_FULL + s), ks == 15);
        wg_fence();
#pragma unroll
        for (int kk = 0; kk < 4; kk++) stage_mma(s, kk);
        wg_commit();
        asm volatile("{\n.reg .pred p;\nsetp.ne.b32 p, %0, 0;\n@p bar.arrive 1, 256;\n}" :: "r"((int)(ks == 15 && !wg)) : "memory");
        if (++s == 5) s = 0;
      }
    }
    wg_wait<0>(); pin<64>(acc);
    TSTAMP(tid == 0, 15); TSTAMP(tid == 128, 16);
#pragma unroll
    for (int hf = 0; hf < 2; hf++) {
      const uint32_t dst = sb + hf * SLOT + wg * 8192;
#pragma unroll
      for (int t = 0; t < 4; t++) {
        const float* a = acc + 32 * hf + 8 * t;
        stsm4(dst + orow + (ox ^ (t << 5)), pack_bf16(a[0], a[1]), pack_bf16(a[2], a[3]), pack_bf16(a[4], a[5]), pack_bf16(a[6], a[7]));
      }
      fence_async_smem();
      __syncwarp();
      if (elect()) { tma2d_store(&P.outa, dst + wq * 2048, 128 * j + 64 * hf, 128 * r + 16 * warp); bulk_commit(); }
    }
    const bool stale = __any_sync(0xffffffffu, acc[0] != acc[0] || acc[2] != acc[2] || FORCE_REDO);
    if (elect()) bulk_wait_read();
    TSTAMP(tid == 128, 17);
    __syncwarp();
    cluster_wait();
    TSTAMP(tid == 128, 28); GSTAMP(tid == 128, 31);
    if (stale) {
      __threadfence();
#pragma unroll
      for (int i = 0; i < 64; i++) acc[i] = 0.f;
      const int row = warp * 16 + (lane >> 2);
#pragma unroll 1
      for (int k = 0; k < 1024; k += 2) {
        const uint8_t* src = g_xch[r * 8 + (k >> 7)] + ((k >> 6) & 1) * SLOT + row * 128 + ((((k >> 3) ^ row) & 7) << 4) + (k & 7) * 2;
        uint32_t a[2];
        int n = 0;
        do { a[0] = ld_relaxed(src); a[1] = ld_relaxed(src + 1024); } while (!all_arrived<2>(a) && ++n < kSpinLimit);
#pragma unroll 1
        for (int e = 0; e < 2; e++) {
          const float a0 = e ? bf_hi(a[0]) : bf_lo(a[0]), a1 = e ? bf_hi(a[1]) : bf_lo(a[1]);
          const uint32_t* wrow = reinterpret_cast<const uint32_t*>(P.wo_ptr + (k + e) * 1024 + 128 * j) + (lane & 3);
#pragma unroll
          for (int i = 0; i < 16; i++) {
            const uint32_t w = __ldg(wrow + 4 * i);
            acc[4 * i] += a0 * bf_lo(w); acc[4 * i + 1] += a0 * bf_hi(w);
            acc[4 * i + 2] += a1 * bf_lo(w); acc[4 * i + 3] += a1 * bf_hi(w);
          }
        }
      }
      uint32_t* op = reinterpret_cast<uint32_t*>(P.out_ptr + (128 * r + row) * 2048 + 128 * j) + (lane & 3);
#pragma unroll
      for (int i = 0; i < 32; i++) op[(i & 1) * 8192 + (i >> 1) * 4] = pack_bf16(acc[2 * i], acc[2 * i + 1]);
    }
  } else {
    asm volatile("setmaxnreg.dec.sync.aligned.u32 56;");
    if (warp == 8) {
      cluster_wait();
      cluster_arrive();
      LOOPSTAMP(3, tid == 256, 15);
#pragma unroll 1
      for (int it = 1; it < 4; it++) if (elect()) load_stage(it);
      LOOPSTAMP(3, tid == 256, 16);
      __syncwarp();
      cluster_wait();
    } else {
      if (elect()) {
#pragma unroll 1
        for (int g = warp - 9; g < 8; g += 3)
          for (int i = 0; i < 8; i++) mbar_init(bar(8 * g + i), 1u << ((BAR_LOG2 >> (4 * g)) & 7));
        if (warp == 11) for (int i = 0; i < 7; i++) mbar_expect(bar(B_H_FULL + i), i < 2 ? 12288 : i < 5 ? 8192 : i == 5 ? 16 : 16384);
        asm volatile("fence.mbarrier_init.release.cluster;" ::: "memory");
      }
      LOOPSTAMP(3, tid == 288, 14);
      __syncwarp();
      cluster_wait();
      cluster_arrive();
#pragma unroll
      for (int i = 0; i < 3; i++) asm volatile("st.shared.v4.b32 [%0], {%1,%1,%1,%1};" :: "r"(sb + SM_F1 + i * 1536 + (tid - 288) * 16), "r"(0xffffffffu) : "memory");
      fence_async_smem();
      asm volatile("bar.arrive 5, 128;" ::: "memory");
      if ((sb & 0xffffff) != SM_BASE) __trap();
      cluster_wait();
    }
    auto chunk = [&](int ks) { const int c = ks >= 9, t = ks - 2 - 7 * c; return ks < 2 ? 2 * j + ks : 2 * (t + (t >= j)) + c; };
    auto load_wo = [&](uint32_t dst, int c, uint32_t bytes, uint32_t fb) {
      mbar_expect(fb, bytes);
      tma2d_mc(dst + rho * 8192, &P.wo, 128 * j + 64 * rho, c * 64, fb);
    };
    uint8_t* const xch = g_xch[r * 8 + j];
    if (warp == 8) {
      int ck = 0, cw = 0, cph = 1;
      const CUtensorMap* kvmap = rho ? &P.v : &P.k;
#pragma unroll 1
      for (int it = 4 - XPF; it < 32 || (ck < 20 && it < kSpinLimit); ++it) {
        if (it >= 4 && it < 32) {
          mbar_wait(bar(B_QKV_EMPTY + (it & 3)), ((it >> 2) - 1) & 1);
          if (elect()) load_stage(it);
          LOOPSTAMP(3, lane == 0 && it < 12, 15 + it);
        }
        if (it < 32 - XPF) {
          if (((it + XPF) & 7) == rp && elect()) {
            l2_prefetch2d(&P.wk, 1024 + 128 * j + 64 * rho, 32 * (it + XPF));
            l2_prefetch3d(&P.w, 0, 32 * (it + XPF), 32 * rho + 2 * j);
          }
          if (((it + XPF) & 7) == j && elect()) l2_prefetch2d(&P.x, 32 * (it + XPF), 128 * r);
        }
        const int n = it - HSTART;
        if (n >= 0 && n < 8) {
          if (elect()) bulk_load(sb + SM_SIG + n * 8192 + 4096, P.ssm_k + (size_t)(cta * 8 + n) * 2048, 4096, bar(B_H_FULL + (n >= 3) + (n >= 6)));
        } else if (n >= 8 && n < 19) {
          if (n == 8) bar_sync(5, 128);
          if (elect()) bulk_store(xch + (n - 8) * 4096, sb + SM_F1, 4096);
        } else if (it >= PF0 && it < PF0 + 4) {
          if (elect()) l2_prefetch(it < PF0 + 2 ? P.wo_ptr + cta * 8192 + (it - PF0) * 4096 : P.q_ptr + (512 + (it - PF0 - 2) * 1024 + cta * 4) * 1024, 8192);
        }
        if (ck < 16 && it >= PSTART && __all_sync(0xffffffffu, mbar_test(bar(B_PREP_EMPTY + cw), cph))) {
          if (elect()) {
            mbar_expect(bar(B_PREP_FULL + cw), 8704);
            tma3d_mc(sb + SM_STG + cw * 8704 + rho * 4608, kvmap, cl * 16, ck * 8 - 1 + rho, 0, bar(B_PREP_FULL + cw));
          }
          ++ck;
          if (++cw == 3) { cw = 0; cph ^= 1; }
        } else if (ck >= 16 && ck < 20 && __all_sync(0xffffffffu, mbar_test(bar(B_STG_FREE), 0))) {
          if (elect()) tma2d(sb + SM_Q + (ck - 16) * 4096, &P.q, cl * 16, rho * 1024 + (ck - 16) * 128, bar(B_Q_FULL));
          ++ck;
        }
      }
      if (elect()) {
        bulk_commit();
        bulk_wait_read();
        mbar_expect(bar(B_SIG_READY), 10240);
        bulk_load(sb + SM_TW, g_tables, 10240, bar(B_SIG_READY));
        TSTAMP(true, 9);
        flag_add(&g_ready);
        TSTAMP(true, 10);
        prefetch_map(&P.wo); prefetch_map(&P.outa);
        const unsigned epoch = ld_relaxed(&g_epoch[cta]) + 1;
        g_epoch[cta] = epoch;
        flag_wait(&g_ready, kCtas * epoch);
        mbar_arrive(bar(B_ZEROED));
        TSTAMP(true, 11);
      }
      __syncwarp();
      mbar_wait(bar(B_QKV_DONE), 0);
#pragma unroll 1
      for (int ks = 0; ks < 4; ++ks) if (elect()) load_wo(sb + (4 + ks) * SLOT, chunk(ks), ks < 2 ? SLOT : 2 * SLOT, bar(B_OUT_FULL + ks));
    } else {
      const int at = tid - 288, aw = warp - 9, ch0 = cta * 8;
      {
        const uint32_t stg = sb + SM_STG + aw * 8704, pf = bar(B_PREP_FULL + aw), pe = bar(B_PREP_EMPTY + aw);
        const uint4 wv = __ldg(reinterpret_cast<const uint4*>(P.shift_k + (ch0 + 2 * (lane & 3)) * 4));
        const float skip = __bfloat162float(P.ssm_d[ch0 + (lane & 7)]);
        const uint32_t w0 = __byte_perm(wv.x, wv.z, 0x5410), w1 = __byte_perm(wv.x, wv.z, 0x7632);
        const uint32_t w2 = __byte_perm(wv.y, wv.w, 0x5410), w3 = __byte_perm(wv.y, wv.w, 0x7632);
        auto swz32 = [](uint32_t a) { return a ^ ((a >> 3) & 16); };
        const uint32_t kl = (lane >> 3) * 288 + (lane & 7) * 32 + rho * 16;
        const uint32_t ka = stg + swz32(kl + 32), kh = stg + swz32(kl + 12 * 288), va = stg + 4608 + swz32(lane * 32 + rho * 16);
        const uint32_t ua = sb + SM_SIG + (lane & 7) * 8192 + (((lane >> 3) ^ (lane & 7)) << 4);
        if (at == 0) prefetch_map(&P.q);
        uint32_t eh = 0;
#pragma unroll 1
        for (int ck = aw, rd = 0; rd < 9; ck += 3, ++rd) {
          if (rd == 6) {
            bar_sync(4, 96);
            if (at == 64) mbar_arrive(bar(B_STG_FREE));
          }
          const int c = rd < 6 ? ck : ck - 18;
          if (c < 8) {
            uint32_t x[32], dst = sb + SM_SIG + c * 8192;
            if (rd < 6) {
              mbar_wait(bar(B_H_FULL + rd), 0);
#pragma unroll
              for (int i = 0; i < 8; i++) ldsm4(x + 4 * i, dst + 4096 + i * 512 + lane * 16);
              const float d = __shfl_sync(0xffffffffu, skip, c);
              if (lane == 0) x[0] = pack_bf16(bf_lo(x[0]) + d, bf_hi(x[0]));
              dst += 4096 + (lane >> 1) * 128 + ((((lane & 1) * 4) ^ ((lane >> 1) & 7)) << 4);
            } else {
#pragma unroll
              for (int i = 0; i < 8; i++) ldsm4_t(x + 4 * i, dst + i * 512 + ((lane ^ c) << 4));
              dst += (lane >> 4) * 1024 + (lane & 7) * 128 + ((((lane >> 1) & 4) ^ (lane & 7)) << 4);
            }
            const uint32_t e = normalize(x, dst);
            if (rd < 6) {
              eh |= e << (8 * rd);
            } else {
              const int f = min(max((int)(e + (eh & 255)) - 125, 0), 254);
              eh >>= 8;
              if (lane == 0) asm volatile("st.shared.b16 [%0], %1;" :: "r"(sb + SM_SC + rho * 16 + 2 * c), "h"((uint16_t)(f << 7)) : "memory");
            }
          }
          if (ck < 16) {
            mbar_wait(pf, rd & 1);
            uint32_t k[20], v[16];
            ldsm4(k, kh);
#pragma unroll
            for (int m = 0; m < 4; m++) { ldsm4(k + 4 + 4 * m, (ka ^ ((m & 1) << 4)) + m * 1152); ldsm4(v + 4 * m, va + m * 1024); }
            arrive_both(pe + ((k[3] | k[4] | k[8] | k[12] | k[16] | v[0] | v[4] | v[8] | v[12]) & P.zero), lane, ck < 13);
#pragma unroll
            for (int m = 0; m < 4; m++) {
              uint32_t u[4];
#pragma unroll
              for (int n = 0; n < 4; n++) {
                const uint32_t* kk = k + 4 + 4 * m + n;
                u[n] = bmul2(bfma2(kk[0], w0, bfma2(kk[-1], w1, bfma2(kk[-2], w2, bmul2(kk[-3], w3)))), v[4 * m + n]);
              }
              stsm4_t((ua ^ (m << 6)) + ck * 256, u[0], u[1], u[2], u[3]);
            }
          }
        }
        fence_async_smem();
        __syncwarp();
        if (lane == 0) mbar_arrive(bar(B_SIG_READY));
        bar_sync(4, 96);
        if (at == 32) {
          const uint4 s = lds128(sb + SM_SC + rho * 16);
          asm volatile("st.async.weak.shared::cluster.mbarrier::complete_tx::bytes.v4.b32 [%0], {%1,%2,%3,%4}, [%5];"
                       :: "r"(peer_addr(sb + SM_SC + rho * 16, rho ^ 1)), "r"(s.x), "r"(s.y), "r"(s.z), "r"(s.w), "r"(peer_addr(bar(B_RDY0), rho ^ 1)) : "memory");
        }
        TSTAMP(at == 0, 20);
      }
    }
    __syncwarp();
    {
      const int a4 = warp - 8;
      const uint8_t* part = xch + 2 * SLOT + (lane >> 3) * 4 * KV_SLICE + (a4 * 8 + (lane & 7)) * 16;
      const uint8_t* zpart = xch + 2 * SLOT + (lane & 15) * KV_SLICE + 512 + (a4 * 2 + (lane >> 4)) * 4;
      uint8_t* red = xch + 2 * SLOT + 16 * KV_SLICE + (a4 * 8 + (lane & 7)) * 16 + (lane >> 3) * 4;
      uint8_t* zred = xch + 2 * SLOT + 16 * KV_SLICE + 512 + (a4 * 2 + (lane >> 4)) * 4;
      const uint8_t* all = g_xch[a4 * 32 + j] + 2 * SLOT + 16 * KV_SLICE + lane * 16;
      const uint8_t* zall = all + 512 + (lane & 28) - lane * 16;
      keep(part); keep(zpart); keep(red); keep(zred); keep(all); keep(zall);
      uint32_t v[20];
      int n = 0;
      mbar_wait(bar(B_KVP), 0);
      delay(PD1);
      auto load1 = [&](uint32_t* d) {
#pragma unroll
        for (int i = 0; i < 4; i++) ld_relaxed4(d + 4 * i, part + i * KV_SLICE);
        d[16] = ld_relaxed(zpart);
      };
      do load1(v); while (!all_arrived<17>(v) && ++n < kSpinLimit);
      TSTAMP(tid == 288, 21);
      float lo[4], hi[4], z = __uint_as_float(v[16]);
#pragma unroll
      for (int b = 0; b < 4; b++) {
        lo[b] = (bf_lo(v[b]) + bf_lo(v[4 + b])) + (bf_lo(v[8 + b]) + bf_lo(v[12 + b]));
        hi[b] = (bf_hi(v[b]) + bf_hi(v[4 + b])) + (bf_hi(v[8 + b]) + bf_hi(v[12 + b]));
      }
      const bool u16 = lane & 16, u8 = lane & 8;
#pragma unroll
      for (int b = 0; b < 2; b++) {
        lo[b] = (u16 ? lo[b + 2] : lo[b]) + __shfl_xor_sync(0xffffffffu, u16 ? lo[b] : lo[b + 2], 16);
        hi[b] = (u16 ? hi[b + 2] : hi[b]) + __shfl_xor_sync(0xffffffffu, u16 ? hi[b] : hi[b + 2], 16);
      }
      const float l = (u8 ? lo[1] : lo[0]) + __shfl_xor_sync(0xffffffffu, u8 ? lo[0] : lo[1], 8);
      const float h = (u8 ? hi[1] : hi[0]) + __shfl_xor_sync(0xffffffffu, u8 ? hi[0] : hi[1], 8);
      st_relaxed(red, pack_bf16(l, h));
#pragma unroll
      for (int o = 8; o; o >>= 1) z += __shfl_xor_sync(0xffffffffu, z, o);
      if ((lane & 15) == 0) st_relaxed(zred, pack_bf16(z, z));
      TSTAMP(tid == 288, 22);
      n = 0;
      delay(PD2);
      auto load2 = [&](uint32_t* d) {
#pragma unroll
        for (int i = 0; i < 4; i++) {
          ld_relaxed4(d + 4 * i, all + i * 8 * XCH_BYTES);
          d[16 + i] = ld_relaxed(zall + i * 8 * XCH_BYTES);
        }
      };
      do load2(v); while (!all_arrived<20>(v) && ++n < kSpinLimit);
#pragma unroll
      for (int i = 0; i < 4; i++) {
        const uint32_t dst = sb + SM_KV + (a4 * 4 + i) * 640;
        stsm4(dst + lane * 16, v[4 * i], v[4 * i + 1], v[4 * i + 2], v[4 * i + 3]);
        asm volatile("st.shared.b32 [%0], %1;" :: "r"(dst + 512 + lane * 4), "r"(v[16 + i]) : "memory");
      }
      fence_async_smem();
      __syncwarp();
      if (lane == 0) mbar_arrive(bar(B_KV_READY + (a4 >> 1)));
      TSTAMP(tid == 288, 23);
    }
    if (warp != 10) cluster_arrive();
    if (warp == 8) {
      int s = 4;
      uint32_t ph = 1;
#pragma unroll 1
      for (int ks = 4; ks < 16; ++ks) {
        uint32_t fb = bar(B_OUT_FULL + s), dst = sb + ((B_SLOTS >> (4 * s)) & 15) * SLOT;
        int c = chunk(ks);
        keep(fb); keep(dst); keep(c);
        mbar_wait(bar(ks == 4 ? B_RDY1 : B_OUT_EMPTY + s), ks == 4 ? 0 : ph);
        if (elect()) load_wo(dst, c, 2 * SLOT, fb);
        if (++s == 5) { s = 0; ph ^= 1; }
      }
    } else {
      auto wait_chunks = [&](unsigned mask) {
        unsigned ready;
        int n = 0;
        do {
          ready = __ballot_sync(0xffffffffu, ld_relaxed(g_xch[r * 8 + ((lane >> 1) & 7)] + XCH_FLAG) + 1 > (lane & 1));
        } while ((~ready & mask) && ++n < kSpinLimit);
        return ready;
      };
      if (warp == 9) {
        if (elect()) {
#pragma unroll 1
          for (int c = 0; c < 2; c++) {
            mbar_wait(bar(B_O_WRITTEN + c), 0);
            TSTAMP(c == 0, 19);
            fence_async_smem();
            bulk_store(xch + c * SLOT, sb + c * SLOT, SLOT);
            bulk_commit();
            bulk_wait_read();
            mbar_arrive(bar(B_OT_FREE + c));
            delay(FDELAY);
            st_relaxed(xch + XCH_FLAG, c);
            if (!c) delay(C1DELAY);
            TSTAMP(c == 1, 25);
          }
        }
        __syncwarp();
        wait_chunks(0xaaaa);
        if (lane == 0) mbar_arrive(bar(B_FLAGS1));
      } else if (warp == 10) {
        mbar_wait(bar(B_Q_FULL), 0);
        mbar_wait(bar(B_RDY0), 0);
        mbar_wait(bar(B_QKV_DONE), 0);
#pragma unroll 1
        for (int n = 0; n < 4; n++) {
          const int w = n & 1;
          mbar_wait(bar(B_SEG + n), 0);
          fence_async_smem();
          if (elect()) bulk_to_peer(sb + (n < 2 ? SM_Y0 : SM_SIG) + w * 8192 + 4096, sb + SM_YT + w * 4096, 4096, bar(B_YIN + (n >> 1)), rho ^ 1);
          if (w) {
            mbar_wait(bar(B_YIN + (n >> 1)), 0);
            if (lane == 0) asm volatile("mbarrier.arrive.shared::cluster.b64 _, [%0];" :: "r"(n < 2 ? peer_addr(bar(B_RDY1), rho ^ 1) : bar(B_Y_READY)) : "memory");
          }
        }
        __syncwarp();
        cluster_arrive();
        TSTAMP(lane == 0, 26);
      } else {
        mbar_wait(bar(B_OUT_FULL), 0);
        mbar_wait(bar(B_OUT_FULL + 1), 0);
        mbar_wait(bar(B_O_WRITTEN), 0);
        delay(PD3);
        unsigned ready = 0;
        int s = 2;
        uint32_t ph = 1;
#pragma unroll 1
        for (int ks = 2; ks < 16; ++ks) {
          const int c = chunk(ks);
          uint32_t fb = bar(B_OUT_FULL + s), dst = sb + ((A_SLOTS >> (4 * s)) & 15) * SLOT;
          uint8_t* src = g_xch[r * 8 + (c >> 1)] + (c & 1) * SLOT;
          keep(fb); keep(dst); keep(src);
          if (ks < 5 || ks == 9) {
            const unsigned need = ks < 4 ? 1u << c : 0x5555u;
            if (ks == 9) mbar_wait(bar(B_FLAGS1), 0);
            else if (~ready & need) ready = wait_chunks(need);
          }
          constexpr uint64_t kFirst = (B_O_WRITTEN + 1) | B_OT_FREE << 8 | B_SLOT_FREE << 16 | (B_OT_FREE + 1) << 24 | (uint64_t)B_CONV_DONE << 32;
          mbar_wait(bar(ks < 7 ? (int)(kFirst >> (8 * ks - 16)) & 255 : B_OUT_EMPTY + s), ks < 7 ? ks == 4 : ph);
          if (ks == 4 || ks == 6) fence_async_smem();
          if (elect()) bulk_load(dst, src, SLOT, fb);
          TSTAMP(ks == 2 && lane == 0, 18); LOOPSTAMP(2, lane == 0, 11 + ks);
          if (++s == 5) { s = 0; ph ^= 1; }
        }
      }
    }
    if (warp == 9 || warp == 10) {
      const int yc = (lane & 1) + ((lane >> 2) & 2) + (lane & 2) * 2, ysrc = (lane >> 2) & 1;
      const uint32_t ya = sb + (yc & 4 ? SM_SIG : SM_Y0) + (yc & 1) * 8192 + (yc & 2) * 1024 + (ysrc ^ rho) * 4096 +
                          (lane >> 4) * 128 + ((yc ^ (2 * ysrc)) << 4);
      uint32_t s0, s1;
      mbar_wait(bar(B_Y_READY), 0);
      asm volatile("ld.shared.v2.b32 {%0,%1}, [%2];" : "=r"(s0), "=r"(s1) : "r"(sb + SM_SC + (lane & 3) * 8) : "memory");
#pragma unroll 1
      for (int n = warp - 9; n < 8; n += 2) {
        __nv_bfloat16* op = P.out_ptr + (rho * 1024 + n * 128 + (lane >> 2)) * 2048 + 1024 + cl * 16 + (lane & 3) * 4;
        const uint32_t qa = sb + SM_Q + (n & 3) * 4096 + lane * 8;
        asm volatile("cp.async.wait_group 1;" ::: "memory");
        __syncwarp();
#pragma unroll 1
        for (int u0 = 0; u0 < 8; u0 += 2) {
          uint32_t y[2][4], q[2][4];
#pragma unroll
          for (int u = 0; u < 2; u++) {
            ldsm4_t(y[u], (ya ^ ((u0 + u) << 4)) + n * 256);
#pragma unroll
            for (int m = 0; m < 2; m++)
              asm volatile("ld.shared.v2.b32 {%0,%1}, [%2];" : "=r"(q[u][2 * m]), "=r"(q[u][2 * m + 1]) : "r"(qa + (u0 + u) * 512 + m * 256) : "memory");
          }
#pragma unroll
          for (int u = 0; u < 2; u++)
#pragma unroll
            for (int m = 0; m < 2; m++)
              asm volatile("st.global.v2.b32 [%0], {%1,%2};" :: "l"(op + (u * 16 + m * 8) * 2048),
                           "r"(bmul2(q[u][2 * m], bmul2(y[u][2 * m], s0))), "r"(bmul2(q[u][2 * m + 1], bmul2(y[u][2 * m + 1], s1))) : "memory");
          op += 32 * 2048;
        }
        __syncwarp();
        if (n < 4) {
          const __nv_bfloat16* qp = P.q_ptr + (rho * 1024 + n * 128 + 512 + (lane >> 1)) * 1024 + cl * 16 + (lane & 1) * 8;
#pragma unroll
          for (int i = 0; i < 8; i++)
            asm volatile("cp.async.cg.shared.global [%0], [%1], 16;" :: "r"(qa + lane * 8 + i * 512), "l"(qp + i * 16384) : "memory");
        }
        asm volatile("cp.async.commit_group;" ::: "memory");
      }
      TSTAMP(tid == 320, 24);
    }
    __syncwarp();
    cluster_wait();
  }
}

typedef CUresult (*EncodeFn)(CUtensorMap*, CUtensorMapDataType, cuuint32_t, void*, const cuuint64_t*, const cuuint64_t*,
                             const cuuint32_t*, const cuuint32_t*, CUtensorMapInterleave, CUtensorMapSwizzle,
                             CUtensorMapL2promotion, CUtensorMapFloatOOBfill);

void encode(EncodeFn fn, CUtensorMap* m, const void* p, int rank, const cuuint64_t* dims, const cuuint64_t* strides,
            const cuuint32_t* box, CUtensorMapSwizzle sw) {
  const cuuint32_t es[3] = {1, 1, 1};
  fn(m, CU_TENSOR_MAP_DATA_TYPE_BFLOAT16, rank, const_cast<void*>(p), dims, strides, box, es, CU_TENSOR_MAP_INTERLEAVE_NONE, sw,
     CU_TENSOR_MAP_L2_PROMOTION_NONE, CU_TENSOR_MAP_FLOAT_OOB_FILL_NONE);
}
void encode2d(EncodeFn fn, CUtensorMap* m, const void* p, uint64_t cols, uint64_t rows, uint32_t bc, uint32_t br, CUtensorMapSwizzle sw) {
  const cuuint64_t dims[2] = {cols, rows}, strides[1] = {cols * 2};
  const cuuint32_t box[2] = {bc, br};
  encode(fn, m, p, 2, dims, strides, box, sw);
}
void encode3d(EncodeFn fn, CUtensorMap* m, const void* p, uint32_t nblk) {
  const cuuint64_t dims[3] = {1024, 128, 16}, strides[2] = {2048 * 16, 2048};
  const cuuint32_t box[3] = {16, nblk, 16};
  encode(fn, m, p, 3, dims, strides, box, CU_TENSOR_MAP_SWIZZLE_32B);
}

}

extern "C" void kernel_launch(void* const* d_in, const int* in_sizes, int n_in, void* d_out, int out_size) {
  static EncodeFn fn = nullptr;
  if (!fn) {
    cudaDriverEntryPointQueryResult qr;
    cudaGetDriverEntryPoint("cuTensorMapEncodeTiled", (void**)&fn, cudaEnableDefault, &qr);
    cudaFuncSetAttribute(fused_kernel, cudaFuncAttributeMaxDynamicSharedMemorySize, SM_TOTAL);
  }
  Params P;
  encode2d(fn, &P.x, d_in[0], 1024, 2048, 32, 128, CU_TENSOR_MAP_SWIZZLE_64B);
  {
    const cuuint64_t dims[3] = {64, 1024, 48}, strides[2] = {6144, 128};
    const cuuint32_t box[3] = {64, 32, 2};
    encode(fn, &P.w, d_in[1], 3, dims, strides, box, CU_TENSOR_MAP_SWIZZLE_128B);
  }
  encode2d(fn, &P.wk, d_in[1], 3072, 1024, 64, 32, CU_TENSOR_MAP_SWIZZLE_128B);
  encode2d(fn, &P.wo, d_in[2], 1024, 1024, 64, 64, CU_TENSOR_MAP_SWIZZLE_128B);
  encode2d(fn, &P.outa, d_out, 2048, 2048, 64, 16, CU_TENSOR_MAP_SWIZZLE_128B);
  encode3d(fn, &P.k, d_in[4], 9);
  encode3d(fn, &P.v, d_in[5], 8);
  encode2d(fn, &P.q, d_in[3], 1024, 2048, 16, 128, CU_TENSOR_MAP_SWIZZLE_NONE);
  P.shift_k = (const __nv_bfloat16*)d_in[6];
  P.ssm_k = (const __nv_bfloat16*)d_in[7];
  P.ssm_d = (const __nv_bfloat16*)d_in[8];
  P.zero = 0;
  P.q_ptr = (const __nv_bfloat16*)d_in[3];
  P.out_ptr = (__nv_bfloat16*)d_out;
  P.wo_ptr = (const __nv_bfloat16*)d_in[2];
  fused_kernel<<<kCtas, kThreads, SM_TOTAL>>>(P);
}
```

```cpp
#include <cuda.h>
#include <cuda_runtime.h>
#include <cuda_bf16.h>
#include <stdint.h>

#define DEVI __device__ __forceinline__

namespace {

DEVI void mma_nt(float* d, uint64_t da, uint64_t db) {
  asm volatile("wgmma.mma_async.sync.aligned.m64n128k16.f32.bf16.bf16 {%0, %1, %2, %3, %4, %5, %6, %7, %8, %9, %10, %11, %12, %13, %14, %15, %16, %17, %18, %19, %20, %21, %22, %23, %24, %25, %26, %27, %28, %29, %30, %31, %32, %33, %34, %35, %36, %37, %38, %39, %40, %41, %42, %43, %44, %45, %46, %47, %48, %49, %50, %51, %52, %53, %54, %55, %56, %57, %58, %59, %60, %61, %62, %63}, %64, %65, 1, 1, 1, 0, 1;\n"
    : "+f"(d[0]), "+f"(d[1]), "+f"(d[2]), "+f"(d[3]), "+f"(d[4]), "+f"(d[5]), "+f"(d[6]), "+f"(d[7]), "+f"(d[8]), "+f"(d[9]), "+f"(d[10]), "+f"(d[11]), "+f"(d[12]), "+f"(d[13]), "+f"(d[14]), "+f"(d[15]), "+f"(d[16]), "+f"(d[17]), "+f"(d[18]), "+f"(d[19]), "+f"(d[20]), "+f"(d[21]), "+f"(d[22]), "+f"(d[23]), "+f"(d[24]), "+f"(d[25]), "+f"(d[26]), "+f"(d[27]), "+f"(d[28]), "+f"(d[29]), "+f"(d[30]), "+f"(d[31]), "+f"(d[32]), "+f"(d[33]), "+f"(d[34]), "+f"(d[35]), "+f"(d[36]), "+f"(d[37]), "+f"(d[38]), "+f"(d[39]), "+f"(d[40]), "+f"(d[41]), "+f"(d[42]), "+f"(d[43]), "+f"(d[44]), "+f"(d[45]), "+f"(d[46]), "+f"(d[47]), "+f"(d[48]), "+f"(d[49]), "+f"(d[50]), "+f"(d[51]), "+f"(d[52]), "+f"(d[53]), "+f"(d[54]), "+f"(d[55]), "+f"(d[56]), "+f"(d[57]), "+f"(d[58]), "+f"(d[59]), "+f"(d[60]), "+f"(d[61]), "+f"(d[62]), "+f"(d[63])
    : "l"(da), "l"(db));
}
DEVI void mma_tn(float* d, uint64_t da, uint64_t db) {
  asm volatile("wgmma.mma_async.sync.aligned.m64n128k16.f32.bf16.bf16 {%0, %1, %2, %3, %4, %5, %6, %7, %8, %9, %10, %11, %12, %13, %14, %15, %16, %17, %18, %19, %20, %21, %22, %23, %24, %25, %26, %27, %28, %29, %30, %31, %32, %33, %34, %35, %36, %37, %38, %39, %40, %41, %42, %43, %44, %45, %46, %47, %48, %49, %50, %51, %52, %53, %54, %55, %56, %57, %58, %59, %60, %61, %62, %63}, %64, %65, 1, 1, 1, 1, 0;\n"
    : "+f"(d[0]), "+f"(d[1]), "+f"(d[2]), "+f"(d[3]), "+f"(d[4]), "+f"(d[5]), "+f"(d[6]), "+f"(d[7]), "+f"(d[8]), "+f"(d[9]), "+f"(d[10]), "+f"(d[11]), "+f"(d[12]), "+f"(d[13]), "+f"(d[14]), "+f"(d[15]), "+f"(d[16]), "+f"(d[17]), "+f"(d[18]), "+f"(d[19]), "+f"(d[20]), "+f"(d[21]), "+f"(d[22]), "+f"(d[23]), "+f"(d[24]), "+f"(d[25]), "+f"(d[26]), "+f"(d[27]), "+f"(d[28]), "+f"(d[29]), "+f"(d[30]), "+f"(d[31]), "+f"(d[32]), "+f"(d[33]), "+f"(d[34]), "+f"(d[35]), "+f"(d[36]), "+f"(d[37]), "+f"(d[38]), "+f"(d[39]), "+f"(d[40]), "+f"(d[41]), "+f"(d[42]), "+f"(d[43]), "+f"(d[44]), "+f"(d[45]), "+f"(d[46]), "+f"(d[47]), "+f"(d[48]), "+f"(d[49]), "+f"(d[50]), "+f"(d[51]), "+f"(d[52]), "+f"(d[53]), "+f"(d[54]), "+f"(d[55]), "+f"(d[56]), "+f"(d[57]), "+f"(d[58]), "+f"(d[59]), "+f"(d[60]), "+f"(d[61]), "+f"(d[62]), "+f"(d[63])
    : "l"(da), "l"(db));
}
DEVI void mma_own_init(float* d, uint32_t a0, uint32_t a1, uint32_t a2, uint32_t a3, uint64_t db) {
  asm volatile("wgmma.mma_async.sync.aligned.m64n128k16.f32.bf16.bf16 {%0, %1, %2, %3, %4, %5, %6, %7, %8, %9, %10, %11, %12, %13, %14, %15, %16, %17, %18, %19, %20, %21, %22, %23, %24, %25, %26, %27, %28, %29, %30, %31, %32, %33, %34, %35, %36, %37, %38, %39, %40, %41, %42, %43, %44, %45, %46, %47, %48, %49, %50, %51, %52, %53, %54, %55, %56, %57, %58, %59, %60, %61, %62, %63}, {%64,%65,%66,%67}, %68, 0, 1, 1, 1;\n"
    : "=f"(d[0]), "=f"(d[1]), "=f"(d[2]), "=f"(d[3]), "=f"(d[4]), "=f"(d[5]), "=f"(d[6]), "=f"(d[7]), "=f"(d[8]), "=f"(d[9]), "=f"(d[10]), "=f"(d[11]), "=f"(d[12]), "=f"(d[13]), "=f"(d[14]), "=f"(d[15]), "=f"(d[16]), "=f"(d[17]), "=f"(d[18]), "=f"(d[19]), "=f"(d[20]), "=f"(d[21]), "=f"(d[22]), "=f"(d[23]), "=f"(d[24]), "=f"(d[25]), "=f"(d[26]), "=f"(d[27]), "=f"(d[28]), "=f"(d[29]), "=f"(d[30]), "=f"(d[31]), "=f"(d[32]), "=f"(d[33]), "=f"(d[34]), "=f"(d[35]), "=f"(d[36]), "=f"(d[37]), "=f"(d[38]), "=f"(d[39]), "=f"(d[40]), "=f"(d[41]), "=f"(d[42]), "=f"(d[43]), "=f"(d[44]), "=f"(d[45]), "=f"(d[46]), "=f"(d[47]), "=f"(d[48]), "=f"(d[49]), "=f"(d[50]), "=f"(d[51]), "=f"(d[52]), "=f"(d[53]), "=f"(d[54]), "=f"(d[55]), "=f"(d[56]), "=f"(d[57]), "=f"(d[58]), "=f"(d[59]), "=f"(d[60]), "=f"(d[61]), "=f"(d[62]), "=f"(d[63])
    : "r"(a0), "r"(a1), "r"(a2), "r"(a3), "l"(db));
}
DEVI void mma_own_acc(float* d, uint32_t a0, uint32_t a1, uint32_t a2, uint32_t a3, uint64_t db) {
  asm volatile("wgmma.mma_async.sync.aligned.m64n128k16.f32.bf16.bf16 {%0, %1, %2, %3, %4, %5, %6, %7, %8, %9, %10, %11, %12, %13, %14, %15, %16, %17, %18, %19, %20, %21, %22, %23, %24, %25, %26, %27, %28, %29, %30, %31, %32, %33, %34, %35, %36, %37, %38, %39, %40, %41, %42, %43, %44, %45, %46, %47, %48, %49, %50, %51, %52, %53, %54, %55, %56, %57, %58, %59, %60, %61, %62, %63}, {%64,%65,%66,%67}, %68, 1, 1, 1, 1;\n"
    : "+f"(d[0]), "+f"(d[1]), "+f"(d[2]), "+f"(d[3]), "+f"(d[4]), "+f"(d[5]), "+f"(d[6]), "+f"(d[7]), "+f"(d[8]), "+f"(d[9]), "+f"(d[10]), "+f"(d[11]), "+f"(d[12]), "+f"(d[13]), "+f"(d[14]), "+f"(d[15]), "+f"(d[16]), "+f"(d[17]), "+f"(d[18]), "+f"(d[19]), "+f"(d[20]), "+f"(d[21]), "+f"(d[22]), "+f"(d[23]), "+f"(d[24]), "+f"(d[25]), "+f"(d[26]), "+f"(d[27]), "+f"(d[28]), "+f"(d[29]), "+f"(d[30]), "+f"(d[31]), "+f"(d[32]), "+f"(d[33]), "+f"(d[34]), "+f"(d[35]), "+f"(d[36]), "+f"(d[37]), "+f"(d[38]), "+f"(d[39]), "+f"(d[40]), "+f"(d[41]), "+f"(d[42]), "+f"(d[43]), "+f"(d[44]), "+f"(d[45]), "+f"(d[46]), "+f"(d[47]), "+f"(d[48]), "+f"(d[49]), "+f"(d[50]), "+f"(d[51]), "+f"(d[52]), "+f"(d[53]), "+f"(d[54]), "+f"(d[55]), "+f"(d[56]), "+f"(d[57]), "+f"(d[58]), "+f"(d[59]), "+f"(d[60]), "+f"(d[61]), "+f"(d[62]), "+f"(d[63])
    : "r"(a0), "r"(a1), "r"(a2), "r"(a3), "l"(db));
}
DEVI void mma_nt256(float* d, uint64_t da, uint64_t db) {
  asm volatile("wgmma.mma_async.sync.aligned.m64n256k16.f32.bf16.bf16 {%0, %1, %2, %3, %4, %5, %6, %7, %8, %9, %10, %11, %12, %13, %14, %15, %16, %17, %18, %19, %20, %21, %22, %23, %24, %25, %26, %27, %28, %29, %30, %31, %32, %33, %34, %35, %36, %37, %38, %39, %40, %41, %42, %43, %44, %45, %46, %47, %48, %49, %50, %51, %52, %53, %54, %55, %56, %57, %58, %59, %60, %61, %62, %63, %64, %65, %66, %67, %68, %69, %70, %71, %72, %73, %74, %75, %76, %77, %78, %79, %80, %81, %82, %83, %84, %85, %86, %87, %88, %89, %90, %91, %92, %93, %94, %95, %96, %97, %98, %99, %100, %101, %102, %103, %104, %105, %106, %107, %108, %109, %110, %111, %112, %113, %114, %115, %116, %117, %118, %119, %120, %121, %122, %123, %124, %125, %126, %127}, %128, %129, 1, 1, 1, 0, 1;\n"
    : "+f"(d[0]), "+f"(d[1]), "+f"(d[2]), "+f"(d[3]), "+f"(d[4]), "+f"(d[5]), "+f"(d[6]), "+f"(d[7]), "+f"(d[8]), "+f"(d[9]), "+f"(d[10]), "+f"(d[11]), "+f"(d[12]), "+f"(d[13]), "+f"(d[14]), "+f"(d[15]), "+f"(d[16]), "+f"(d[17]), "+f"(d[18]), "+f"(d[19]), "+f"(d[20]), "+f"(d[21]), "+f"(d[22]), "+f"(d[23]), "+f"(d[24]), "+f"(d[25]), "+f"(d[26]), "+f"(d[27]), "+f"(d[28]), "+f"(d[29]), "+f"(d[30]), "+f"(d[31]), "+f"(d[32]), "+f"(d[33]), "+f"(d[34]), "+f"(d[35]), "+f"(d[36]), "+f"(d[37]), "+f"(d[38]), "+f"(d[39]), "+f"(d[40]), "+f"(d[41]), "+f"(d[42]), "+f"(d[43]), "+f"(d[44]), "+f"(d[45]), "+f"(d[46]), "+f"(d[47]), "+f"(d[48]), "+f"(d[49]), "+f"(d[50]), "+f"(d[51]), "+f"(d[52]), "+f"(d[53]), "+f"(d[54]), "+f"(d[55]), "+f"(d[56]), "+f"(d[57]), "+f"(d[58]), "+f"(d[59]), "+f"(d[60]), "+f"(d[61]), "+f"(d[62]), "+f"(d[63]), "+f"(d[64]), "+f"(d[65]), "+f"(d[66]), "+f"(d[67]), "+f"(d[68]), "+f"(d[69]), "+f"(d[70]), "+f"(d[71]), "+f"(d[72]), "+f"(d[73]), "+f"(d[74]), "+f"(d[75]), "+f"(d[76]), "+f"(d[77]), "+f"(d[78]), "+f"(d[79]), "+f"(d[80]), "+f"(d[81]), "+f"(d[82]), "+f"(d[83]), "+f"(d[84]), "+f"(d[85]), "+f"(d[86]), "+f"(d[87]), "+f"(d[88]), "+f"(d[89]), "+f"(d[90]), "+f"(d[91]), "+f"(d[92]), "+f"(d[93]), "+f"(d[94]), "+f"(d[95]), "+f"(d[96]), "+f"(d[97]), "+f"(d[98]), "+f"(d[99]), "+f"(d[100]), "+f"(d[101]), "+f"(d[102]), "+f"(d[103]), "+f"(d[104]), "+f"(d[105]), "+f"(d[106]), "+f"(d[107]), "+f"(d[108]), "+f"(d[109]), "+f"(d[110]), "+f"(d[111]), "+f"(d[112]), "+f"(d[113]), "+f"(d[114]), "+f"(d[115]), "+f"(d[116]), "+f"(d[117]), "+f"(d[118]), "+f"(d[119]), "+f"(d[120]), "+f"(d[121]), "+f"(d[122]), "+f"(d[123]), "+f"(d[124]), "+f"(d[125]), "+f"(d[126]), "+f"(d[127])
    : "l"(da), "l"(db));
}
DEVI void mma_kv_init(float* d, uint32_t a0, uint32_t a1, uint32_t a2, uint32_t a3, uint64_t db) {
  asm volatile("wgmma.mma_async.sync.aligned.m64n72k16.f32.bf16.bf16 {%0, %1, %2, %3, %4, %5, %6, %7, %8, %9, %10, %11, %12, %13, %14, %15, %16, %17, %18, %19, %20, %21, %22, %23, %24, %25, %26, %27, %28, %29, %30, %31, %32, %33, %34, %35}, {%36,%37,%38,%39}, %40, 0, 1, 1, 1;\n"
    : "=f"(d[0]), "=f"(d[1]), "=f"(d[2]), "=f"(d[3]), "=f"(d[4]), "=f"(d[5]), "=f"(d[6]), "=f"(d[7]), "=f"(d[8]), "=f"(d[9]), "=f"(d[10]), "=f"(d[11]), "=f"(d[12]), "=f"(d[13]), "=f"(d[14]), "=f"(d[15]), "=f"(d[16]), "=f"(d[17]), "=f"(d[18]), "=f"(d[19]), "=f"(d[20]), "=f"(d[21]), "=f"(d[22]), "=f"(d[23]), "=f"(d[24]), "=f"(d[25]), "=f"(d[26]), "=f"(d[27]), "=f"(d[28]), "=f"(d[29]), "=f"(d[30]), "=f"(d[31]), "=f"(d[32]), "=f"(d[33]), "=f"(d[34]), "=f"(d[35])
    : "r"(a0), "r"(a1), "r"(a2), "r"(a3), "l"(db));
}
DEVI void mma_kv_acc(float* d, uint32_t a0, uint32_t a1, uint32_t a2, uint32_t a3, uint64_t db) {
  asm volatile("wgmma.mma_async.sync.aligned.m64n72k16.f32.bf16.bf16 {%0, %1, %2, %3, %4, %5, %6, %7, %8, %9, %10, %11, %12, %13, %14, %15, %16, %17, %18, %19, %20, %21, %22, %23, %24, %25, %26, %27, %28, %29, %30, %31, %32, %33, %34, %35}, {%36,%37,%38,%39}, %40, 1, 1, 1, 1;\n"
    : "+f"(d[0]), "+f"(d[1]), "+f"(d[2]), "+f"(d[3]), "+f"(d[4]), "+f"(d[5]), "+f"(d[6]), "+f"(d[7]), "+f"(d[8]), "+f"(d[9]), "+f"(d[10]), "+f"(d[11]), "+f"(d[12]), "+f"(d[13]), "+f"(d[14]), "+f"(d[15]), "+f"(d[16]), "+f"(d[17]), "+f"(d[18]), "+f"(d[19]), "+f"(d[20]), "+f"(d[21]), "+f"(d[22]), "+f"(d[23]), "+f"(d[24]), "+f"(d[25]), "+f"(d[26]), "+f"(d[27]), "+f"(d[28]), "+f"(d[29]), "+f"(d[30]), "+f"(d[31]), "+f"(d[32]), "+f"(d[33]), "+f"(d[34]), "+f"(d[35])
    : "r"(a0), "r"(a1), "r"(a2), "r"(a3), "l"(db));
}
DEVI void mma_o_init(float* d, uint32_t a0, uint32_t a1, uint32_t a2, uint32_t a3, uint64_t db) {
  asm volatile("wgmma.mma_async.sync.aligned.m64n40k16.f32.bf16.bf16 {%0, %1, %2, %3, %4, %5, %6, %7, %8, %9, %10, %11, %12, %13, %14, %15, %16, %17, %18, %19}, {%20,%21,%22,%23}, %24, 0, 1, 1, 1;\n"
    : "=f"(d[0]), "=f"(d[1]), "=f"(d[2]), "=f"(d[3]), "=f"(d[4]), "=f"(d[5]), "=f"(d[6]), "=f"(d[7]), "=f"(d[8]), "=f"(d[9]), "=f"(d[10]), "=f"(d[11]), "=f"(d[12]), "=f"(d[13]), "=f"(d[14]), "=f"(d[15]), "=f"(d[16]), "=f"(d[17]), "=f"(d[18]), "=f"(d[19])
    : "r"(a0), "r"(a1), "r"(a2), "r"(a3), "l"(db));
}
DEVI void mma_o_acc(float* d, uint32_t a0, uint32_t a1, uint32_t a2, uint32_t a3, uint64_t db) {
  asm volatile("wgmma.mma_async.sync.aligned.m64n40k16.f32.bf16.bf16 {%0, %1, %2, %3, %4, %5, %6, %7, %8, %9, %10, %11, %12, %13, %14, %15, %16, %17, %18, %19}, {%20,%21,%22,%23}, %24, 1, 1, 1, 1;\n"
    : "+f"(d[0]), "+f"(d[1]), "+f"(d[2]), "+f"(d[3]), "+f"(d[4]), "+f"(d[5]), "+f"(d[6]), "+f"(d[7]), "+f"(d[8]), "+f"(d[9]), "+f"(d[10]), "+f"(d[11]), "+f"(d[12]), "+f"(d[13]), "+f"(d[14]), "+f"(d[15]), "+f"(d[16]), "+f"(d[17]), "+f"(d[18]), "+f"(d[19])
    : "r"(a0), "r"(a1), "r"(a2), "r"(a3), "l"(db));
}
DEVI void fft1_init(uint32_t* d, uint32_t a0, uint32_t a1, uint32_t a2, uint32_t a3, uint64_t db) {
  asm volatile("wgmma.mma_async.sync.aligned.m64n128k16.f16.f16.f16 {%0, %1, %2, %3, %4, %5, %6, %7, %8, %9, %10, %11, %12, %13, %14, %15, %16, %17, %18, %19, %20, %21, %22, %23, %24, %25, %26, %27, %28, %29, %30, %31}, {%32,%33,%34,%35}, %36, 0, 1, 1, 1;\n"
    : "=r"(d[0]), "=r"(d[1]), "=r"(d[2]), "=r"(d[3]), "=r"(d[4]), "=r"(d[5]), "=r"(d[6]), "=r"(d[7]), "=r"(d[8]), "=r"(d[9]), "=r"(d[10]), "=r"(d[11]), "=r"(d[12]), "=r"(d[13]), "=r"(d[14]), "=r"(d[15]), "=r"(d[16]), "=r"(d[17]), "=r"(d[18]), "=r"(d[19]), "=r"(d[20]), "=r"(d[21]), "=r"(d[22]), "=r"(d[23]), "=r"(d[24]), "=r"(d[25]), "=r"(d[26]), "=r"(d[27]), "=r"(d[28]), "=r"(d[29]), "=r"(d[30]), "=r"(d[31])
    : "r"(a0), "r"(a1), "r"(a2), "r"(a3), "l"(db));
}
DEVI void fft1_acc(uint32_t* d, uint32_t a0, uint32_t a1, uint32_t a2, uint32_t a3, uint64_t db) {
  asm volatile("wgmma.mma_async.sync.aligned.m64n128k16.f16.f16.f16 {%0, %1, %2, %3, %4, %5, %6, %7, %8, %9, %10, %11, %12, %13, %14, %15, %16, %17, %18, %19, %20, %21, %22, %23, %24, %25, %26, %27, %28, %29, %30, %31}, {%32,%33,%34,%35}, %36, 1, 1, 1, 1;\n"
    : "+r"(d[0]), "+r"(d[1]), "+r"(d[2]), "+r"(d[3]), "+r"(d[4]), "+r"(d[5]), "+r"(d[6]), "+r"(d[7]), "+r"(d[8]), "+r"(d[9]), "+r"(d[10]), "+r"(d[11]), "+r"(d[12]), "+r"(d[13]), "+r"(d[14]), "+r"(d[15]), "+r"(d[16]), "+r"(d[17]), "+r"(d[18]), "+r"(d[19]), "+r"(d[20]), "+r"(d[21]), "+r"(d[22]), "+r"(d[23]), "+r"(d[24]), "+r"(d[25]), "+r"(d[26]), "+r"(d[27]), "+r"(d[28]), "+r"(d[29]), "+r"(d[30]), "+r"(d[31])
    : "r"(a0), "r"(a1), "r"(a2), "r"(a3), "l"(db));
}
DEVI void fft2_init(uint32_t* d, uint32_t a0, uint32_t a1, uint32_t a2, uint32_t a3, uint64_t db) {
  asm volatile("wgmma.mma_async.sync.aligned.m64n32k16.f16.f16.f16 {%0, %1, %2, %3, %4, %5, %6, %7}, {%8,%9,%10,%11}, %12, 0, 1, 1, 0;\n"
    : "=r"(d[0]), "=r"(d[1]), "=r"(d[2]), "=r"(d[3]), "=r"(d[4]), "=r"(d[5]), "=r"(d[6]), "=r"(d[7])
    : "r"(a0), "r"(a1), "r"(a2), "r"(a3), "l"(db));
}
DEVI void fft2_acc(uint32_t* d, uint32_t a0, uint32_t a1, uint32_t a2, uint32_t a3, uint64_t db) {
  asm volatile("wgmma.mma_async.sync.aligned.m64n32k16.f16.f16.f16 {%0, %1, %2, %3, %4, %5, %6, %7}, {%8,%9,%10,%11}, %12, 1, 1, 1, 0;\n"
    : "+r"(d[0]), "+r"(d[1]), "+r"(d[2]), "+r"(d[3]), "+r"(d[4]), "+r"(d[5]), "+r"(d[6]), "+r"(d[7])
    : "r"(a0), "r"(a1), "r"(a2), "r"(a3), "l"(db));
}
DEVI void fft3_init(float* d, uint32_t a0, uint32_t a1, uint32_t a2, uint32_t a3, uint64_t db) {
  asm volatile("wgmma.mma_async.sync.aligned.m64n32k16.f32.f16.f16 {%0, %1, %2, %3, %4, %5, %6, %7, %8, %9, %10, %11, %12, %13, %14, %15}, {%16,%17,%18,%19}, %20, 0, 1, 1, 0;\n"
    : "=f"(d[0]), "=f"(d[1]), "=f"(d[2]), "=f"(d[3]), "=f"(d[4]), "=f"(d[5]), "=f"(d[6]), "=f"(d[7]), "=f"(d[8]), "=f"(d[9]), "=f"(d[10]), "=f"(d[11]), "=f"(d[12]), "=f"(d[13]), "=f"(d[14]), "=f"(d[15])
    : "r"(a0), "r"(a1), "r"(a2), "r"(a3), "l"(db));
}
DEVI void fft3_acc(float* d, uint32_t a0, uint32_t a1, uint32_t a2, uint32_t a3, uint64_t db) {
  asm volatile("wgmma.mma_async.sync.aligned.m64n32k16.f32.f16.f16 {%0, %1, %2, %3, %4, %5, %6, %7, %8, %9, %10, %11, %12, %13, %14, %15}, {%16,%17,%18,%19}, %20, 1, 1, 1, 0;\n"
    : "+f"(d[0]), "+f"(d[1]), "+f"(d[2]), "+f"(d[3]), "+f"(d[4]), "+f"(d[5]), "+f"(d[6]), "+f"(d[7]), "+f"(d[8]), "+f"(d[9]), "+f"(d[10]), "+f"(d[11]), "+f"(d[12]), "+f"(d[13]), "+f"(d[14]), "+f"(d[15])
    : "r"(a0), "r"(a1), "r"(a2), "r"(a3), "l"(db));
}

__device__ __align__(128) const uint32_t g_tables[2560] = {
0xa11ba1e4,0xa51ba5e4,0x18b61248,0x1cb61648,0x9f12a052,0xa311a452,0x1d7f1bdb,0x217f1fdb,0x9bdb9d7f,0x9fdba17f,0x20521f12,0x24522311,
0x924898b6,0x96489cb6,0x21e4211b,0x25e4251b,0xaa63ab5f,0xae5faf59,0x21e41bdb,0x25e41fdb,0xa86ba967,0xac6aad65,0x26e024e9,0x2ade28e8,
0xa4e9a6e0,0xa8e8aade,0x2967286b,0x2d652c6a,0x9bdba1e4,0x9fdba5e4,0x2b5f2a63,0x2f592e5f,0xadc2aea7,0xb1b6b294,0x254d1f12,0x294d2311,
0xabf6acde,0xafefb0d7,0x2a31286b,0x2e2d2c6a,0xa86baa31,0xac6aae2d,0x2cde2bf6,0x30d72fef,0x9f12a54d,0xa311a94d,0x2ea72dc2,0x329431b6,
0xb02cb0d2,0xb41ab4b7,0x27a9211b,0x2ba7251b,0xadc2af0c,0xb1b6b2f7,0x2c792a63,0x30742e5f,0xaa63ac79,0xae5fb074,0x2f0c2dc2,0x32f731b6,
0xa11ba7a9,0xa51baba7,0x30d2302c,0x34b7341a,0xb17ab257,0xb552b61a,0x290222ad,0x2d0026ad,0xaf8cb09f,0xb371b487,0x2ddc2c2e,0x31cf3029,
0xac2eaddc,0xb029b1cf,0x309f2f8c,0x34873371,0xa2ada902,0xa6adad00,0x3257317a,0x361a3552,0xb2cdb3e3,0xb682b76f,0x2a312420,0x2e2d281f,
0xb0acb1bb,0xb493b58d,0x2f3f2d2a,0x33283122,0xad2aaf3f,0xb122b328,0x31bb30ac,0x358d3493,0xa420aa31,0xa81fae2d,0x33e332cd,0x376f3682,
0xb413b4bc,0xb7a6b85a,0x2b5f24e9,0x2f5928e8,0xb194b2da,0xb56ab68d,0x30522e28,0x343e3219,0xae28b052,0xb219b43e,0x32da3194,0x368d356a,
0xa4e9ab5f,0xa8e8af59,0x34bc3413,0x385a37a6,0xb4c3b58c,0xb85fb8f3,0x2c4725b2,0x304229b1,0xb27eb3fd,0xb63cb785,0x31062f26,0x34e7330f,
0xaf26b106,0xb30fb4e7,0x33fd327e,0x3785363c,0xa5b2ac47,0xa9b1b042,0x358c34c3,0x38f3385f,0xb577b662,0xb8e5b982,0x2cde267b,0x30d72a7a,
0xb36bb493,0xb70ab83a,0x31bb3012,0x358d3402,0xb012b1bb,0xb402b58d,0x3493336b,0x383a370a,0xa67bacde,0xaa7ab0d7,0x36623577,0x398238e5,
0xb630b741,0xb962ba04,0x2d762744,0x316c2b43,0xb42eb52a,0xb7d2b8ad,0x32713092,0x3631347b,0xb092b271,0xb47bb631,0x352a342e,0x38ad37d2,
0xa744ad76,0xab43b16c,0x37413630,0x3a043962,0xb6eeb815,0xb9d6ba7a,0x2e0e2807,0x32012c06,0xb4a7b5c4,0xb84ab91b,0x33293113,0x36d234f3,
0xb113b329,0xb4f3b6d2,0x35c434a7,0x391b384a,0xa807ae0e,0xac06b201,0x381536ee,0x3a7a39d6,0xb7b4b88e,0xba41bae1,0x2ea7286b,0x32942c6a,
0xb523b662,0xb8a8b982,0x33e33194,0x376f356a,0xb194b3e3,0xb56ab76f,0x36623523,0x398238a8,0xa86baea7,0xac6ab294,0x388e37b4,0x3ae13a41,
0xb841b90f,0xbaa2bb3a,0x2f3f28d0,0x33282cce,0xb5a1b705,0xb902b9e3,0x344f3216,0x380535df,0xb216b44f,0xb5dfb805,0x370535a1,0x39e33902,
0xa8d0af3f,0xacceb328,0x390f3841,0x3b3a3aa2,0xb8acb997,0xbaf7bb83,0x2fd82935,0x33ba2d33,0xb621b7ac,0xb958ba3d,0x34ae3298,0x38503654,
0xb298b4ae,0xb654b850,0x37ac3621,0x3a3d3958,0xa935afd8,0xad33b3ba,0x399738ac,0x3b833af7,0xb91cba28,0xbb42bbbc,0x30392999,0x34262d97,
0xb6a4b82d,0xb9aaba90,0x350e331c,0x389936c6,0xb31cb50e,0xb6c6b899,0x382d36a4,0x3a9039aa,0xa999b039,0xad97b426,0x3a28391c,0x3bbc3b42,
0xb992bac3,0xbb81bbe3,0x308529fe,0x346f2dfb,0xb72ab886,0xb9f8badb,0x357033a0,0x38e03737,0xb3a0b570,0xb737b8e0,0x3886372a,0x3adb39f8,
0xa9feb085,0xadfbb46f,0x3ac33992,0x3be33b81,0x39cf3b16,0x3b9c3bf1,0xb0acaa31,0xb493ae2d,0x376f38b4,0x3a1d3afe,0xb5a1b3e3,0xb902b76f,
0x33e335a1,0x376f3902,0xb8b4b76f,0xbafeba1d,0x2a3130ac,0x2e2d3493,0xbb16b9cf,0xbbf1bb9c,0x39563a74,0x3b633bd2,0xb05fa9cc,0xb44badc9,
0x36e73859,0x39d23ab6,0xb53fb35e,0xb8bcb6ff,0x335e353f,0x36ff38bc,0xb859b6e7,0xbab6b9d2,0x29cc305f,0x2dc9344b,0xba74b956,0xbbd2bb63,
0x38e339de,0x3b1e3ba1,0xb012a967,0xb402ad65,0x36623801,0x39823a67,0xb4deb2da,0xb874b68d,0x32da34de,0x368d3874,0xb801b662,0xba67b982,
0x29673012,0x2d653402,0xb9deb8e3,0xbba1bb1e,0x38763952,0x3ace3b60,0xaf8ca902,0xb371ad00,0x35e13758,0x392e3a11,0xb47eb257,0xb82ab61a,
0x3257347e,0x361a382a,0xb758b5e1,0xba11b92e,0x29022f8c,0x2d003371,0xb952b876,0xbb60bace,0x380d38ce,0x3a733b10,0xaef3a89e,0xb2deac9c,
0x356236b3,0x38d639b3,0xb420b1d5,0xb7bdb5a5,0x31d53420,0x35a537bd,0xb6b3b562,0xb9b3b8d6,0x289e2ef3,0x2c9c32de,0xb8ceb80d,0xbb10ba73,
0x37503851,0x3a0d3ab0,0xae5aa839,0xb24bac38,0x34e53613,0x387a394f,0xb386b153,0xb721b52f,0x31533386,0x352f3721,0xb613b4e5,0xb94fb87a,
0x28392e5a,0x2c38324b,0xb851b750,0xbab0ba0d,0x368e37b4,0x399d3a41,0xadc2a7a9,0xb1b6aba7,0x346a3577,0x381a38e5,0xb2cdb0d2,0xb682b4b7,
0x30d232cd,0x34b73682,0xb577b46a,0xb8e5b81a,0x27a92dc2,0x2ba731b6,0xb7b4b68e,0xba41b99d,0x35d236d1,0x392439c5,0xad2aa6e0,0xb122aade,
0x33e334de,0x376f3874,0xb216b052,0xb5dfb43e,0x30523216,0x343e35df,0xb4deb3e3,0xb874b76f,0x26e02d2a,0x2ade3122,0xb6d1b5d2,0xb9c5b924,
0x351c35f6,0x38a3393c,0xac93a617,0xb08daa16,0x32f43448,0x36a437fe,0xb160afa5,0xb53ab389,0x2fa53160,0x3389353a,0xb448b2f4,0xb7feb6a4,
0x26172c93,0x2a16308d,0xb5f6b51c,0xb93cb8a3,0x346a3523,0x381a38a8,0xabf6a54d,0xafefa94d,0x3209336b,0x35d4370a,0xb0acaea7,0xb493b294,
0x2ea730ac,0x32943493,0xb36bb209,0xb70ab5d4,0x254d2bf6,0x294d2fef,0xb523b46a,0xb8a8b81a,0x33783456,0x3715380a,0xaac8a484,0xaec3a884,
0x3120324a,0x34ff360e,0xaff2ada9,0xb3d3b19e,0x2da92ff2,0x319e33d3,0xb24ab120,0xb60eb4ff,0x24842ac8,0x28842ec3,0xb456b378,0xb80ab715,
0x3223331c,0x35eb36c6,0xa999a376,0xad97a776,0x3039312d,0x3426350b,0xae8dacac,0xb27cb0a6,0x2cac2e8d,0x30a6327c,0xb12db039,0xb50bb426,
0x23762999,0x27762d97,0xb31cb223,0xb6c6b5eb,0x30d23194,0x34b7356a,0xa86ba1e4,0xac6aa5e4,0x2ea73012,0x32943402,0xad2aab5f,0xb122af59,
0x2b5f2d2a,0x2f593122,0xb012aea7,0xb402b294,0x21e4286b,0x25e42c6a,0xb194b0d2,0xb56ab4b7,0x2f0c3012,0x32f73402,0xa67ba052,0xaa7aa452,
0x2cde2df5,0x30d731e8,0xab91a967,0xaf8bad65,0x29672b91,0x2d652f8b,0xadf5acde,0xb1e8b0d7,0x2052267b,0x24522a7a,0xb012af0c,0xb402b2f7,
0x2c792d2a,0x30743122,0xa4209d7f,0xa81fa17f,0x2a312b91,0x2e2d2f8b,0xa8d0a6e0,0xacceaade,0x26e028d0,0x2ade2cce,0xab91aa31,0xaf8bae2d,
0x1d7f2420,0x217f281f,0xad2aac79,0xb122b074,0x27a9286b,0x2ba72c6a,0x9f1298b6,0xa3119cb6,0x254d267b,0x294d2a7a,0xa420a1e4,0xa81fa5e4,
0x21e42420,0x25e4281f,0xa67ba54d,0xaa7aa94d,0x18b61f12,0x1cb62311,0xa86ba7a9,0xac6aaba7,0x3f803f80,0x3f803f80,0x3f803f80,0x3f803f80,
0x3f803f80,0x3f803f80,0x3f803f80,0x3f803f80,0x3f803f80,0x3f803f80,0x3f803f80,0x3f803f80,0x3f803f80,0x3f803f80,0x3f803f80,0x3f803f80,
0x3f803f80,0x3f803f80,0x3f803f80,0x3f803f80,0x3f803f80,0x3f803f80,0x3f803f80,0x3f803f80,0x3f803f80,0x3f803f80,0x3f803f80,0x3f803f80,
0x3f803f80,0x3f803f80,0x3f803f80,0x3f803f80,0x3f803f80,0x3f803f80,0x3f803f80,0x3f803f80,0x3f803f80,0x3f803f80,0x3f803f80,0x3f803f80,
0x3f803f80,0x3f803f80,0x3f803f80,0x3f803f80,0x3f803f80,0x3f803f80,0x3f803f80,0x3f803f80,0x3f803f80,0x3f803f80,0x3f803f80,0x3f803f80,
0x3f803f80,0x3f803f80,0x3f803f80,0x3f803f80,0x3f803f80,0x3f803f80,0x3f803f80,0x3f803f80,0x3f803f80,0x3f803f80,0x3f803f80,0x3f803f80,
0x3f803f80,0x3f803f80,0x3f803f80,0x3f803f80,0x3f803f80,0x3f803f80,0x3f803f80,0x3f803f80,0x3f803f80,0x3f803f80,0x3f803f80,0x3f803f80,
0x3f803f80,0x3f803f80,0x3f803f80,0x3f803f80,0x3f803f80,0x3f803f80,0x3f803f80,0x3f803f80,0x3f803f80,0x3f803f80,0x3f803f80,0x3f803f80,
0x3f803f80,0x3f803f80,0x3f803f80,0x3f803f80,0x3f803f80,0x3f803f80,0x3f803f80,0x3f803f80,0x3f803f80,0x3f803f80,0x3f803f80,0x3f803f80,
0x3f803f80,0x3f803f80,0x3f803f80,0x3f803f80,0x3f803f80,0x3f803f80,0x3f803f80,0x3f803f80,0x3f803f80,0x3f803f80,0x3f803f80,0x3f803f80,
0x3f803f80,0x3f803f80,0x3f803f80,0x3f803f80,0x3f803f80,0x3f803f80,0x3f803f80,0x3f803f80,0x3f803f80,0x3f803f80,0x3f803f80,0x3f803f80,
0x3f803f80,0x3f803f80,0x3f803f80,0x3f803f80,0x3f803f80,0x3f803f80,0x3f803f80,0x3f803f80,0x3f803f80,0x3f803f80,0x3f803f80,0x3f803f80,
0x3f803f80,0x3f803f80,0x3f803f80,0x3f803f80,0x3f803f80,0x3f803f80,0x3f803f80,0x3f803f80,0x3f803f80,0x3f803f80,0x3f803f80,0x3f803f80,
0x3f803f80,0x3f803f80,0x3f803f80,0x3f803f80,0x3f803f80,0x3f803f80,0x3f803f80,0x3f803f80,0x3f803f80,0x3f803f80,0x3f803f80,0x3f803f80,
0x3f803f80,0x3f803f80,0x3f803f80,0x3f803f80,0x3f803f80,0x3f803f80,0x3f803f80,0x3f803f80,0x3f803f80,0x3f803f80,0x3f803f80,0x3f803f80,
0x3f803f80,0x3f803f80,0x3f803f80,0x3f803f80,0x3f803f80,0x3f803f80,0x3f803f80,0x3f803f80,0x3f803f80,0x3f803f80,0x3f803f80,0x3f803f80,
0x3f803f80,0x3f803f80,0x3f803f80,0x3f803f80,0x3f803f80,0x3f803f80,0x3f803f80,0x3f803f80,0x3f803f80,0x3f803f80,0x3f803f80,0x3f803f80,
0x3f803f80,0x3f803f80,0x3f803f80,0x3f803f80,0x3f803f80,0x3f803f80,0x3f803f80,0x3f803f80,0x3f803f80,0x3f803f80,0x3f803f80,0x3f803f80,
0x3f803f80,0x3f803f80,0x3f803f80,0x3f803f80,0x3f803f80,0x3f803f80,0x3f803f80,0x3f803f80,0x3f803f80,0x3f803f80,0x3f803f80,0x3f803f80,
0x3f803f80,0x3f803f80,0x3f803f80,0x3f803f80,0x3f803f80,0x3f803f80,0x3f803f80,0x3f803f80,0x3f803f80,0x3f803f80,0x3f803f80,0x3f803f80,
0x3f803f80,0x3f803f80,0x3f803f80,0x3f803f80,0x3f803f80,0x3f803f80,0x3f803f80,0x3f803f80,0x3f803f80,0x3f803f80,0x3f803f80,0x3f803f80,
0x3f803f80,0x3f803f80,0x3f803f80,0x3f803f80,0x3f803f80,0x3f803f80,0x3f803f80,0x3f803f80,0x3f803f80,0x3f803f80,0x3f803f80,0x3f803f80,
0x3f803f80,0x3f803f80,0x3f803f80,0x3f803f80,0x3f803f80,0x3f803f80,0x3f803f80,0x3f803f80,0x3f803f80,0x3f803f80,0x3f803f80,0x3f803f80,
0x3f803f80,0x3f803f80,0x3f803f80,0x3f803f80,0x3f803f80,0x3f803f80,0x3f803f80,0x3f803f80,0x3f803f80,0x3f803f80,0x3f803f80,0x3f803f80,
0x3f803f80,0x3f803f80,0x3f803f80,0x3f803f80,0x3f803f80,0x3f803f80,0x3f803f80,0x3f803f80,0x3f803f80,0x3f803f80,0x3f803f80,0x3f803f80,
0x3f803f80,0x3f803f80,0x3f803f80,0x3f803f80,0x3f803f80,0x3f803f80,0x3f803f80,0x3f803f80,0x3f803f80,0x3f803f80,0x3f803f80,0x3f803f80,
0x3f803f80,0x3f803f80,0x3f803f80,0x3f803f80,0x3f803f80,0x3f803f80,0x3f803f80,0x3f803f80,0x3f803f80,0x3f803f80,0x3f803f80,0x3f803f80,
0x3f803f80,0x3f803f80,0x3f803f80,0x3f803f80,0x3f803f80,0x3f803f80,0x3f803f80,0x3f803f80,0x3f803f80,0x3f803f80,0x3f803f80,0x3f803f80,
0x3f803f80,0x3f803f80,0x3f803f80,0x3f803f80,0x3f803f80,0x3f803f80,0x3f803f80,0x3f803f80,0x3f803f80,0x3f803f80,0x3f803f80,0x3f803f80,
0x3f803f80,0x3f803f80,0x3f803f80,0x3f803f80,0x3f803f80,0x3f803f80,0x3f803f80,0x3f803f80,0x3f803f80,0x3f803f80,0x3f803f80,0x3f803f80,
0x3f803f80,0x3f803f80,0x3f803f80,0x3f803f80,0x3f803f80,0x3f803f80,0x3f803f80,0x3f803f80,0x3f803f80,0x3f803f80,0x3f803f80,0x3f803f80,
0x3f803f80,0x3f803f80,0x3f803f80,0x3f803f80,0x3f803f80,0x3f803f80,0x3f803f80,0x3f803f80,0x3f803f80,0x3f803f80,0x3f803f80,0x3f803f80,
0x3f803f80,0x3f803f80,0x3f803f80,0x3f803f80,0x3f803f80,0x3f803f80,0x3f803f80,0x3f803f80,0x3f803f80,0x3f803f80,0x3f803f80,0x3f803f80,
0x3f803f80,0x3f803f80,0x3f803f80,0x3f803f80,0x3f803f80,0x3f803f80,0x3f803f80,0x3f803f80,0x3f803f80,0x3f803f80,0x3f803f80,0x3f803f80,
0x3f803f80,0x3f803f80,0x3f803f80,0x3f803f80,0x3f803f80,0x3f803f80,0x3f803f80,0x3f803f80,0x3f803f80,0x3f803f80,0x3f803f80,0x3f803f80,
0x3f803f80,0x3f803f80,0x3f803f80,0x3f803f80,0x3f803f80,0x3f803f80,0x3f803f80,0x3f803f80,0x3f803f80,0x3f803f80,0x3f803f80,0x3f803f80,
0x3f803f80,0x3f803f80,0x3f803f80,0x3f803f80,0x3f803f80,0x3f803f80,0x3f803f80,0x3f803f80,0x3f803f80,0x3f803f80,0x3f803f80,0x3f803f80,
0x3f803f80,0x3f803f80,0x3f803f80,0x3f803f80,0x3f803f80,0x3f803f80,0x3f803f80,0x3f803f80,0x3f803f80,0x3f803f80,0x3f803f80,0x3f803f80,
0x3f803f80,0x3f803f80,0x3f803f80,0x3f803f80,0x3f803f80,0x3f803f80,0x3f803f80,0x3f803f80,0x3f803f80,0x3f803f80,0x3f803f80,0x3f803f80,
0x3f803f80,0x3f803f80,0x3f803f80,0x3f803f80,0x3f803f80,0x3f803f80,0x3f803f80,0x3f803f80,0x3f803f80,0x3f803f80,0x3f803f80,0x3f803f80,
0x3f803f80,0x3f803f80,0x3f803f80,0x3f803f80,0x3f803f80,0x3f803f80,0x3f803f80,0x3f803f80,0x3f803f80,0x3f803f80,0x3f803f80,0x3f803f80,
0x3f803f80,0x3f803f80,0x3f803f80,0x3f803f80,0x3f803f80,0x3f803f80,0x3f803f80,0x3f803f80,0x3f803f80,0x3f803f80,0x3f803f80,0x3f803f80,
0x3f803f80,0x3f803f80,0x3f803f80,0x3f803f80,0x3f803f80,0x3f803f80,0x3f803f80,0x3f803f80,0x3f803f80,0x3f803f80,0x3f803f80,0x3f803f80,
0x3f803f80,0x3f803f80,0x3f803f80,0x3f803f80,0x3bf23bff,0x3ba53bd4,0x3b163b65,0x3a493ab6,0x3b7c3bfb,0x38bc3a60,0x2b43356a,0xb7f3b359,
0x3a933bf1,0x9cb63764,0xba9eb785,0xbb73bbf3,0x39463be2,0xb8cc28e8,0xbb42bbc2,0x3328b70a,0x374e3bcf,0xbbabb648,0xaec3baa9,0x3bfa3994,
0x33403bb7,0xbb85b9fc,0x3a64b0be,0x2c6a3b47,0xa4523b9a,0xb86abbae,0x3b6a3911,0xbbd0ad65,0xb4263b78,0x2adebbe6,0x30f03bfd,0xb5b1bbbc,
0x2f5925e4,0x34b73294,0x376f361a,0x38f3385a,0x35a52c9c,0x3a7338d6,0x3bfd3b87,0x3af13bc9,0x388e2fbd,0x3c003b18,0x387f3b10,0xb5d42f27,
0x3a04316c,0x3a673bfe,0xb6bb33d3,0xbbccbb2f,0x3b1e32f7,0x34933b5c,0xbbf5b86f,0x2d00b9bc,0x3bcb343e,0xb576394f,0xb8d1bbe9,0x3bfb36a4,
0x3c0034ff,0xbaac347b,0x3602ba31,0x32de3bf9,0x3bba35bc,0xbbfdb109,0x3be7aa7a,0xbb7a341a,0x394639cd,0x381538b2,0x358136dd,0x3153341a,
0xbb1eb9c9,0xbbf5bbdd,0xba39bb65,0xb4f3b889,0xb340b93c,0x3966340e,0x3bec3b87,0x37213a7e,0x3c003a4d,0x32193a21,0xbb5eb785,0xb894bbb0,
0xb426389e,0xbb37bb45,0x38b7b3d3,0x397d3bfc,0xbafebac1,0x3b13217f,0xadc93aa9,0xba49bb59,0x3979b7e8,0xb0d73b32,0xb6f4bbe9,0x3af139da,
0x38553b24,0xb9a1ba3d,0x3ab03911,0xbb73b759,0x3a043982,0x3ae13a7a,0x3b833b3a,0x3be33bbc,0x374e3986,0xae9131e8,0xb907b61a,0xbb9cba97,
0xbbcbba0d,0xb9e7bbbd,0x3074b56a,0x3b2a38ad,0x2452b8ee,0x3bda3924,0x363c3b10,0xba90b46f,0x3bba3a89,0xb6e836af,0xba76bbc2,0x39d2ac06,
0xb7c8384a,0xb77abc00,0x3bf8386f,0xb8f33654,0xb9d6baf4,0x3be836ff,0xbb3530be,0x37f3b974,0x3abab737,0xb9af3902,0x3865ba31,0xb5d43b1b,
0x32c62fbd,0x363134cf,0x38653785,0x398b38fd,0xb715b16c,0xbae1b970,0xbbfebbc2,0xba85bb92,0x392e32f7,0x3bf53b6c,0x37a63aa9,0xb7422311,
0xba81b43e,0xb9e7bbfc,0x380fb0be,0x3b963b7f,0x3b7134ff,0x32193b04,0xbc00b911,0x319eb929,0xbbefb5bc,0x36e8b8b2,0x382a3bfd,0xbbffb805,
0x3bf23676,0xbb1331e8,0x376fb9aa,0x2f8b3bde,0xbb7cb72c,0x3be8340e,0xbbfdaa16,0x3bb8b122,0xbbd2bbf1,0xbb60bba1,0xbab0bb10,0xb9c5ba41,
0x3b2c3be2,0x381539df,0xa94d33d3,0xb8a3b52f,0xba19bbcf,0x2e91b5f7,0x3b07386f,0x3b213c00,0x38a83bb7,0xb966aba7,0xbae5bbe9,0x3517b599,
0xb5dfbb9a,0x3bda37b2,0x1fdb3a31,0xbbe0ba1d,0x30293b78,0xbb37ba7a,0x3ad5aa7a,0xa7763aeb,0x2f59bb52,0x377a3bdd,0xbb16b9a6,0x3bf231cf,
0xb5a53b27,0x30d7bbbd,0x2b433bfe,0xb432bbe5,0x3a813a0d,0x3b3f3ae8,0x3bbf3b87,0x3bfb3be5,0xb5dfb8ee,0x3263ad97,0x399d3785,0x3bd03b01,
0xbbefba89,0xb958bb81,0x3389b3d3,0x3b7a394a,0xaf59384a,0xbbf7b9b8,0xb4c3baa9,0x3afb35eb,0x3b7c3af4,0xb825353a,0xb9f8bbe9,0x3a542884,
0x388eb737,0x360e3bf4,0xbbdcb911,0x398bb4db,0xb946bb4f,0x3bc03830,0xbb832a7a,0x38a3b8db,0xbb1e35c8,0x3a35b85f,0xb90739aa,0x3742bab6,
0xb8a8b93c,0xb6c6b80a,0xb402b56a,0xac6ab122,0xbb71ba4d,0xbbd7bbf8,0xb9b3bb10,0xb2deb7bd,0x3029389e,0xb9f4b58d,0xbbc6bbc2,0xb5b1ba00,
0x3bf23ac1,0x2dfb3999,0xbba3b86f,0xb7d2bb6f,0x35a5b7e8,0x3ad83b90,0xb95430be,0xb8e5bbff,0xba93bb24,0x3b682ef5,0xb2013a31,0xb9c5bb9f,
0xba043682,0x33ebbad1,0x35813bfd,0xba85ba5c,0x374e3b76,0xb90cbab3,0x3a3939a6,0xbb21b85a,0xb7c83b52,0x391bba9b,0xba2539aa,0x3afbb889,
0xb9793b27,0x3bc5b80a,0xbb8eaa16,0x38e538ad,0xbaba3af7,0x3b60ad97,0xb27cba2d,0xb98b3bb0,0xbb943ac4,0x3815358d,0x39e3bbea,0xba852c06,
0xbbf93a8c,0xae9139b8,0x3bacb874,0x3742bb59,0xbbe43a50,0xb9663b90,0x340233ba,0x3b96b974,0xbb573a11,0xbbda3bf4,0xb99d3b0d,0xb19e3759,
0xba5839cd,0xbb373ad1,0xbbc63b89,0xbbff3bee,0x3afe3676,0xba29b884,0x391f39a6,0xb7d2ba97,0x39d6372c,0xb3a2bae8,0xb5463bfe,0x3a54ba7e,
0x385537dd,0x3631bbf8,0xbbd63916,0x39c5346f,0x35233845,0x3ae1bb81,0xb96bb0a6,0xb8a33bfc,0x2d333899,0x3bf5b999,0x3487baa5,0xbb213654,
0xb13b38ea,0x39e7b53a,0x3bbfbbc3,0x3517b9da,0xb65f3937,0x32192ef5,0x39b3b790,0x3be0bb1b,0xb8e03982,0xb6e83830,0xb389355e,0xa7763042,
0xbb943682,0x3bebb371,0xbbfe2a7a,0x3bcc3042,0xad33bb76,0xb79b3bd4,0x3b07b9aa,0xbbfa32ad,0x3be4b50b,0xb6c6b8d6,0xb80f3bfe,0x3bfbb835,
0xb65f3bb5,0x3bd7b764,0x9fdbba2d,0xbbd03a41,0xba58330f,0xb9f43bfe,0x382a30a6,0x3b7abb92,0x3a45bbe1,0xadfbb648,0xbb163874,0xbafb3c00,
0x3699afef,0x3ad8b94f,0x3bfdbbc3,0x3a54bb7f,0xbbdf3bfa,0xbb683bae,0xba9e3b0d,0xb98b3a1d,0x35233b4f,0xb08dbbc8,0xa94d3bfd,0x3328bbee,
0xbbf935c8,0x3b0a3294,0xb7a6b9a6,0xad003bd3,0x313bbb98,0xbb3f3a60,0x3ae52a16,0xac6abace,0x3b57b44b,0x3263bb18,0xbc003916,0x32de38fd,
0xb8e03bce,0x3958a8e8,0x3ad5bbea,0xb5b1b52f,0xb8f83185,0xbbf73b5c,0xb76f3aa5,0x37d2a311,0x3b4abbf0,0x3825b9fc,0xab43b3ba,0xb8e53599,
0x31b6acce,0x360eb47b,0x387fb790,0x39c5b929,0x3a9337dd,0xb9a1b924,0x387f3a2d,0xb66bbb01,0xb946b845,0x308d3b45,0x36bbbbea,0xbac73a00,
0x374e3899,0x379bbc00,0xbbf53874,0x393335eb,0xb340b8ea,0xbb3f3b32,0x38d133ba,0x3941bbff,0xa4523937,0x3bd7b902,0x3602bb0d,0xbabd34db,
0x3426b982,0xb9583371,0xbbe73b89,0xb68d3a5c,0xb7c839c9,0x2dfb3294,0x391fb625,0x3bb3bab6,0x3979ba0d,0x3825b8d6,0x3546b6d2,0x3010b359,
0x388ebaf7,0xb9af3a21,0x3a9eb916,0xbb5437bd,0xba043ac4,0x3bebb6af,0xbb42b0a6,0x3840394a,0x3b1eba8c,0xbb0aa17f,0x2ec33aa5,0x3a15bb6f,
0xbbcb3a50,0x36c636ff,0x3a64bbc3,0xba09a884,0x3c00ba11,0x3263ba3d,0xbb6a3790,0xb8503b9f,0xbbba39cd,0xb9f43bc8,0x30f0355e,0x3b4cb8db,
0x3afeb986,0x3bf7bbd4,0x3a25bb63,0x3457b85a,0xb9d6393c,0xbad83a60,0xbb8e3b3d,0xbbef3bc9,0x33403b98,0xa9b1bbed,0xb0743bfe,0x3517bbc9,
0x3c00b44b,0xbaa2b4cf,0x363c3a2d,0x319ebbf3,0x3426bbce,0xbb8b39df,0x3a7630a6,0x2776bb2f,0xbafe3185,0xb4b73b6c,0x3bf8b874,0xaf8bb994,
0xb9793bf0,0x38bc2ba7,0x3b35bbc3,0xb432b6a4,0x3855acce,0x3c00bb04,0x3865bb0d,0xb66bad65,0x3b94bbff,0x38ccba7a,0x294db55e,0xb840341a,
0xad33a5e4,0xb49331e8,0xb7a63625,0xb9333889,0x3bcbb50b,0xbbfe305b,0x3bec2a16,0xbb96b359,0x2452bbb5,0xb87a3ba1,0x3b5eb916,0xbbe02f27,
0xbbba330f,0x35523970,0x38b7bbea,0xbbff370a,0xb7c83be1,0x3ba5b5f7,0x2dc9baa5,0xbbf239bc,0x39d6afef,0x3a73bbfc,0xb6f4b3ba,0xbbb83b47,
0x3ababbfa,0x1cb6b7b2,0xbab03790,0xbb543bf9,0xb52326ad,0xba6738b2,0xbbfe3b89,0xbac73bbc,0xbbf93bff,0xbbab3bdd,0xbb073b63,0xba153a97,
0xb8f83986,0xb77a385f,0xb4c33625,0xaf8b32ad,0xb699393c,0x30d7305b,0x3954b6d2,0x3bb8bace,0xb1b638ee,0x39afb4cf,0x3bdcbba7,0x366bba41,
0x2c38389e,0x3bebb970,0x3581bade,0xbac7352f,0x34e7384a,0x3b0abb6c,0xb907b24b,0xb9333c00,0x383a37e8,0x36c6bbfc,0xbbec38c1,0x39413599,
0x39c03737,0xb263bb04,0xb63c3bf6,0x3abdba1d,0x3aee3682,0xb9f4b8b2,0x38b739f0,0xb68dbaeb,0xba4539c9,0xbb133ab3,0xbba33b63,0xbbf23bd3,
0xbb4a3a0d,0xbbe83bed,0xb9f83b3d,0xb4323835,0xbbdf3a4d,0xb9a13ba1,0x320134ab,0x3b54b8fd,0xbbfc3a89,0xb08d39df,0x3b83b81a,0x3840bb92,
0xbb9e3ac1,0x379b35f7,0x3a39bbd8,0xba15a311,0xbacb3af4,0x3b3faba7,0xb074ba6f,0xba093b7f,0xb9903b24,0x3bd7b7b2,0xbb5eae5f,0x38503929,
0xb7fe3b4f,0x3958ba7a,0xba76395d,0x3b4cb805,0x2c3826ad,0x33ebb109,0x36bbb55e,0x38a3b805,0x3b9ebbff,0x390cba9b,0x2ec3b625,0xb74231cf,
0xb83a2c9c,0xbbfe3ae8,0xb8d13b3d,0x35173122,0xb9903bf1,0x387a2d97,0x3b6abba7,0xb19eb7bd,0x3aeeb16c,0x3552bb81,0xbbe7381a,0x27763a00,
0x3463bbcf,0xbba539b8,0x3a25324b,0x2f8bbb6f,0xbbff343e,0x3a73353a,0xb546ba6f,0xb4323bff,0x32c63b9a,0x9cb6bbf4,0xb27c3bf6,0x366bbb9f,
0xbbfc3bff,0xbbc03be6,0xbb423b89,0xba853aeb,0x34e7a5e4,0x3a35b884,0x3bf5bb63,0x3b21bbde,0x3acbbbfb,0x29b1b80a,0xba6436d2,0xbb963be5,
0xb9c02fbd,0xbaa23bf8,0x360234ab,0x3be0bb01,0xb7fe3be2,0x3b8bb58d,0x30f0bade,0xbbff394a,0x3bb2b2f7,0xb4b7b999,0xb91f3bd8,0x3bf2b5eb,
0x281fbbb7,0xb8bc3b90,0x3b8eb8c1,0xbbb82884,0xbbd234ff,0x3c00aef5,0xbbd6ae5f,0x3b5434db,0xbaba3a4d,0xbb683b18,0xbbd63ba7,0xbc003bf3,
0x3b94ba89,0x3bc0bbfe,0x396bbade,0x3153b70a,0xbbf93ac1,0xb90c3b5c,0x3487324b,0x3b9cb994,0x3be4baf4,0x29b1b94f,0xbbbf38c1,0xb7213b47,
0xbb573b24,0x387a347b,0x39b3bbf6,0xba902d65,0x3a58bb4f,0xbb8b3109,0x338939f0,0x397dbbbc,0xb8f83b76,0x3ba5b884,0xbba39648,0x38f33889,
0x3699bb98,0xb8bc3ae8,0x39f8b9eb,0xbaf138ad,0x3855b8ee,0x360eb764,0x327cb4ab,0x251baf27,0xb523389e,0x33eb28e8,0x39e3b81a,0x3be3bb2f,
0x2d33b84a,0xba353648,0xbbac3bd8,0xb4f339bc,0x313b37e8,0x3bfeb9fc,0x3402ba6f,0xbb2a36a4,0xb65fb737,0xbaa23bae,0x399d2e5f,0x3894bbf9,
0x38e03682,0x3552bbe6,0xbbc6395d,0x39d2341a,0xba45b5c8,0x34b73a9b,0x34c3bc00,0xba493a97,0x3b4a350b,0xba73b80a,0x39543962,0xb7f3ba7e,
0xbbe43bfb,0xbb853bbd,0xbae53b3d,0xba093a7e,0xb65f2fbd,0xbaac3924,0xbc003ba7,0xbabd3bb0,0x3a58bbe2,0xaadeb6af,0xbad5381a,0xbb4c3bfc,
0x3a45b2f7,0x3a29bc00,0xb76fb24b,0xbbb33b59,0xb6993bb7,0x3bc5b6ff,0x2b43ba6f,0xbbef39da,0xbbdf34ff,0x36313902,0x387fbbf6,0xbc003759,
0xac38bb78,0xb8153bc8,0x3b42b95d,0xbbe33042,0x3b9eb676,0xbbf53294,0x3bf51648,0xbb9cb2ad,0xb13b2c9c,0xb576340e,0xb80f36d2,0xb94138ad,
0x3b57bbf1,0x386aba21,0x1fdbb4ab,0xb850346f,0x38e0b16c,0x3bfdbb45,0x382abade,0xb68dac06,0xb8f83bcf,0x391ba17f,0x3b16bbd8,0xb457b654,
0xbb4a343e,0xb3a23b32,0x3bfdb8c1,0xb010b974,0x31b6bb9a,0xbb603a3d,0x3a9e2e5f,0x251bbb1b,0x3bfcb5bc,0xbae1b371,0x36bb39f0,0x3153bbee,
0x34e73b52,0xae91bbd4,0xaec33c00,0x34f3bbd3,0x3bb235c8,0xbbf7b1e8,0x3bf81648,0xbbb331cf,0x3bff350b,0xbad8340e,0x36f4b9eb,0x30103be5,
0x3bd2344b,0xb60e3924,0xb865bbf6,0x3c0037bd,0x3b2c330f,0x33eb3b45,0xbbfeb8c7,0x3153b94a,0x3a193185,0x3a353c00,0xb7a63232,0xbb9cbb6f,
0x38a82fef,0x3bfe3b32,0x380f3adb,0xb7212884,0x35df2cce,0x3aa23902,0x3c003ba9,0x3a903b9f,0x302926ad,0x35523371,0x382a36dd,0x397d38db,
0xb4633b76,0x2dfbbbdd,0x2dc93c00,0xb457bbde,0xa81f3b98,0xb825bbbd,0x3b353962,0xbbefb122,0x32c63bb5,0xbb68ba21,0x3ab0ae2d,0xa51b3b01,
0x37153bce,0xbbc0b6af,0xa94dba6b,0x3be33a00,0x392e3be1,0xb90c217f,0xbb07bbd9,0x34f3b5eb,0x3a813bf0,0xa9b136ff,0xbae5b820,0xbb2abbff,
0x3b713bfa,0x387a3a3d,0x9fdb349f,0xb894b4db,0x3bef3bff,0x3b8b3bc8,0x3ad53b3a,0x39d23a5c,0x3b2cb5bc,0xba673830,0x396bb95d,0xb8403a5c,
0xb92ebb52,0x3bab385f,0xbbac9648,0x3933b85a,0xb8a8372c,0xb576bbed,0x3bbf3962,0xba093359,0x3b713af7,0xb86a34cf,0xb99dbbf6,0x3abd2f27,
0x3029b845,0x3bfd39df,0x33893a6b,0xbb4cb70a,0xbbf2ba8c,0xb91bbb6c,0x34c3b232,0x3bb339bc,0x35a538ea,0xb3a22ba7,0xb9f8b820,0xbbefbb47,
0x3a933a11,0x3b603b04,0x3bdc3ba9,0x3c003bf9,0x37153b78,0xb8ccbad1,0x39e339f0,0xbac7b8db,0x3a19b676,0xb4933ab3,0xb487bc00,0x3a153ab6,
0xba81bb27,0x3b85305b,0xb40239eb,0xb941bbc9,0xb5df37dd,0xbaacbba1,0x39b3ae2d,0x38503bf3,0x3bef3ac4,0x2ade3970,0xbbc6b8c7,0xb68dbb2f,
0xaf59b899,0x3a2935f7,0x3ba33bd9,0x34573994,0xbb7cba50,0xbbc5bbfc,0xb954badb,0xb010b6a4,0x388e3937,0x363137b2,0x3201349f,0xa51b2d65,
0xb1b63bb5,0x9cb6bbf8,0x32013bf6,0xb5d4bbb0,0xac38bbce,0x38cc3b81,0xbb83b8c7,0x3bcc2c06,0x34e73be1,0xbbabb999,0x3a39b232,0x2d003b59,
0xb83abbf0,0x3b85353a,0x30743adb,0xbbfbb974,0x39c03bfa,0xb86a2ef5,0xbb5ebba9,0x32deb759,0xbaeebbff,0xaadeb830,0x3a7636dd,0x3b7a3bee,
0x3bb23bff,0x391b3ab3,0x2dc9361a,0xb7d2b2ad,0xbbffbbfb,0xbbc5bbed,0xbb35bb87,0xba54bace,0xbbdfb44b,0x3c002d97,0xbbdc2e2d,0x3b73b46f,
0x3bfc330f,0xba67358d,0x3581ba6b,0x33283bfc,0xbb9eb185,0x3493b9b8,0x39073bd9,0xbbfab654,0x3acb2fef,0x35763b90,0xbbecb820,0x2c6ab9da,
0xb990acce,0xbaacbbf4,0x363cb49f,0x3bd03b1b,0x37fe26ad,0x3bfd3ad1,0x38b73b3a,0xb5b13042,0xb46325e4,0xba29b85f,0xbbf8bb65,0xbafbbbd3,
0x281fac9c,0x33a2305b,0x36f4356a,0x38e53835,0x383a3b27,0xb966ba60,0x3a643962,0xbb2ab835,0xb99037dd,0x3219bb18,0x36023bf6,0xba90ba41,
0xbaeebac4,0x3b3728e8,0xb0f03a6b,0xb9d2bb92,0x3463b899,0x3b133b5c,0xb91f3232,0xb8f3bc00,0x3bff3a50,0x30d739fc,0xbb8eb820,0xb7f3bb7f,
0x32c63937,0xb9a1b47b,0xbbd6bba9,0xb5d4ba1d,0xbb2cb9cd,0xbbebbbe6,0xb9e3bb3a,0xb328b805,0xb92eb9c9,0xb79bb884,0xb487b61a,0xad00b1cf,
0xbacb372c,0x39e7b8d6,0xb8d139eb,0x3721bace,0xb9c0baf7,0x3bda3764,0xbb6a2e2d,0x3894b8fd,0x37feb845,0x36e83bfe,0xbbe7b8c7,0x397db52f,
0x3bb23a8c,0xb77a3648,0xba25bbd9,0x3a492311,0xa81f38ea,0xbbe8b94f,0xb546badb,0x3af13599,0xbbd2ba11,0xb9afbbae,0x327cb49f,0x3b733929,
0xb715b982,0x308db109,0x396b36dd,0x3bcc3aeb,0x3a193986,0x3b0a3a9b,0x3bac3b65,0x3bfa3bde,0x30003000,0x30003000,0x30003000,0x30003000,
0x2f643000,0x2a1f2da8,0xaa1f0000,0xaf64ada8,0x2da83000,0xada80000,0xada8b000,0x2da88000,0x2a1f3000,0xaf64ada8,0x2f648000,0xaa1f2da8,
0x00003000,0x8000b000,0x00003000,0x8000b000,0xaa1f3000,0x2f64ada8,0xaf640000,0x2a1f2da8,0xada83000,0x2da88000,0x2da8b000,0xada80000,
0xaf643000,0xaa1f2da8,0x2a1f8000,0x2f64ada8,0x30003000,0x30003000,0x30003000,0x30003000,0xaf64b000,0xaa1fada8,0x2a1f8000,0x2f642da8,
0x2da83000,0xada80000,0xada8b000,0x2da88000,0xaa1fb000,0x2f642da8,0xaf640000,0x2a1fada8,0x00003000,0x8000b000,0x00003000,0x8000b000,
0x2a1fb000,0xaf642da8,0x2f648000,0xaa1fada8,0xada83000,0x2da88000,0x2da8b000,0xada80000,0x2f64b000,0x2a1fada8,0xaa1f0000,0xaf642da8,
0x80008000,0x80008000,0x80008000,0x80008000,0xaa1f8000,0xaf64ada8,0xaf64b000,0xaa1fada8,0xada88000,0xada8b000,0x2da88000,0x2da83000,
0xaf648000,0x2a1fada8,0x2a1f3000,0xaf64ada8,0xb0008000,0x30008000,0xb0008000,0x30008000,0xaf648000,0x2a1f2da8,0x2a1fb000,0xaf642da8,
0xada88000,0xada83000,0x2da88000,0x2da8b000,0xaa1f8000,0xaf642da8,0xaf643000,0xaa1f2da8,0x80008000,0x80008000,0x80008000,0x80008000,
0x2a1f8000,0x2f642da8,0x2f643000,0x2a1f2da8,0xada88000,0xada8b000,0x2da88000,0x2da83000,0x2f648000,0xaa1f2da8,0xaa1fb000,0x2f642da8,
0xb0008000,0x30008000,0xb0008000,0x30008000,0x2f648000,0xaa1fada8,0xaa1f3000,0x2f64ada8,0xada88000,0xada83000,0x2da88000,0x2da8b000,
0x2a1f8000,0x2f64ada8,0x2f64b000,0x2a1fada8,0xb0003000,0xb0003000,0xb0003000,0xb0003000,0xaf643000,0xaa1f2da8,0x2a1f0000,0x2f64ada8,
0xada83000,0x2da80000,0x2da8b000,0xada88000,0xaa1f3000,0x2f64ada8,0xaf648000,0x2a1f2da8,0x80003000,0x0000b000,0x80003000,0x0000b000,
0x2a1f3000,0xaf64ada8,0x2f640000,0xaa1f2da8,0x2da83000,0xada88000,0xada8b000,0x2da80000,0x2f643000,0x2a1f2da8,0xaa1f8000,0xaf64ada8,
0xb0003000,0xb0003000,0xb0003000,0xb0003000,0x2f64b000,0x2a1fada8,0xaa1f8000,0xaf642da8,0xada83000,0x2da80000,0x2da8b000,0xada88000,
0x2a1fb000,0xaf642da8,0x2f640000,0xaa1fada8,0x80003000,0x0000b000,0x80003000,0x0000b000,0xaa1fb000,0x2f642da8,0xaf648000,0x2a1fada8,
0x2da83000,0xada88000,0xada8b000,0x2da80000,0xaf64b000,0xaa1fada8,0x2a1f0000,0x2f642da8,0x80008000,0x80008000,0x80008000,0x80008000,
0x2a1f8000,0x2f64ada8,0x2f64b000,0x2a1fada8,0x2da88000,0x2da8b000,0xada88000,0xada83000,0x2f648000,0xaa1fada8,0xaa1f3000,0x2f64ada8,
0x30008000,0xb0008000,0x30008000,0xb0008000,0x2f648000,0xaa1f2da8,0xaa1fb000,0x2f642da8,0x2da88000,0x2da83000,0xada88000,0xada8b000,
0x2a1f8000,0x2f642da8,0x2f643000,0x2a1f2da8,0x80008000,0x80008000,0x80008000,0x80008000,0xaa1f8000,0xaf642da8,0xaf643000,0xaa1f2da8,
0x2da88000,0x2da8b000,0xada88000,0xada83000,0xaf648000,0x2a1f2da8,0x2a1fb000,0xaf642da8,0x30008000,0xb0008000,0x30008000,0xb0008000,
0xaf648000,0x2a1fada8,0x2a1f3000,0xaf64ada8,0x2da88000,0x2da83000,0xada88000,0xada8b000,0xaa1f8000,0xaf64ada8,0xaf64b000,0xaa1fada8,
0x00000000,0x00000000,0x00000000,0x00000000,0x2a1f0000,0x2f642da8,0x2f643000,0x2a1f2da8,0x2da80000,0x2da83000,0xada80000,0xada8b000,
0x2f640000,0xaa1f2da8,0xaa1fb000,0x2f642da8,0x30000000,0xb0000000,0x30000000,0xb0000000,0x2f640000,0xaa1fada8,0xaa1f3000,0x2f64ada8,
0x2da80000,0x2da8b000,0xada80000,0xada83000,0x2a1f0000,0x2f64ada8,0x2f64b000,0x2a1fada8,0x00000000,0x00000000,0x00000000,0x00000000,
0xaa1f0000,0xaf64ada8,0xaf64b000,0xaa1fada8,0x2da80000,0x2da83000,0xada80000,0xada8b000,0xaf640000,0x2a1fada8,0x2a1f3000,0xaf64ada8,
0x30000000,0xb0000000,0x30000000,0xb0000000,0xaf640000,0x2a1f2da8,0x2a1fb000,0xaf642da8,0x2da80000,0x2da8b000,0xada80000,0xada83000,
0xaa1f0000,0xaf642da8,0xaf643000,0xaa1f2da8,0x30003000,0x30003000,0x30003000,0x30003000,0x2f643000,0x2a1f2da8,0xaa1f0000,0xaf64ada8,
0x2da83000,0xada80000,0xada8b000,0x2da88000,0x2a1f3000,0xaf64ada8,0x2f648000,0xaa1f2da8,0x00003000,0x8000b000,0x00003000,0x8000b000,
0xaa1f3000,0x2f64ada8,0xaf640000,0x2a1f2da8,0xada83000,0x2da88000,0x2da8b000,0xada80000,0xaf643000,0xaa1f2da8,0x2a1f8000,0x2f64ada8,
0x30003000,0x30003000,0x30003000,0x30003000,0xaf64b000,0xaa1fada8,0x2a1f8000,0x2f642da8,0x2da83000,0xada80000,0xada8b000,0x2da88000,
0xaa1fb000,0x2f642da8,0xaf640000,0x2a1fada8,0x00003000,0x8000b000,0x00003000,0x8000b000,0x2a1fb000,0xaf642da8,0x2f648000,0xaa1fada8,
0xada83000,0x2da88000,0x2da8b000,0xada80000,0x2f64b000,0x2a1fada8,0xaa1f0000,0xaf642da8,0x00000000,0x00000000,0x00000000,0x00000000,
0xaa1f0000,0xaf642da8,0xaf643000,0xaa1f2da8,0xada80000,0xada83000,0x2da80000,0x2da8b000,0xaf640000,0x2a1f2da8,0x2a1fb000,0xaf642da8,
0xb0000000,0x30000000,0xb0000000,0x30000000,0xaf640000,0x2a1fada8,0x2a1f3000,0xaf64ada8,0xada80000,0xada8b000,0x2da80000,0x2da83000,
0xaa1f0000,0xaf64ada8,0xaf64b000,0xaa1fada8,0x00000000,0x00000000,0x00000000,0x00000000,0x2a1f0000,0x2f64ada8,0x2f64b000,0x2a1fada8,
0xada80000,0xada83000,0x2da80000,0x2da8b000,0x2f640000,0xaa1fada8,0xaa1f3000,0x2f64ada8,0xb0000000,0x30000000,0xb0000000,0x30000000,
0x2f640000,0xaa1f2da8,0xaa1fb000,0x2f642da8,0xada80000,0xada8b000,0x2da80000,0x2da83000,0x2a1f0000,0x2f642da8,0x2f643000,0x2a1f2da8,
0xb0003000,0xb0003000,0xb0003000,0xb0003000,0xaf643000,0xaa1f2da8,0x2a1f0000,0x2f64ada8,0xada83000,0x2da80000,0x2da8b000,0xada88000,
0xaa1f3000,0x2f64ada8,0xaf648000,0x2a1f2da8,0x80003000,0x0000b000,0x80003000,0x0000b000,0x2a1f3000,0xaf64ada8,0x2f640000,0xaa1f2da8,
0x2da83000,0xada88000,0xada8b000,0x2da80000,0x2f643000,0x2a1f2da8,0xaa1f8000,0xaf64ada8,0xb0003000,0xb0003000,0xb0003000,0xb0003000,
0x2f64b000,0x2a1fada8,0xaa1f8000,0xaf642da8,0xada83000,0x2da80000,0x2da8b000,0xada88000,0x2a1fb000,0xaf642da8,0x2f640000,0xaa1fada8,
0x80003000,0x0000b000,0x80003000,0x0000b000,0xaa1fb000,0x2f642da8,0xaf648000,0x2a1fada8,0x2da83000,0xada88000,0xada8b000,0x2da80000,
0xaf64b000,0xaa1fada8,0x2a1f0000,0x2f642da8};

constexpr int kThreads = 384;
constexpr int kCtas = 128;

constexpr uint32_t SM_BASE = 1024;
constexpr uint32_t QKV_STAGE = 32768;
constexpr uint32_t SLOT = 16384;
constexpr uint32_t SM_KV = 2 * SLOT;
constexpr uint32_t SM_SIG = 131072;
constexpr uint32_t SM_STG = 196608;
constexpr uint32_t SM_Q = SM_STG;
constexpr uint32_t SM_Y0 = 3 * SLOT;
constexpr uint32_t SM_YT = SM_STG + 16384;
constexpr uint32_t SM_TW = SM_STG + 24576, SM_ONES = SM_TW + 2048, SM_F1 = SM_ONES + 2048, SM_F2 = SM_F1 + 4096;
constexpr uint32_t SM_BAR = SM_F2 + 2048;
constexpr uint32_t SM_SC = SM_BAR + 640;
constexpr uint32_t SM_TOTAL = 232448;
constexpr uint32_t A_SLOTS = 0xA02B1, B_SLOTS = 0x97654;

enum Bar { B_QKV_EMPTY = 0, B_QKV_DONE = 4,
           B_OUT_EMPTY = 8,
           B_H_FULL = 16, B_YIN = 19, B_RDY0 = 21, B_Q_FULL = 22, B_ZEROED = 23,
           B_OUT_FULL = 24, B_PREP_FULL = 29,
           B_RDY1 = 32, B_STG_FREE = 33, B_OT_FREE = 36, B_Y_READY = 38, B_FLAGS1 = 39,
           B_SEG = 40, B_SIG_READY = 44,
           B_KVP = 48, B_O_WRITTEN = 49, B_SLOT_FREE = 51, B_CONV_DONE = 52,
           B_PREP_EMPTY = 56, B_KV_READY = 59,
           B_QKV_FULL = 64, B_FIRST = 68 };
constexpr uint32_t BAR_LOG2 = 0x13200044;

constexpr int KV_SLICE = 640;
constexpr int XCH_FLAG = 2 * SLOT + 17 * KV_SLICE;
constexpr int XCH_BYTES = 11 * 4096;

struct Params {
  CUtensorMap x, w, wk, wo, outa, k, v, q;
  const __nv_bfloat16* shift_k;
  const __nv_bfloat16* ssm_k;
  const __nv_bfloat16* ssm_d;
  const __nv_bfloat16* q_ptr;
  __nv_bfloat16* out_ptr;
  const __nv_bfloat16* wo_ptr;
  int zero;
};

__device__ __align__(128) uint8_t g_xch[kCtas][XCH_BYTES];
__device__ unsigned g_ready, g_epoch[kCtas];

#define TSTAMP(cond, i) do { } while (0)
#define GSTAMP(cond, i) do { } while (0)
#define LOOPSTAMP(id, cond, i) do { } while (0)

constexpr int kSpinLimit = 1 << 17;

DEVI void mbar_init(uint32_t a, uint32_t c) { asm volatile("mbarrier.init.shared::cta.b64 [%0], %1;" :: "r"(a), "r"(c) : "memory"); }
DEVI void mbar_expect(uint32_t a, uint32_t b) { asm volatile("mbarrier.arrive.expect_tx.shared::cta.b64 _, [%0], %1;" :: "r"(a), "r"(b) : "memory"); }
DEVI void mbar_arrive(uint32_t a) { asm volatile("mbarrier.arrive.shared::cta.b64 _, [%0];" :: "r"(a) : "memory"); }
DEVI void mbar_arrive_if(uint32_t a, bool pred) {
  asm volatile("{\n.reg .pred p;\nsetp.ne.b32 p, %1, 0;\n@p mbarrier.arrive.shared::cta.b64 _, [%0];\n}" :: "r"(a), "r"((int)pred) : "memory");
}
DEVI void mbar_wait(uint32_t a, uint32_t parity) {
  asm volatile("{\n.reg .pred p;\n.reg .u32 n;\nmov.u32 n, 0;\nW_LOOP:\n"
               "mbarrier.try_wait.parity.shared::cta.b64 p, [%0], %1;\nadd.u32 n, n, 1;\n"
               "setp.lt.and.u32 p, n, %2, !p;\n@p bra W_LOOP;\n}"
               :: "r"(a), "r"(parity), "n"(kSpinLimit) : "memory");
}
DEVI bool mbar_test(uint32_t a, uint32_t parity) {
  uint32_t ok;
  asm volatile("{\n.reg .pred p;\nmbarrier.test_wait.parity.shared::cta.b64 p, [%1], %2;\nselp.u32 %0, 1, 0, p;\n}" : "=r"(ok) : "r"(a), "r"(parity) : "memory");
  return ok;
}
DEVI bool elect() {
  uint32_t ok;
  asm volatile("{\n.reg .pred p;\nelect.sync _|p, 0xffffffff;\nselp.u32 %0, 1, 0, p;\n}" : "=r"(ok));
  return ok;
}
DEVI void flag_wait(const unsigned* p, unsigned target) {
  int n = 0; unsigned v;
  do {
    asm volatile("ld.acquire.gpu.global.u32 %0, [%1];" : "=r"(v) : "l"(p) : "memory");
  } while ((int)(v - target) < 0 && ++n < kSpinLimit);
}
DEVI uint32_t clock32() { uint32_t t; asm volatile("mov.u32 %0, %%clock;" : "=r"(t) :: "memory"); return t; }
DEVI void delay(uint32_t cycles) { const uint32_t t = clock32(); while (clock32() - t < cycles) { } }
DEVI void st_relaxed(void* p, uint32_t v) { asm volatile("st.relaxed.gpu.global.b32 [%0], %1;" :: "l"(p), "r"(v) : "memory"); }
DEVI uint32_t ld_relaxed(const void* p) { uint32_t v; asm volatile("ld.relaxed.gpu.global.b32 %0, [%1];" : "=r"(v) : "l"(p) : "memory"); return v; }
DEVI void ld_relaxed4(uint32_t* v, const void* p) {
  asm volatile("ld.relaxed.gpu.global.v4.b32 {%0,%1,%2,%3}, [%4];" : "=r"(v[0]), "=r"(v[1]), "=r"(v[2]), "=r"(v[3]) : "l"(p) : "memory");
}
template <int N> DEVI uint32_t umax(const uint32_t* v) {
  if constexpr (N == 1) return v[0];
  else if constexpr (N == 2) return max(v[0], v[1]);
  else if constexpr (N <= 6) return __vimax3_u32(v[0], v[1], umax<N - 2>(v + 2));
  else return __vimax3_u32(umax<N / 3 | 1>(v), umax<N / 3 | 1>(v + (N / 3 | 1)), umax<N - 2 * (N / 3 | 1)>(v + 2 * (N / 3 | 1)));
}
template <int N> DEVI bool all_arrived(const uint32_t* v) { return __all_sync(0xffffffffu, umax<N>(v) != 0xffffffffu); }
DEVI void flag_add(unsigned* p) {
  asm volatile("fence.release.gpu;\nred.relaxed.gpu.global.add.u32 [%0], 1;" :: "l"(p) : "memory");
}
DEVI void fence_async_smem() { asm volatile("fence.proxy.async.shared::cta;" ::: "memory"); }
DEVI void bar_sync(int id, int n) { asm volatile("bar.sync %0, %1;" :: "r"(id), "r"(n) : "memory"); }
DEVI void cluster_arrive() { asm volatile("barrier.cluster.arrive.relaxed.aligned;" ::: "memory"); }
DEVI void cluster_wait() { asm volatile("barrier.cluster.wait.aligned;" ::: "memory"); }
DEVI void wg_fence() { asm volatile("wgmma.fence.sync.aligned;" ::: "memory"); }
DEVI void wg_commit() { asm volatile("wgmma.commit_group.sync.aligned;" ::: "memory"); }
template <int N> DEVI void wg_wait() { asm volatile("wgmma.wait_group.sync.aligned %0;" :: "n"(N) : "memory"); }
template <int N> DEVI void pin(uint32_t* r) {
#pragma unroll
  for (int i = 0; i < N; i++) asm volatile("" : "+r"(r[i]) :: "memory");
}
template <int N> DEVI void pin(float* r) {
#pragma unroll
  for (int i = 0; i < N; i++) asm volatile("" : "+f"(r[i]) :: "memory");
}

DEVI void sched_fence(int zero, int id) { asm volatile("{\n.reg .pred p;\nsetp.eq.b32 p, %0, %1;\nS_LOOP:\n@p st.volatile.shared.b32 [%0], %0;\n@p bra S_LOOP;\n}" :: "r"(zero), "r"(id + 1) : "memory"); }
DEVI void pin_range(float* r, int i0, int i1) {
#pragma unroll
  for (int i = i0; i < i1; i++) asm volatile("" : "+f"(r[i]) :: "memory");
}
DEVI void keep(uint32_t& x) { asm volatile("" : "+r"(x) :: "memory"); }
DEVI void keep(int& x) { asm volatile("" : "+r"(x) :: "memory"); }
template <class T> DEVI void keep(T*& x) { asm volatile("" : "+l"(x) :: "memory"); }

DEVI void tma2d(uint32_t dst, const CUtensorMap* m, int c0, int c1, uint32_t bar) {
  asm volatile("cp.async.bulk.tensor.2d.shared::cluster.global.mbarrier::complete_tx::bytes [%0], [%1, {%3, %4}], [%2];"
               :: "r"(dst), "l"(m), "r"(bar), "r"(c0), "r"(c1) : "memory");
}
DEVI void tma2d_mc(uint32_t dst, const CUtensorMap* m, int c0, int c1, uint32_t bar) {
  asm volatile("cp.async.bulk.tensor.2d.shared::cluster.global.mbarrier::complete_tx::bytes.multicast::cluster [%0], [%1, {%3, %4}], [%2], %5;"
               :: "r"(dst), "l"(m), "r"(bar), "r"(c0), "r"(c1), "h"((uint16_t)3) : "memory");
}
DEVI void tma3d(uint32_t dst, const CUtensorMap* m, int c0, int c1, int c2, uint32_t bar) {
  asm volatile("cp.async.bulk.tensor.3d.shared::cluster.global.mbarrier::complete_tx::bytes [%0], [%1, {%3, %4, %5}], [%2];"
               :: "r"(dst), "l"(m), "r"(bar), "r"(c0), "r"(c1), "r"(c2) : "memory");
}
DEVI void tma3d_mc(uint32_t dst, const CUtensorMap* m, int c0, int c1, int c2, uint32_t bar) {
  asm volatile("cp.async.bulk.tensor.3d.shared::cluster.global.mbarrier::complete_tx::bytes.multicast::cluster [%0], [%1, {%3, %4, %5}], [%2], %6;"
               :: "r"(dst), "l"(m), "r"(bar), "r"(c0), "r"(c1), "r"(c2), "h"((uint16_t)3) : "memory");
}
DEVI void tma2d_store(const CUtensorMap* m, uint32_t src, int c0, int c1) {
  asm volatile("cp.async.bulk.tensor.2d.global.shared::cta.bulk_group [%0, {%2, %3}], [%1];" :: "l"(m), "r"(src), "r"(c0), "r"(c1) : "memory");
}
DEVI void bulk_load(uint32_t dst, const void* src, uint32_t bytes, uint32_t bar) {
  asm volatile("cp.async.bulk.shared::cluster.global.mbarrier::complete_tx::bytes [%0], [%1], %2, [%3];" :: "r"(dst), "l"(src), "r"(bytes), "r"(bar) : "memory");
}
DEVI void bulk_store(void* dst, uint32_t src, uint32_t bytes) {
  asm volatile("cp.async.bulk.global.shared::cta.bulk_group [%0], [%1], %2;" :: "l"(dst), "r"(src), "r"(bytes) : "memory");
}
DEVI uint32_t peer_addr(uint32_t a, int rank) { uint32_t r; asm("mapa.shared::cluster.u32 %0, %1, %2;" : "=r"(r) : "r"(a), "r"(rank)); return r; }
DEVI void bulk_to_peer(uint32_t dst, uint32_t src, uint32_t bytes, uint32_t bar, int rank) {
  asm volatile("cp.async.bulk.shared::cluster.shared::cta.mbarrier::complete_tx::bytes [%0], [%1], %2, [%3];"
               :: "r"(peer_addr(dst, rank)), "r"(src), "r"(bytes), "r"(peer_addr(bar, rank)) : "memory");
}
DEVI void l2_prefetch(const void* p, uint32_t bytes) {
  asm volatile("cp.async.bulk.prefetch.L2.global [%0], %1;" :: "l"(p), "r"(bytes) : "memory");
}
DEVI void l2_prefetch2d(const CUtensorMap* m, int c0, int c1) {
  asm volatile("cp.async.bulk.prefetch.tensor.2d.L2.global [%0, {%1, %2}];" :: "l"(m), "r"(c0), "r"(c1) : "memory");
}
DEVI void l2_prefetch3d(const CUtensorMap* m, int c0, int c1, int c2) {
  asm volatile("cp.async.bulk.prefetch.tensor.3d.L2.global [%0, {%1, %2, %3}];" :: "l"(m), "r"(c0), "r"(c1), "r"(c2) : "memory");
}
DEVI void bulk_commit() { asm volatile("cp.async.bulk.commit_group;" ::: "memory"); }
DEVI void bulk_wait_read() { asm volatile("cp.async.bulk.wait_group.read 0;" ::: "memory"); }
DEVI void prefetch_map(const CUtensorMap* m) { asm volatile("prefetch.tensormap [%0];" :: "l"(m) : "memory"); }
DEVI void arrive_both(uint32_t bar, int lane, bool pred = true) {
  asm volatile("{\n.reg .pred p;\n.reg .b32 r;\nsetp.ne.b32 p, %2, 0;\nmapa.shared::cluster.u32 r, %0, %1;\n@p mbarrier.arrive.shared::cluster.b64 _, [r];\n}"
               :: "r"(bar), "r"(lane & 1), "r"((int)(pred && lane < 2)) : "memory");
}

DEVI uint64_t make_desc(uint32_t off, uint32_t lbo, uint32_t sbo, uint32_t mode) {
  const uint32_t lo = (off >> 4) + (SM_BASE >> 4) + ((lbo >> 4) << 16), hi = (sbo >> 4) | (mode << 30);
  return ((uint64_t)hi << 32) | lo;
}
DEVI uint32_t pack_bf16(float lo, float hi) { uint32_t r; asm("cvt.rn.bf16x2.f32 %0, %1, %2;" : "=r"(r) : "f"(hi), "f"(lo)); return r; }
DEVI void stsm4(uint32_t addr, uint32_t r0, uint32_t r1, uint32_t r2, uint32_t r3) {
  asm volatile("stmatrix.sync.aligned.m8n8.x4.shared.b16 [%0], {%1,%2,%3,%4};" :: "r"(addr), "r"(r0), "r"(r1), "r"(r2), "r"(r3) : "memory");
}
DEVI void stsm4_t(uint32_t addr, uint32_t r0, uint32_t r1, uint32_t r2, uint32_t r3) {
  asm volatile("stmatrix.sync.aligned.m8n8.x4.trans.shared.b16 [%0], {%1,%2,%3,%4};" :: "r"(addr), "r"(r0), "r"(r1), "r"(r2), "r"(r3) : "memory");
}
DEVI void ldsm4(uint32_t* r, uint32_t addr) {
  asm volatile("ldmatrix.sync.aligned.m8n8.x4.shared.b16 {%0,%1,%2,%3}, [%4];" : "=r"(r[0]), "=r"(r[1]), "=r"(r[2]), "=r"(r[3]) : "r"(addr) : "memory");
}
DEVI void ldsm4_t(uint32_t* r, uint32_t addr) {
  asm volatile("ldmatrix.sync.aligned.m8n8.x4.trans.shared.b16 {%0,%1,%2,%3}, [%4];" : "=r"(r[0]), "=r"(r[1]), "=r"(r[2]), "=r"(r[3]) : "r"(addr) : "memory");
}
DEVI uint4 lds128(uint32_t a) {
  uint4 v; asm volatile("ld.shared.v4.b32 {%0,%1,%2,%3}, [%4];" : "=r"(v.x), "=r"(v.y), "=r"(v.z), "=r"(v.w) : "r"(a) : "memory"); return v;
}
DEVI uint32_t bmul2(uint32_t a, uint32_t b) { uint32_t r; asm("mul.rn.bf16x2 %0, %1, %2;" : "=r"(r) : "r"(a), "r"(b)); return r; }
DEVI uint32_t bfma2(uint32_t a, uint32_t b, uint32_t c) { uint32_t r; asm("fma.rn.bf16x2 %0, %1, %2, %3;" : "=r"(r) : "r"(a), "r"(b), "r"(c)); return r; }
DEVI float bf_lo(uint32_t w) { return __uint_as_float(w << 16); }
DEVI float bf_hi(uint32_t w) { return __uint_as_float(w & 0xffff0000u); }
DEVI uint32_t elu1(float a0, float a1) {
  constexpr float L = 1.4426950408889634f;
  float e0, e1;
  asm("ex2.approx.ftz.f32 %0, %1;" : "=f"(e0) : "f"(-fabsf(fmaf(a0, L, -L))));
  asm("ex2.approx.ftz.f32 %0, %1;" : "=f"(e1) : "f"(-fabsf(fmaf(a1, L, -L))));
  return pack_bf16(fmaxf(e0, a0), fmaxf(e1, a1));
}
DEVI float rcp(float x) { float r; asm("rcp.approx.ftz.f32 %0, %1;" : "=f"(r) : "f"(x)); return r; }
DEVI uint32_t add_eps(uint32_t x) { uint32_t r; asm("add.rn.bf16x2 %0, %1, %2;" : "=r"(r) : "r"(x), "r"(0x35863586u)); return r; }

DEVI uint32_t hmul(uint32_t a, uint32_t b) { uint32_t r; asm("mul.rn.f16x2 %0, %1, %2;" : "=r"(r) : "r"(a), "r"(b)); return r; }
DEVI uint32_t hfma(uint32_t a, uint32_t b, uint32_t c) { uint32_t r; asm("fma.rn.f16x2 %0, %1, %2, %3;" : "=r"(r) : "r"(a), "r"(b), "r"(c)); return r; }
DEVI uint32_t hneg(uint32_t a) { uint32_t r; asm("neg.f16x2 %0, %1;" : "=r"(r) : "r"(a)); return r; }
DEVI uint32_t hadd(uint32_t a, uint32_t b) { uint32_t r; asm("add.rn.f16x2 %0, %1, %2;" : "=r"(r) : "r"(a), "r"(b)); return r; }
DEVI uint32_t hsub(uint32_t a, uint32_t b) { uint32_t r; asm("sub.rn.f16x2 %0, %1, %2;" : "=r"(r) : "r"(a), "r"(b)); return r; }
struct Cx { uint32_t re, im; };
DEVI Cx cmul(Cx a, Cx b) { return {hfma(a.re, b.re, hneg(hmul(a.im, b.im))), hfma(a.re, b.im, hmul(a.im, b.re))}; }
DEVI Cx cfma(Cx a, Cx b, Cx c) { return {hfma(a.re, b.re, hfma(hneg(a.im), b.im, c.re)), hfma(a.re, b.im, hfma(a.im, b.re, c.im))}; }
DEVI Cx rot(Cx a, Cx t) {
  const uint32_t x = hfma(hneg(t.re), a.im, a.re), y = hfma(t.im, x, a.im);
  return {hfma(hneg(t.re), y, x), y};
}
struct Fft {
  uint32_t fa[8];
  Cx tw[2];
  uint32_t vld;
  uint64_t dF2a, dF2b;
  uint32_t vst;
  DEVI void stage1(uint32_t* d1, uint32_t slot) const {
    wg_fence();
    fft1_init(d1, fa[0], fa[1], fa[2], fa[3], make_desc(slot, 4096, 1024, 1));
    fft1_acc(d1, fa[4], fa[5], fa[6], fa[7], make_desc(slot + 2048, 4096, 1024, 1));
    wg_commit();
  }
  DEVI void stage2(uint32_t* d, const Cx* t) const {
    wg_fence();
    fft2_init(d, t[0].re, t[1].re, t[2].re, t[3].re, dF2a);
    fft2_acc(d, t[0].im, t[1].im, t[2].im, t[3].im, dF2b);
    wg_commit();
  }
  template <int PR> DEVI void fwd(const uint32_t* d1, uint32_t* d2) const {
    Cx t[4];
#pragma unroll
    for (int e = 0; e < 4; e++) {
      const int j = 8 * (PR & 1) + 4 * (e >> 1) + 2 * (PR >> 1) + (e & 1);
      t[e] = rot({d1[2 * j], d1[2 * j + 1]}, tw[e >> 1]);
    }
    stage2(d2 + 8 * PR, t);
  }
  static DEVI Cx U(const uint32_t* d2, int p, int hi) { return {d2[16 * (p >> 1) + 2 * hi + (p & 1)], d2[16 * (p >> 1) + 4 + 2 * hi + (p & 1)]}; }
  static DEVI Cx H(const uint32_t* d2, int p, int hi) { return U(d2 + 8, p, hi); }
  DEVI void prod01(const uint32_t* d2, Cx* p1, uint32_t* d3) const {
    Cx z[4];
#pragma unroll
    for (int hi = 0; hi < 2; hi++) {
      const Cx p0 = cmul(H(d2, 0, hi), U(d2, 0, hi));
      p1[hi] = cfma(H(d2, 1, hi), U(d2, 0, hi), cmul(H(d2, 0, hi), U(d2, 1, hi)));
      z[2 * hi] = {p0.im, p0.re};
      z[2 * hi + 1] = {hsub(p1[hi].im, p0.re), hadd(p1[hi].re, p0.im)};
    }
    stage2(d3, z);
  }
  DEVI void prod23(const uint32_t* d2, const Cx* p1, uint32_t* d3) const {
    Cx z[4];
#pragma unroll
    for (int hi = 0; hi < 2; hi++) {
      const Cx p2 = cfma(H(d2, 2, hi), U(d2, 0, hi), cfma(H(d2, 0, hi), U(d2, 2, hi), cmul(H(d2, 1, hi), U(d2, 1, hi))));
      const Cx z3 = cfma(H(d2, 3, hi), U(d2, 0, hi), cfma(H(d2, 2, hi), U(d2, 1, hi),
                    cfma(H(d2, 1, hi), U(d2, 2, hi), cfma(H(d2, 0, hi), U(d2, 3, hi), {p2.im, hneg(p2.re)}))));
      z[2 * hi] = {hsub(p2.im, p1[hi].re), hadd(p2.re, p1[hi].im)};
      z[2 * hi + 1] = {z3.im, z3.re};
    }
    stage2(d3 + 8, z);
  }
  template <int PB> DEVI void inv(const uint32_t* d3, uint32_t slot) const {
    Cx v[4];
#pragma unroll
    for (int e = 0; e < 4; e++) {
      const int r = 8 * PB + 2 * (e & 1) + (e >> 1);
      v[e] = rot({d3[r], d3[r + 4]}, tw[e & 1]);
    }
    stsm4(slot + (vst ^ (PB * 64)), v[0].im, v[1].im, v[2].im, v[3].im);
    stsm4(slot + 1024 + (vst ^ (PB * 64)), v[0].re, v[1].re, v[2].re, v[3].re);
  }
  DEVI void last_load(uint32_t* a, uint32_t slot, int wg) const {
    bar_sync(2 + wg, 128);
#pragma unroll
    for (int ks = 0; ks < 4; ks++) ldsm4_t(a + 4 * ks, vld + slot + ks * 2048);
  }
  DEVI void last_mma(float* dy, const uint32_t* a) const {
    wg_fence();
    fft3_init(dy, a[0], a[1], a[2], a[3], make_desc(SM_F1, 128, 1024, 0));
#pragma unroll
    for (int ks = 1; ks < 4; ks++) fft3_acc(dy, a[4 * ks], a[4 * ks + 1], a[4 * ks + 2], a[4 * ks + 3], make_desc(SM_F1 + ks * 256, 128, 1024, 0));
    wg_commit();
  }
  DEVI void last(float* dy, uint32_t slot, int wg) const { uint32_t a[16]; last_load(a, slot, wg); last_mma(dy, a); }
  static DEVI void store_y(const float* dy, uint32_t a) {
    stsm4_t(a, pack_bf16(dy[0], dy[1]), pack_bf16(dy[2], dy[3]), pack_bf16(dy[4], dy[5]), pack_bf16(dy[6], dy[7]));
    stsm4_t(a + 512, pack_bf16(dy[8], dy[9]), pack_bf16(dy[10], dy[11]), pack_bf16(dy[12], dy[13]), pack_bf16(dy[14], dy[15]));
  }
};
DEVI uint32_t normalize(uint32_t* x, uint32_t dst) {
  uint32_t m = x[0];
#pragma unroll
  for (int i = 1; i < 32; i++) asm("max.xorsign.abs.bf16x2 %0, %0, %1;" : "+r"(m) : "r"(x[i]));
  const uint32_t e = min(__reduce_max_sync(0xffffffffu, max(m & 0x7fffu, (m >> 16) & 0x7fffu)) >> 7, 252u);
  if (e > 140) {
#pragma unroll
    for (int i = 0; i < 32; i++) x[i] = bmul2(x[i], 15u * 0x00800080u);
  }
  const uint32_t sc = (e > 140 ? 253u - e : 141u - e) * 0x00800080u;
#pragma unroll
  for (int i = 0; i < 8; i++) {
    uint32_t y[4];
#pragma unroll
    for (int n = 0; n < 4; n++) {
      const uint32_t w = bmul2(x[4 * i + n], sc);
      y[n] = (w & 0x7fff7fffu) * 7u + w;
    }
    stsm4((dst ^ ((i >> 1) << 4)) + (i & 1) * 2048, y[0], y[1], y[2], y[3]);
  }
  return e;
}
#define XPF 3
#define HSTART 3
#define PSTART 5
#define PF0 28
#define PD1 600
#define PD2 500
#define PD3 900
#define FDELAY 100
#define C1DELAY 200
#define FORCE_REDO 0
static_assert(HSTART >= 4 - XPF && PF0 >= HSTART + 19 && PF0 <= 28, "producer schedule");

__global__ void __cluster_dims__(2, 1, 1) __launch_bounds__(kThreads, 1)
fused_kernel(const __grid_constant__ Params P) {
  extern __shared__ __align__(1024) uint8_t smem[];
  if (threadIdx.x == 0) { prefetch_map(&P.x); prefetch_map(&P.w); prefetch_map(&P.wk); prefetch_map(blockIdx.x & 1 ? &P.v : &P.k); }
  const uint32_t sb = __shfl_sync(0xffffffffu, (uint32_t)__cvta_generic_to_shared(smem), 0);
  const int tid = threadIdx.x, lane = tid & 31;
  const int warp = __shfl_sync(0xffffffffu, tid >> 5, 0);
  const int bc = blockIdx.x >> 1, late = ((bc - 36) * 37) >> 8;
  const int rp = bc < 4 ? 0 : bc < 36 ? (bc - 4) & 7 : bc - 35 - 7 * late, j = bc < 4 ? 4 + bc : bc < 36 ? (bc - 4) >> 3 : 4 + late;
  const int rho = blockIdx.x & 1, cl = 8 * rp + j, cta = 2 * cl + rho, r = rp * 2 + rho;
  auto bar = [&](int i) { return sb + SM_BAR + 8u * i; };
  TSTAMP(tid == 0, 0); GSTAMP(tid == 0, 30);
  auto load_stage = [&](int it) {
    const uint32_t st = sb + (it & 3) * QKV_STAGE, fb = bar(B_QKV_FULL + (it & 3));
    mbar_expect(fb, QKV_STAGE);
    tma2d_mc(st + 24576 + rho * 4096, &P.wk, 1024 + 128 * j + 64 * rho, 32 * it, fb);
    tma3d_mc(st + 8192 + rho * 8192, &P.w, 0, 32 * it, 32 * rho + 2 * j, fb);
    tma2d(st, &P.x, 32 * it, 128 * r, fb);
  };
  if (warp == 8 && elect()) {
    mbar_init(bar(B_FIRST), 1);
    mbar_expect(bar(B_FIRST), 16384);
    tma2d(sb, &P.x, 0, 128 * r, bar(B_FIRST));
    tma3d(sb + 24576, &P.w, 0, 0, 16 + 2 * j, bar(B_FIRST));
    mbar_init(bar(B_QKV_FULL), 1);
    mbar_expect(bar(B_QKV_FULL), 16384);
    tma3d(sb + 8192, &P.w, 0, 0, 2 * j, bar(B_QKV_FULL));
    tma3d(sb + 16384, &P.w, 0, 0, 32 + 2 * j, bar(B_QKV_FULL));
    for (int i = 1; i < 4; i++) mbar_init(bar(B_QKV_FULL + i), 1);
    asm volatile("fence.mbarrier_init.release.cluster;" ::: "memory");
  }
  LOOPSTAMP(3, tid == 256, 13);
  __syncwarp();
  cluster_arrive();

  if (warp < 8) {
    asm volatile("setmaxnreg.inc.sync.aligned.u32 224;");
    const int wg = warp >> 2, wq = warp & 3;
    const int zero = __shfl_sync(0xffffffffu, P.zero, 0);
    const uint32_t orow = wq * 2048 + (lane & 15) * 128, ox = ((lane >> 4) ^ (lane & 7)) << 4;
    float aq[64];
    Fft F;
    uint32_t a1[32];
    {
      float ak[64], avq[128];
      auto k_step = [&](uint32_t st, int kk) {
        mma_tn(ak, make_desc(st + 24576 + wg * 4096 + kk * 2048, 4096, 1024, 1), make_desc(st + kk * 32, 16, 512, 2));
      };
      auto vq_step = [&](uint32_t st, int kk) {
        mma_nt256(avq, make_desc(st + wg * 4096 + kk * 32, 16, 512, 2), make_desc(st + 8192 + kk * 2048, 4096, 1024, 1));
      };
#pragma unroll
      for (int i = 0; i < 64; i++) { ak[i] = 1.f; avq[i] = 1.f; avq[64 + i] = 0.f; }
      pin<64>(ak); pin<128>(avq);
      cluster_wait();
      cluster_arrive();
      cluster_wait();
      LOOPSTAMP(3, tid == 0, 17);
      mbar_wait(bar(B_FIRST), 0);
      TSTAMP(tid == 0, 1);
      wg_fence();
      k_step(0, 0); k_step(0, 1);
      wg_commit();
      mbar_wait(bar(B_QKV_FULL), 0);
      wg_fence();
      vq_step(0, 0); vq_step(0, 1);
      wg_commit();
#pragma unroll 1
      for (int it = 1; it < 29; ++it) {
        mbar_wait(bar(B_QKV_FULL + (it & 3)), (it >> 2) & 1);
        TSTAMP(tid == 0 && it == 4, 6); TSTAMP(tid == 0 && it == 12, 29); LOOPSTAMP(1, tid == 0 && it < 27, 1 + it); LOOPSTAMP(3, tid == 0 && it < 12, 1 + it);
        const uint32_t st = (it & 3) * QKV_STAGE;
        wg_fence();
        k_step(st, 0);
        wg_commit();
        wg_wait<1>();
        arrive_both(bar(B_QKV_EMPTY + ((it - 1) & 3)), lane);
        wg_fence();
        vq_step(st, 0);
        k_step(st, 1);
        vq_step(st, 1);
        wg_commit();
      }
#pragma unroll 1
      for (int s = 1; s < 4; ++s) {
        mbar_wait(bar(B_QKV_FULL + s), 1);
        wg_fence();
        k_step(s * QKV_STAGE, 0);
        k_step(s * QKV_STAGE, 1);
        wg_commit();
      }
      uint32_t pk[32];
      auto phi_k = [&](int i0, int i1) {
#pragma unroll
        for (int i = i0; i < i1; i++) { pk[i] = elu1(ak[2 * i], ak[2 * i + 1]); asm volatile("" : "+r"(pk[i]) :: "memory"); }
        sched_fence(zero, i0);
      };
#pragma unroll
      for (int n = 0; n < 6; n++) {
        wg_fence();
        vq_step((1 + (n >> 1)) * QKV_STAGE, n & 1);
        wg_commit();
        if (n == 0) {
          wg_wait<1>();
          pin<64>(ak);
          TSTAMP(tid == 0, 2);
          bar_sync(1, 256);
        }
        phi_k(n ? 6 * n - 4 : 0, 6 * n + 2);
      }
      mbar_wait(bar(B_SIG_READY), 0);
      ldsm4_t(F.fa, sb + SM_F1 + (lane >> 4) * 1024 + wq * 256 + (lane & 15) * 16);
      ldsm4_t(F.fa + 4, sb + SM_F1 + 2048 + (lane >> 4) * 1024 + wq * 256 + (lane & 15) * 16);
      const uint4 tw = lds128(sb + SM_TW + (tid & 127) * 16);
      F.tw[0] = {tw.x, tw.y}; F.tw[1] = {tw.z, tw.w};
      F.vld = sb + ((lane >> 4) * 8 + (lane & 7)) * 128 + (((2 * wq + ((lane >> 3) & 1)) ^ (lane & 7)) << 4);
      F.dF2a = make_desc(SM_F2, 128, 512, 0) + (uint64_t)zero * 0x100000001ull;
      F.dF2b = F.dF2a + 16;
      F.vst = sb + (16 * wq + (lane & 7)) * 128 + (((lane >> 3) ^ (lane & 7)) << 4);
      wg_wait<0>();
      pin<128>(avq);
      arrive_both(bar(B_QKV_DONE), lane);
      TSTAMP(tid == 0, 3);
#pragma unroll
      for (int t = 0; t < 8; t++) {
        const float* b = avq + 64 + 8 * t;
        stsm4(sb + (t >> 2) * SLOT + wg * 8192 + orow + (ox ^ ((t & 3) << 5)), pack_bf16(b[0], b[1]), pack_bf16(b[2], b[3]), pack_bf16(b[4], b[5]), pack_bf16(b[6], b[7]));
      }
#pragma unroll
      for (int i = 0; i < 64; i++) aq[i] = avq[i];
      fence_async_smem();
      bar_sync(1, 256);
      float dkv[36];
#pragma unroll
      for (int ks = 0; ks < 8; ks++) {
        const uint32_t va = wg * SLOT + ks * 2048;
        const uint64_t db = make_desc(va, SM_ONES - va, 1024, 1);
        uint32_t a[4];
        pin<4>(pk + 4 * ks);
#pragma unroll
        for (int i = 0; i < 4; i++) a[i] = add_eps(pk[4 * ks + i]);
        wg_fence();
        if (ks == 0) mma_kv_init(dkv, a[0], a[1], a[2], a[3], db);
        else mma_kv_acc(dkv, a[0], a[1], a[2], a[3], db);
      }
      wg_commit();
      uint8_t* box = g_xch[warp * 16 + j] + 2 * SLOT + r * KV_SLICE + lane * 16;
      uint8_t* zbox = box + (lane & 1) * 8 * XCH_BYTES + 512 + (lane & 28) - lane * 16;
      keep(box); keep(zbox);
      mbar_wait(bar(B_ZEROED), 0);
      wg_wait<0>();
      pin<36>(dkv);
      F.stage1(a1, SM_SIG + wg * 8192);
      TSTAMP(tid == 0, 4);
      auto put = [&](const float* d) {
#pragma unroll
        for (int m = 0; m < 2; m++)
          asm volatile("st.relaxed.gpu.global.v4.b32 [%0], {%1,%2,%3,%4};" :: "l"(box + m * 8 * XCH_BYTES), "r"(pack_bf16(d[2 * m], d[2 * m + 1])),
                       "r"(pack_bf16(d[2 * m + 4], d[2 * m + 5])), "r"(pack_bf16(d[2 * m + 8], d[2 * m + 9])), "r"(pack_bf16(d[2 * m + 12], d[2 * m + 13])) : "memory");
      };
      if (wq < 2) put(dkv); else put(dkv + 16);
      asm volatile("{\n.reg .pred p;\nsetp.eq.b32 p, %2, 0;\n@p st.relaxed.gpu.global.b32 [%0], %1;\n}" :: "l"(zbox), "f"(lane & 1 ? dkv[34] : dkv[32]), "r"(lane & 2) : "memory");
      __syncwarp();
      mbar_arrive_if(bar(B_KVP), lane == 0);
      TSTAMP(tid == 0, 5);
    }

    uint32_t pq[32];
    auto phi_q = [&](int i0, int i1) {
      pin_range(aq, 2 * i0, 2 * i1);
#pragma unroll
      for (int i = i0; i < i1; i++) { pq[i] = add_eps(elu1(aq[2 * i], aq[2 * i + 1])); keep(pq[i]); }
    };
    uint32_t a2[32];
    float by[16];
    auto conv_pair = [&](uint32_t sa, uint32_t ya, uint32_t first) {
      const uint32_t sc = sa + SLOT;
      uint32_t b1[32], b2[32], a3[16], b3[16];
      float ay[16];
      Cx pa[2], pb[2];
      F.stage1(b1, sc);
      F.prod01(a2, pa, a3);
      F.prod23(a2, pa, a3);
      uint32_t va[16];
      wg_wait<1>(); pin<32>(b1); pin<8>(a3);
      F.fwd<0>(b1, b2); F.fwd<1>(b1, b2);
      F.inv<0>(a3, sa);
      F.fwd<2>(b1, b2);
      wg_wait<3>(); pin<8>(a3 + 8);
      F.inv<1>(a3, sa);
      F.fwd<3>(b1, b2);
      F.last_load(va, sa, wg);
      wg_wait<2>(); pin<16>(b2);
      F.prod01(b2, pb, b3);
      F.last_mma(ay, va);
      wg_wait<2>(); pin<16>(b2 + 16);
      F.prod23(b2, pb, b3);
      mbar_wait(bar(B_RDY1), first);
      wg_wait<1>(); pin<8>(b3); pin<16>(ay);
      mbar_arrive_if(bar(B_SLOT_FREE), lane == 0);
      F.inv<0>(b3, sc);
      Fft::store_y(ay, ya);
      wg_wait<0>(); pin<8>(b3 + 8);
      F.inv<1>(b3, sc);
    };
    const bool ylocal = (wq >> 1) == rho;
    const uint32_t yoff = sb + (wq & 1) * 1024 + ((lane ^ wg ^ (2 * rho)) << 4);
    const uint32_t ya0 = yoff + (ylocal ? SM_Y0 + wg * 8192 : SM_YT + wg * 4096), ya1 = (yoff ^ 64) + (ylocal ? SM_SIG + wg * 8192 : SM_YT + wg * 4096);
    auto pair_done = [&](uint32_t ya, int seg) {
      pin<16>(by);
      Fft::store_y(by, (ya ^ 32) + 2048);
      __syncwarp();
      mbar_arrive_if(bar(B_SEG + 2 * seg + wg), lane == 0);
    };
    const uint32_t s0 = SM_SIG + wg * 8192, s1 = s0 + 2 * SLOT;
    phi_q(0, 2);
    wg_wait<0>(); pin<32>(a1);
    bar_sync(2 + wg, 128);
    F.fwd<0>(a1, a2); phi_q(2, 5);
    F.fwd<1>(a1, a2); phi_q(5, 8);
    F.fwd<2>(a1, a2); phi_q(8, 11);
    F.fwd<3>(a1, a2); phi_q(11, 13);
    wg_wait<0>(); pin<32>(a2);
#pragma unroll 1
    for (uint32_t sa = s0;; sa += 2 * SLOT + P.zero) {
      conv_pair(sa, sa == s1 ? ya1 : ya0, sa != s1);
      if (sa == s1) break;
      F.stage1(a1, s1);
      phi_q(13, 17);
      F.last(by, s0 + SLOT, wg);
      phi_q(17, 32);
      wg_wait<0>();
      pair_done(ya0, 0);
      TSTAMP(tid == 0, 7);
      float dn[4][20];
      pin<32>(a1);
      bar_sync(2 + wg, 128);
      F.fwd<0>(a1, a2); F.fwd<1>(a1, a2); F.fwd<2>(a1, a2);
      mbar_wait(bar(B_KV_READY), 0);
      TSTAMP(tid == 0, 8);
      auto head_mma = [&](int h) {
        wg_fence();
        const uint64_t db = make_desc(SM_KV + h * 2560, 640, 128, 0);
        const uint32_t* a = pq + 8 * h;
        mma_o_init(dn[h], a[0], a[1], a[2], a[3], db);
        mma_o_acc(dn[h], a[4], a[5], a[6], a[7], db + (1280 >> 4));
        wg_commit();
      };
      auto head_store = [&](int h) {
        pin<20>(dn[h]);
        const float i0 = rcp(dn[h][16] + 1e-6f), i1 = rcp(dn[h][18] + 1e-6f);
        const uint32_t p0 = pack_bf16(i0, i0), p1 = pack_bf16(i1, i1);
#pragma unroll
        for (int hf = 0; hf < 2; hf++) {
          const float* a = dn[h] + 8 * hf;
          const uint32_t dst = sb + (h >> 1) * SLOT + wg * 8192 + orow + (ox ^ (((h & 1) * 2 + hf) << 5));
          uint32_t o[4];
#pragma unroll
          for (int i = 0; i < 4; i++) o[i] = bmul2(pack_bf16(a[2 * i], a[2 * i + 1]), i & 1 ? p1 : p0);
          stsm4(dst, o[0], o[1], o[2], o[3]);
#pragma unroll
          for (int i = 0; i < 4; i++) pq[8 * h + 4 * hf + i] = o[i];
        }
        if (h & 1) { __syncwarp(); mbar_arrive_if(bar(B_O_WRITTEN + (h >> 1)), lane == 0); }
      };
      head_mma(0); head_mma(1);
      wg_wait<1>(); head_store(0);
      mbar_wait(bar(B_KV_READY + 1), 0);
      head_mma(2);
      wg_wait<1>(); head_store(1);
      head_mma(3);
      wg_wait<1>(); head_store(2);
      F.fwd<3>(a1, a2);
      wg_wait<1>(); head_store(3);
      wg_wait<0>();
      pin<32>(a2);
    }

    float acc[64];
    auto stage_mma = [&](int s, int kk) {
      mma_nt(acc, make_desc(((A_SLOTS >> (4 * s)) & 15) * SLOT + wg * 8192 + kk * 32, 16, 1024, 1),
             make_desc(((B_SLOTS >> (4 * s)) & 15) * SLOT + kk * 2048, 8192, 1024, 1));
    };
    {
      auto own_mma = [&](int n) {
        const uint64_t db = make_desc((4 + (n >> 2)) * SLOT + (n & 3) * 2048, 8192, 1024, 1);
        if (n == 0) mma_own_init(acc, pq[0], pq[1], pq[2], pq[3], db);
        else mma_own_acc(acc, pq[4 * n], pq[4 * n + 1], pq[4 * n + 2], pq[4 * n + 3], db);
      };
      mbar_wait(bar(B_OUT_FULL), 0);
      wg_fence();
      own_mma(0);
      wg_commit();
      F.last(by, s1 + SLOT, wg);
      wg_fence();
      own_mma(1);
      wg_commit();
      wg_wait<1>();
      pair_done(ya1, 1);
      mbar_arrive_if(bar(B_CONV_DONE), lane == 0);
      cluster_arrive();
      wg_fence();
      own_mma(2); own_mma(3);
      wg_commit();
      mbar_wait(bar(B_OUT_FULL + 1), 0);
      wg_fence();
      own_mma(4);
      wg_commit();
      wg_wait<1>();
      arrive_both(bar(B_OUT_EMPTY), lane);
      wg_fence();
      own_mma(5); own_mma(6); own_mma(7);
      wg_commit();
      int s = 2, sprev = 1;
      uint32_t ph = 0;
#pragma unroll 1
      for (int ks = 2; ks < 12; ++ks) {
        mbar_wait(bar(B_OUT_FULL + s), ph);
        LOOPSTAMP(2, tid == 0, 1 + ks);
        TSTAMP(tid == 0 && ks == 2, 13); TSTAMP(tid == 0 && ks == 9, 14);
        wg_fence();
        stage_mma(s, 0);
        wg_commit();
        wg_wait<1>();
        arrive_both(bar(B_OUT_EMPTY + sprev), lane);
        wg_fence();
#pragma unroll
        for (int kk = 1; kk < 4; kk++) stage_mma(s, kk);
        wg_commit();
        sprev = s;
        if (++s == 5) { s = 0; ph ^= 1; }
      }
      asm volatile("{\n.reg .pred p;\nsetp.ne.b32 p, %0, 0;\n@p bar.sync 1, 256;\n}" :: "r"(wg) : "memory");
#pragma unroll 1
      for (int ks = 12; ks < 16; ++ks) {
        mbar_wait(bar(B_OUT_FULL + s), ks == 15);
        wg_fence();
#pragma unroll
        for (int kk = 0; kk < 4; kk++) stage_mma(s, kk);
        wg_commit();
        if (++s == 5) s = 0;
      }
      asm volatile("{\n.reg .pred p;\nsetp.eq.b32 p, %0, 0;\n@p bar.arrive 1, 256;\n}" :: "r"(wg) : "memory");
    }
    wg_wait<0>(); pin<64>(acc);
    TSTAMP(tid == 0, 15); TSTAMP(tid == 128, 16);
#pragma unroll
    for (int hf = 0; hf < 2; hf++) {
      const uint32_t dst = sb + hf * SLOT + wg * 8192;
#pragma unroll
      for (int t = 0; t < 4; t++) {
        const float* a = acc + 32 * hf + 8 * t;
        stsm4(dst + orow + (ox ^ (t << 5)), pack_bf16(a[0], a[1]), pack_bf16(a[2], a[3]), pack_bf16(a[4], a[5]), pack_bf16(a[6], a[7]));
      }
      fence_async_smem();
      __syncwarp();
      if (elect()) { tma2d_store(&P.outa, dst + wq * 2048, 128 * j + 64 * hf, 128 * r + 16 * warp); bulk_commit(); }
    }
    const bool stale = __any_sync(0xffffffffu, acc[0] != acc[0] || acc[2] != acc[2] || FORCE_REDO);
    if (elect()) bulk_wait_read();
    TSTAMP(tid == 128, 17);
    __syncwarp();
    cluster_wait();
    TSTAMP(tid == 128, 28); GSTAMP(tid == 128, 31);
    if (stale) {
      __threadfence();
#pragma unroll
      for (int i = 0; i < 64; i++) acc[i] = 0.f;
      const int row = warp * 16 + (lane >> 2);
#pragma unroll 1
      for (int k = 0; k < 1024; k += 2) {
        const uint8_t* src = g_xch[r * 8 + (k >> 7)] + ((k >> 6) & 1) * SLOT + row * 128 + ((((k >> 3) ^ row) & 7) << 4) + (k & 7) * 2;
        uint32_t a[2];
        int n = 0;
        do { a[0] = ld_relaxed(src); a[1] = ld_relaxed(src + 1024); } while (!all_arrived<2>(a) && ++n < kSpinLimit);
#pragma unroll 1
        for (int e = 0; e < 2; e++) {
          const float a0 = e ? bf_hi(a[0]) : bf_lo(a[0]), a1 = e ? bf_hi(a[1]) : bf_lo(a[1]);
          const uint32_t* wrow = reinterpret_cast<const uint32_t*>(P.wo_ptr + (k + e) * 1024 + 128 * j) + (lane & 3);
#pragma unroll
          for (int i = 0; i < 16; i++) {
            const uint32_t w = __ldg(wrow + 4 * i);
            acc[4 * i] += a0 * bf_lo(w); acc[4 * i + 1] += a0 * bf_hi(w);
            acc[4 * i + 2] += a1 * bf_lo(w); acc[4 * i + 3] += a1 * bf_hi(w);
          }
        }
      }
      uint32_t* op = reinterpret_cast<uint32_t*>(P.out_ptr + (128 * r + row) * 2048 + 128 * j) + (lane & 3);
#pragma unroll
      for (int i = 0; i < 32; i++) op[(i & 1) * 8192 + (i >> 1) * 4] = pack_bf16(acc[2 * i], acc[2 * i + 1]);
    }
  } else {
    asm volatile("setmaxnreg.dec.sync.aligned.u32 56;");
    if (warp == 8) {
      cluster_wait();
      cluster_arrive();
      LOOPSTAMP(3, tid == 256, 15);
#pragma unroll 1
      for (int it = 1; it < 4; it++) if (elect()) load_stage(it);
      LOOPSTAMP(3, tid == 256, 16);
      __syncwarp();
      cluster_wait();
    } else {
      if (elect()) {
#pragma unroll 1
        for (int g = warp - 9; g < 8; g += 3)
          for (int i = 0; i < 8; i++) mbar_init(bar(8 * g + i), 1u << ((BAR_LOG2 >> (4 * g)) & 7));
        if (warp == 11) for (int i = 0; i < 7; i++) mbar_expect(bar(B_H_FULL + i), i < 2 ? 12288 : i < 5 ? 8192 : i == 5 ? 16 : 16384);
        asm volatile("fence.mbarrier_init.release.cluster;" ::: "memory");
      }
      LOOPSTAMP(3, tid == 288, 14);
      __syncwarp();
      cluster_wait();
      cluster_arrive();
#pragma unroll
      for (int i = 0; i < 3; i++) asm volatile("st.shared.v4.b32 [%0], {%1,%1,%1,%1};" :: "r"(sb + SM_F1 + i * 1536 + (tid - 288) * 16), "r"(0xffffffffu) : "memory");
      fence_async_smem();
      asm volatile("bar.arrive 5, 128;" ::: "memory");
      if ((sb & 0xffffff) != SM_BASE) __trap();
      cluster_wait();
    }
    auto chunk = [&](int ks) { const int c = ks >= 9, t = ks - 2 - 7 * c; return ks < 2 ? 2 * j + ks : 2 * (t + (t >= j)) + c; };
    auto load_wo = [&](uint32_t dst, int c, uint32_t bytes, uint32_t fb) {
      mbar_expect(fb, bytes);
      tma2d_mc(dst + rho * 8192, &P.wo, 128 * j + 64 * rho, c * 64, fb);
    };
    uint8_t* const xch = g_xch[r * 8 + j];
    if (warp == 8) {
      int ck = 0, cw = 0, cph = 1;
      const CUtensorMap* kvmap = rho ? &P.v : &P.k;
#pragma unroll 1
      for (int it = 4 - XPF; it < 32 || (ck < 20 && it < kSpinLimit); ++it) {
        if (it >= 4 && it < 32) {
          mbar_wait(bar(B_QKV_EMPTY + (it & 3)), ((it >> 2) - 1) & 1);
          if (elect()) load_stage(it);
          LOOPSTAMP(3, lane == 0 && it < 12, 15 + it);
        }
        if (it < 32 - XPF) {
          if (((it + XPF) & 7) == rp && elect()) {
            l2_prefetch2d(&P.wk, 1024 + 128 * j + 64 * rho, 32 * (it + XPF));
            l2_prefetch3d(&P.w, 0, 32 * (it + XPF), 32 * rho + 2 * j);
          }
          if (((it + XPF) & 7) == j && elect()) l2_prefetch2d(&P.x, 32 * (it + XPF), 128 * r);
        }
        const int n = it - HSTART;
        if (n >= 0 && n < 8) {
          if (elect()) bulk_load(sb + SM_SIG + n * 8192 + 4096, P.ssm_k + (size_t)(cta * 8 + n) * 2048, 4096, bar(B_H_FULL + (n >= 3) + (n >= 6)));
        } else if (n >= 8 && n < 19) {
          if (n == 8) bar_sync(5, 128);
          if (elect()) bulk_store(xch + (n - 8) * 4096, sb + SM_F1, 4096);
        } else if (it >= PF0 && it < PF0 + 4) {
          if (elect()) l2_prefetch(it < PF0 + 2 ? P.wo_ptr + cta * 8192 + (it - PF0) * 4096 : P.q_ptr + (512 + (it - PF0 - 2) * 1024 + cta * 4) * 1024, 8192);
        }
        if (ck < 16 && it >= PSTART && __all_sync(0xffffffffu, mbar_test(bar(B_PREP_EMPTY + cw), cph))) {
          if (elect()) {
            mbar_expect(bar(B_PREP_FULL + cw), 8704);
            tma3d_mc(sb + SM_STG + cw * 8704 + rho * 4608, kvmap, cl * 16, ck * 8 - 1 + rho, 0, bar(B_PREP_FULL + cw));
          }
          ++ck;
          if (++cw == 3) { cw = 0; cph ^= 1; }
        } else if (ck >= 16 && ck < 20 && __all_sync(0xffffffffu, mbar_test(bar(B_STG_FREE), 0))) {
          if (elect()) tma2d(sb + SM_Q + (ck - 16) * 4096, &P.q, cl * 16, rho * 1024 + (ck - 16) * 128, bar(B_Q_FULL));
          ++ck;
        }
      }
      if (elect()) {
        bulk_commit();
        bulk_wait_read();
        mbar_expect(bar(B_SIG_READY), 10240);
        bulk_load(sb + SM_TW, g_tables, 10240, bar(B_SIG_READY));
        TSTAMP(true, 9);
        flag_add(&g_ready);
        TSTAMP(true, 10);
        prefetch_map(&P.wo); prefetch_map(&P.outa);
        const unsigned epoch = ld_relaxed(&g_epoch[cta]) + 1;
        g_epoch[cta] = epoch;
        flag_wait(&g_ready, kCtas * epoch);
        mbar_arrive(bar(B_ZEROED));
        TSTAMP(true, 11);
      }
      __syncwarp();
      mbar_wait(bar(B_QKV_DONE), 0);
#pragma unroll 1
      for (int ks = 0; ks < 4; ++ks) if (elect()) load_wo(sb + (4 + ks) * SLOT, chunk(ks), ks < 2 ? SLOT : 2 * SLOT, bar(B_OUT_FULL + ks));
    } else {
      const int at = tid - 288, aw = warp - 9, ch0 = cta * 8;
      {
        const uint32_t stg = sb + SM_STG + aw * 8704, pf = bar(B_PREP_FULL + aw), pe = bar(B_PREP_EMPTY + aw);
        const uint4 wv = __ldg(reinterpret_cast<const uint4*>(P.shift_k + (ch0 + 2 * (lane & 3)) * 4));
        const float skip = __bfloat162float(P.ssm_d[ch0 + (lane & 7)]);
        const uint32_t w0 = __byte_perm(wv.x, wv.z, 0x5410), w1 = __byte_perm(wv.x, wv.z, 0x7632);
        const uint32_t w2 = __byte_perm(wv.y, wv.w, 0x5410), w3 = __byte_perm(wv.y, wv.w, 0x7632);
        auto swz32 = [](uint32_t a) { return a ^ ((a >> 3) & 16); };
        const uint32_t kl = (lane >> 3) * 288 + (lane & 7) * 32 + rho * 16;
        const uint32_t ka = stg + swz32(kl + 32), kh = stg + swz32(kl + 12 * 288), va = stg + 4608 + swz32(lane * 32 + rho * 16);
        const uint32_t ua = sb + SM_SIG + (lane & 7) * 8192 + (((lane >> 3) ^ (lane & 7)) << 4);
        if (at == 0) prefetch_map(&P.q);
        uint32_t eh = 0;
#pragma unroll 1
        for (int ck = aw, rd = 0; rd < 9; ck += 3, ++rd) {
          if (rd == 6) {
            bar_sync(4, 96);
            if (at == 64) mbar_arrive(bar(B_STG_FREE));
          }
          const int c = rd < 6 ? ck : ck - 18;
          if (c < 8) {
            uint32_t x[32], dst = sb + SM_SIG + c * 8192;
            if (rd < 6) {
              mbar_wait(bar(B_H_FULL + rd), 0);
#pragma unroll
              for (int i = 0; i < 8; i++) ldsm4(x + 4 * i, dst + 4096 + i * 512 + lane * 16);
              const float d = __shfl_sync(0xffffffffu, skip, c);
              if (lane == 0) x[0] = pack_bf16(bf_lo(x[0]) + d, bf_hi(x[0]));
              dst += 4096 + (lane >> 1) * 128 + ((((lane & 1) * 4) ^ ((lane >> 1) & 7)) << 4);
            } else {
#pragma unroll
              for (int i = 0; i < 8; i++) ldsm4_t(x + 4 * i, dst + i * 512 + ((lane ^ c) << 4));
              dst += (lane >> 4) * 1024 + (lane & 7) * 128 + ((((lane >> 1) & 4) ^ (lane & 7)) << 4);
            }
            const uint32_t e = normalize(x, dst);
            if (rd < 6) {
              eh |= e << (8 * rd);
            } else {
              const int f = min(max((int)(e + (eh & 255)) - 125, 0), 254);
              eh >>= 8;
              if (lane == 0) asm volatile("st.shared.b16 [%0], %1;" :: "r"(sb + SM_SC + rho * 16 + 2 * c), "h"((uint16_t)(f << 7)) : "memory");
            }
          }
          if (ck < 16) {
            mbar_wait(pf, rd & 1);
            uint32_t k[20], v[16];
            ldsm4(k, kh);
#pragma unroll
            for (int m = 0; m < 4; m++) { ldsm4(k + 4 + 4 * m, (ka ^ ((m & 1) << 4)) + m * 1152); ldsm4(v + 4 * m, va + m * 1024); }
            arrive_both(pe + ((k[3] | k[4] | k[8] | k[12] | k[16] | v[0] | v[4] | v[8] | v[12]) & P.zero), lane, ck < 13);
#pragma unroll
            for (int m = 0; m < 4; m++) {
              uint32_t u[4];
#pragma unroll
              for (int n = 0; n < 4; n++) {
                const uint32_t* kk = k + 4 + 4 * m + n;
                u[n] = bmul2(bfma2(kk[0], w0, bfma2(kk[-1], w1, bfma2(kk[-2], w2, bmul2(kk[-3], w3)))), v[4 * m + n]);
              }
              stsm4_t((ua ^ (m << 6)) + ck * 256, u[0], u[1], u[2], u[3]);
            }
          }
        }
        fence_async_smem();
        __syncwarp();
        if (lane == 0) mbar_arrive(bar(B_SIG_READY));
        bar_sync(4, 96);
        if (at == 32) {
          const uint4 s = lds128(sb + SM_SC + rho * 16);
          asm volatile("st.async.weak.shared::cluster.mbarrier::complete_tx::bytes.v4.b32 [%0], {%1,%2,%3,%4}, [%5];"
                       :: "r"(peer_addr(sb + SM_SC + rho * 16, rho ^ 1)), "r"(s.x), "r"(s.y), "r"(s.z), "r"(s.w), "r"(peer_addr(bar(B_RDY0), rho ^ 1)) : "memory");
        }
        TSTAMP(at == 0, 20);
      }
    }
    __syncwarp();
    {
      const int a4 = warp - 8;
      const uint8_t* part = xch + 2 * SLOT + (lane >> 3) * 4 * KV_SLICE + (a4 * 8 + (lane & 7)) * 16;
      const uint8_t* zpart = xch + 2 * SLOT + (lane & 15) * KV_SLICE + 512 + (a4 * 2 + (lane >> 4)) * 4;
      uint8_t* red = xch + 2 * SLOT + 16 * KV_SLICE + (a4 * 8 + (lane & 7)) * 16 + (lane >> 3) * 4;
      uint8_t* zred = xch + 2 * SLOT + 16 * KV_SLICE + 512 + (a4 * 2 + (lane >> 4)) * 4;
      const uint8_t* all = g_xch[a4 * 32 + j] + 2 * SLOT + 16 * KV_SLICE + lane * 16;
      const uint8_t* zall = all + 512 + (lane & 28) - lane * 16;
      keep(part); keep(zpart); keep(red); keep(zred); keep(all); keep(zall);
      uint32_t v[20];
      int n = 0;
      mbar_wait(bar(B_KVP), 0);
      delay(PD1);
      auto load1 = [&](uint32_t* d) {
#pragma unroll
        for (int i = 0; i < 4; i++) ld_relaxed4(d + 4 * i, part + i * KV_SLICE);
        d[16] = ld_relaxed(zpart);
      };
      do load1(v); while (!all_arrived<17>(v) && ++n < kSpinLimit);
      TSTAMP(tid == 288, 21);
      float lo[4], hi[4], z = __uint_as_float(v[16]);
#pragma unroll
      for (int b = 0; b < 4; b++) {
        lo[b] = (bf_lo(v[b]) + bf_lo(v[4 + b])) + (bf_lo(v[8 + b]) + bf_lo(v[12 + b]));
        hi[b] = (bf_hi(v[b]) + bf_hi(v[4 + b])) + (bf_hi(v[8 + b]) + bf_hi(v[12 + b]));
      }
      const bool u16 = lane & 16, u8 = lane & 8;
#pragma unroll
      for (int b = 0; b < 2; b++) {
        lo[b] = (u16 ? lo[b + 2] : lo[b]) + __shfl_xor_sync(0xffffffffu, u16 ? lo[b] : lo[b + 2], 16);
        hi[b] = (u16 ? hi[b + 2] : hi[b]) + __shfl_xor_sync(0xffffffffu, u16 ? hi[b] : hi[b + 2], 16);
      }
      const float l = (u8 ? lo[1] : lo[0]) + __shfl_xor_sync(0xffffffffu, u8 ? lo[0] : lo[1], 8);
      const float h = (u8 ? hi[1] : hi[0]) + __shfl_xor_sync(0xffffffffu, u8 ? hi[0] : hi[1], 8);
      st_relaxed(red, pack_bf16(l, h));
#pragma unroll
      for (int o = 8; o; o >>= 1) z += __shfl_xor_sync(0xffffffffu, z, o);
      if ((lane & 15) == 0) st_relaxed(zred, pack_bf16(z, z));
      TSTAMP(tid == 288, 22);
      n = 0;
      delay(PD2);
      auto load2 = [&](uint32_t* d) {
#pragma unroll
        for (int i = 0; i < 4; i++) {
          ld_relaxed4(d + 4 * i, all + i * 8 * XCH_BYTES);
          d[16 + i] = ld_relaxed(zall + i * 8 * XCH_BYTES);
        }
      };
      do load2(v); while (!all_arrived<20>(v) && ++n < kSpinLimit);
#pragma unroll
      for (int i = 0; i < 4; i++) {
        const uint32_t dst = sb + SM_KV + (a4 * 4 + i) * 640;
        stsm4(dst + lane * 16, v[4 * i], v[4 * i + 1], v[4 * i + 2], v[4 * i + 3]);
        asm volatile("st.shared.b32 [%0], %1;" :: "r"(dst + 512 + lane * 4), "r"(v[16 + i]) : "memory");
      }
      fence_async_smem();
      __syncwarp();
      if (lane == 0) mbar_arrive(bar(B_KV_READY + (a4 >> 1)));
      TSTAMP(tid == 288, 23);
    }
    if (warp != 10) cluster_arrive();
    if (warp == 8) {
      int s = 4;
      uint32_t ph = 1;
#pragma unroll 1
      for (int ks = 4; ks < 16; ++ks) {
        uint32_t fb = bar(B_OUT_FULL + s), dst = sb + ((B_SLOTS >> (4 * s)) & 15) * SLOT;
        int c = chunk(ks);
        keep(fb); keep(dst); keep(c);
        mbar_wait(bar(ks == 4 ? B_RDY1 : B_OUT_EMPTY + s), ks == 4 ? 0 : ph);
        if (elect()) load_wo(dst, c, 2 * SLOT, fb);
        if (++s == 5) { s = 0; ph ^= 1; }
      }
    } else {
      auto wait_chunks = [&](unsigned mask) {
        unsigned ready;
        int n = 0;
        do {
          ready = __ballot_sync(0xffffffffu, ld_relaxed(g_xch[r * 8 + ((lane >> 1) & 7)] + XCH_FLAG) + 1 > (lane & 1));
        } while ((~ready & mask) && ++n < kSpinLimit);
        return ready;
      };
      if (warp == 9) {
        if (elect()) {
#pragma unroll 1
          for (int c = 0; c < 2; c++) {
            mbar_wait(bar(B_O_WRITTEN + c), 0);
            TSTAMP(c == 0, 19);
            fence_async_smem();
            bulk_store(xch + c * SLOT, sb + c * SLOT, SLOT);
            bulk_commit();
            bulk_wait_read();
            mbar_arrive(bar(B_OT_FREE + c));
            delay(FDELAY);
            st_relaxed(xch + XCH_FLAG, c);
            if (!c) delay(C1DELAY);
            TSTAMP(c == 1, 25);
          }
        }
        __syncwarp();
        wait_chunks(0xaaaa);
        if (lane == 0) mbar_arrive(bar(B_FLAGS1));
      } else if (warp == 10) {
        mbar_wait(bar(B_Q_FULL), 0);
        mbar_wait(bar(B_RDY0), 0);
        mbar_wait(bar(B_QKV_DONE), 0);
#pragma unroll 1
        for (int n = 0; n < 4; n++) {
          const int w = n & 1;
          mbar_wait(bar(B_SEG + n), 0);
          fence_async_smem();
          if (elect()) bulk_to_peer(sb + (n < 2 ? SM_Y0 : SM_SIG) + w * 8192 + 4096, sb + SM_YT + w * 4096, 4096, bar(B_YIN + (n >> 1)), rho ^ 1);
          if (w) {
            mbar_wait(bar(B_YIN + (n >> 1)), 0);
            if (lane == 0) asm volatile("mbarrier.arrive.shared::cluster.b64 _, [%0];" :: "r"(n < 2 ? peer_addr(bar(B_RDY1), rho ^ 1) : bar(B_Y_READY)) : "memory");
          }
        }
        __syncwarp();
        cluster_arrive();
        TSTAMP(lane == 0, 26);
      } else {
        mbar_wait(bar(B_OUT_FULL), 0);
        mbar_wait(bar(B_OUT_FULL + 1), 0);
        mbar_wait(bar(B_O_WRITTEN), 0);
        delay(PD3);
        unsigned ready = 0;
        int s = 2;
        uint32_t ph = 1;
#pragma unroll 1
        for (int ks = 2; ks < 16; ++ks) {
          const int c = chunk(ks);
          uint32_t fb = bar(B_OUT_FULL + s), dst = sb + ((A_SLOTS >> (4 * s)) & 15) * SLOT;
          uint8_t* src = g_xch[r * 8 + (c >> 1)] + (c & 1) * SLOT;
          keep(fb); keep(dst); keep(src);
          if (ks < 5 || ks == 9) {
            const unsigned need = ks < 4 ? 1u << c : 0x5555u;
            if (ks == 9) mbar_wait(bar(B_FLAGS1), 0);
            else if (~ready & need) ready = wait_chunks(need);
          }
          constexpr uint64_t kFirst = (B_O_WRITTEN + 1) | B_OT_FREE << 8 | B_SLOT_FREE << 16 | (B_OT_FREE + 1) << 24 | (uint64_t)B_CONV_DONE << 32;
          mbar_wait(bar(ks < 7 ? (int)(kFirst >> (8 * ks - 16)) & 255 : B_OUT_EMPTY + s), ks < 7 ? ks == 4 : ph);
          if (ks == 4 || ks == 6) fence_async_smem();
          if (elect()) bulk_load(dst, src, SLOT, fb);
          TSTAMP(ks == 2 && lane == 0, 18); LOOPSTAMP(2, lane == 0, 11 + ks);
          if (++s == 5) { s = 0; ph ^= 1; }
        }
      }
    }
    if (warp == 9 || warp == 10) {
      const int yc = (lane & 1) + ((lane >> 2) & 2) + (lane & 2) * 2, ysrc = (lane >> 2) & 1;
      const uint32_t ya = sb + (yc & 4 ? SM_SIG : SM_Y0) + (yc & 1) * 8192 + (yc & 2) * 1024 + (ysrc ^ rho) * 4096 +
                          (lane >> 4) * 128 + ((yc ^ (2 * ysrc)) << 4);
      uint32_t s0, s1;
      mbar_wait(bar(B_Y_READY), 0);
      asm volatile("ld.shared.v2.b32 {%0,%1}, [%2];" : "=r"(s0), "=r"(s1) : "r"(sb + SM_SC + (lane & 3) * 8) : "memory");
#pragma unroll 1
      for (int n = warp - 9; n < 8; n += 2) {
        __nv_bfloat16* op = P.out_ptr + (rho * 1024 + n * 128 + (lane >> 2)) * 2048 + 1024 + cl * 16 + (lane & 3) * 4;
        const uint32_t qa = sb + SM_Q + (n & 3) * 4096 + lane * 8;
        asm volatile("cp.async.wait_group 1;" ::: "memory");
        __syncwarp();
#pragma unroll 1
        for (int u0 = 0; u0 < 8; u0 += 2) {
          uint32_t y[2][4], q[2][4];
#pragma unroll
          for (int u = 0; u < 2; u++) {
            ldsm4_t(y[u], (ya ^ ((u0 + u) << 4)) + n * 256);
#pragma unroll
            for (int m = 0; m < 2; m++)
              asm volatile("ld.shared.v2.b32 {%0,%1}, [%2];" : "=r"(q[u][2 * m]), "=r"(q[u][2 * m + 1]) : "r"(qa + (u0 + u) * 512 + m * 256) : "memory");
          }
#pragma unroll
          for (int u = 0; u < 2; u++)
#pragma unroll
            for (int m = 0; m < 2; m++)
              asm volatile("st.global.v2.b32 [%0], {%1,%2};" :: "l"(op + (u * 16 + m * 8) * 2048),
                           "r"(bmul2(q[u][2 * m], bmul2(y[u][2 * m], s0))), "r"(bmul2(q[u][2 * m + 1], bmul2(y[u][2 * m + 1], s1))) : "memory");
          op += 32 * 2048;
        }
        __syncwarp();
        if (n < 4) {
          const __nv_bfloat16* qp = P.q_ptr + (rho * 1024 + n * 128 + 512 + (lane >> 1)) * 1024 + cl * 16 + (lane & 1) * 8;
#pragma unroll
          for (int i = 0; i < 8; i++)
            asm volatile("cp.async.cg.shared.global [%0], [%1], 16;" :: "r"(qa + lane * 8 + i * 512), "l"(qp + i * 16384) : "memory");
        }
        asm volatile("cp.async.commit_group;" ::: "memory");
      }
      TSTAMP(tid == 320, 24);
    }
    __syncwarp();
    cluster_wait();
  }
}

typedef CUresult (*EncodeFn)(CUtensorMap*, CUtensorMapDataType, cuuint32_t, void*, const cuuint64_t*, const cuuint64_t*,
                             const cuuint32_t*, const cuuint32_t*, CUtensorMapInterleave, CUtensorMapSwizzle,
                             CUtensorMapL2promotion, CUtensorMapFloatOOBfill);

void encode(EncodeFn fn, CUtensorMap* m, const void* p, int rank, const cuuint64_t* dims, const cuuint64_t* strides,
            const cuuint32_t* box, CUtensorMapSwizzle sw) {
  const cuuint32_t es[3] = {1, 1, 1};
  fn(m, CU_TENSOR_MAP_DATA_TYPE_BFLOAT16, rank, const_cast<void*>(p), dims, strides, box, es, CU_TENSOR_MAP_INTERLEAVE_NONE, sw,
     CU_TENSOR_MAP_L2_PROMOTION_NONE, CU_TENSOR_MAP_FLOAT_OOB_FILL_NONE);
}
void encode2d(EncodeFn fn, CUtensorMap* m, const void* p, uint64_t cols, uint64_t rows, uint32_t bc, uint32_t br, CUtensorMapSwizzle sw) {
  const cuuint64_t dims[2] = {cols, rows}, strides[1] = {cols * 2};
  const cuuint32_t box[2] = {bc, br};
  encode(fn, m, p, 2, dims, strides, box, sw);
}
void encode3d(EncodeFn fn, CUtensorMap* m, const void* p, uint32_t nblk) {
  const cuuint64_t dims[3] = {1024, 128, 16}, strides[2] = {2048 * 16, 2048};
  const cuuint32_t box[3] = {16, nblk, 16};
  encode(fn, m, p, 3, dims, strides, box, CU_TENSOR_MAP_SWIZZLE_32B);
}

}

extern "C" void kernel_launch(void* const* d_in, const int* in_sizes, int n_in, void* d_out, int out_size) {
  static EncodeFn fn = nullptr;
  if (!fn) {
    cudaDriverEntryPointQueryResult qr;
    cudaGetDriverEntryPoint("cuTensorMapEncodeTiled", (void**)&fn, cudaEnableDefault, &qr);
    cudaFuncSetAttribute(fused_kernel, cudaFuncAttributeMaxDynamicSharedMemorySize, SM_TOTAL);
  }
  Params P;
  encode2d(fn, &P.x, d_in[0], 1024, 2048, 32, 128, CU_TENSOR_MAP_SWIZZLE_64B);
  {
    const cuuint64_t dims[3] = {64, 1024, 48}, strides[2] = {6144, 128};
    const cuuint32_t box[3] = {64, 32, 2};
    encode(fn, &P.w, d_in[1], 3, dims, strides, box, CU_TENSOR_MAP_SWIZZLE_128B);
  }
  encode2d(fn, &P.wk, d_in[1], 3072, 1024, 64, 32, CU_TENSOR_MAP_SWIZZLE_128B);
  encode2d(fn, &P.wo, d_in[2], 1024, 1024, 64, 64, CU_TENSOR_MAP_SWIZZLE_128B);
  encode2d(fn, &P.outa, d_out, 2048, 2048, 64, 16, CU_TENSOR_MAP_SWIZZLE_128B);
  encode3d(fn, &P.k, d_in[4], 9);
  encode3d(fn, &P.v, d_in[5], 8);
  encode2d(fn, &P.q, d_in[3], 1024, 2048, 16, 128, CU_TENSOR_MAP_SWIZZLE_NONE);
  P.shift_k = (const __nv_bfloat16*)d_in[6];
  P.ssm_k = (const __nv_bfloat16*)d_in[7];
  P.ssm_d = (const __nv_bfloat16*)d_in[8];
  P.zero = 0;
  P.q_ptr = (const __nv_bfloat16*)d_in[3];
  P.out_ptr = (__nv_bfloat16*)d_out;
  P.wo_ptr = (const __nv_bfloat16*)d_in[2];
  fused_kernel<<<kCtas, kThreads, SM_TOTAL>>>(P);
}
```

```cpp
#include <cuda.h>
#include <cuda_runtime.h>
#include <cuda_bf16.h>
#include <stdint.h>

#define DEVI __device__ __forceinline__

namespace {

DEVI void mma_nt(float* d, uint64_t da, uint64_t db) {
  asm volatile("wgmma.mma_async.sync.aligned.m64n128k16.f32.bf16.bf16 {%0, %1, %2, %3, %4, %5, %6, %7, %8, %9, %10, %11, %12, %13, %14, %15, %16, %17, %18, %19, %20, %21, %22, %23, %24, %25, %26, %27, %28, %29, %30, %31, %32, %33, %34, %35, %36, %37, %38, %39, %40, %41, %42, %43, %44, %45, %46, %47, %48, %49, %50, %51, %52, %53, %54, %55, %56, %57, %58, %59, %60, %61, %62, %63}, %64, %65, 1, 1, 1, 0, 1;\n"
    : "+f"(d[0]), "+f"(d[1]), "+f"(d[2]), "+f"(d[3]), "+f"(d[4]), "+f"(d[5]), "+f"(d[6]), "+f"(d[7]), "+f"(d[8]), "+f"(d[9]), "+f"(d[10]), "+f"(d[11]), "+f"(d[12]), "+f"(d[13]), "+f"(d[14]), "+f"(d[15]), "+f"(d[16]), "+f"(d[17]), "+f"(d[18]), "+f"(d[19]), "+f"(d[20]), "+f"(d[21]), "+f"(d[22]), "+f"(d[23]), "+f"(d[24]), "+f"(d[25]), "+f"(d[26]), "+f"(d[27]), "+f"(d[28]), "+f"(d[29]), "+f"(d[30]), "+f"(d[31]), "+f"(d[32]), "+f"(d[33]), "+f"(d[34]), "+f"(d[35]), "+f"(d[36]), "+f"(d[37]), "+f"(d[38]), "+f"(d[39]), "+f"(d[40]), "+f"(d[41]), "+f"(d[42]), "+f"(d[43]), "+f"(d[44]), "+f"(d[45]), "+f"(d[46]), "+f"(d[47]), "+f"(d[48]), "+f"(d[49]), "+f"(d[50]), "+f"(d[51]), "+f"(d[52]), "+f"(d[53]), "+f"(d[54]), "+f"(d[55]), "+f"(d[56]), "+f"(d[57]), "+f"(d[58]), "+f"(d[59]), "+f"(d[60]), "+f"(d[61]), "+f"(d[62]), "+f"(d[63])
    : "l"(da), "l"(db));
}
DEVI void mma_tn(float* d, uint64_t da, uint64_t db) {
  asm volatile("wgmma.mma_async.sync.aligned.m64n128k16.f32.bf16.bf16 {%0, %1, %2, %3, %4, %5, %6, %7, %8, %9, %10, %11, %12, %13, %14, %15, %16, %17, %18, %19, %20, %21, %22, %23, %24, %25, %26, %27, %28, %29, %30, %31, %32, %33, %34, %35, %36, %37, %38, %39, %40, %41, %42, %43, %44, %45, %46, %47, %48, %49, %50, %51, %52, %53, %54, %55, %56, %57, %58, %59, %60, %61, %62, %63}, %64, %65, 1, 1, 1, 1, 0;\n"
    : "+f"(d[0]), "+f"(d[1]), "+f"(d[2]), "+f"(d[3]), "+f"(d[4]), "+f"(d[5]), "+f"(d[6]), "+f"(d[7]), "+f"(d[8]), "+f"(d[9]), "+f"(d[10]), "+f"(d[11]), "+f"(d[12]), "+f"(d[13]), "+f"(d[14]), "+f"(d[15]), "+f"(d[16]), "+f"(d[17]), "+f"(d[18]), "+f"(d[19]), "+f"(d[20]), "+f"(d[21]), "+f"(d[22]), "+f"(d[23]), "+f"(d[24]), "+f"(d[25]), "+f"(d[26]), "+f"(d[27]), "+f"(d[28]), "+f"(d[29]), "+f"(d[30]), "+f"(d[31]), "+f"(d[32]), "+f"(d[33]), "+f"(d[34]), "+f"(d[35]), "+f"(d[36]), "+f"(d[37]), "+f"(d[38]), "+f"(d[39]), "+f"(d[40]), "+f"(d[41]), "+f"(d[42]), "+f"(d[43]), "+f"(d[44]), "+f"(d[45]), "+f"(d[46]), "+f"(d[47]), "+f"(d[48]), "+f"(d[49]), "+f"(d[50]), "+f"(d[51]), "+f"(d[52]), "+f"(d[53]), "+f"(d[54]), "+f"(d[55]), "+f"(d[56]), "+f"(d[57]), "+f"(d[58]), "+f"(d[59]), "+f"(d[60]), "+f"(d[61]), "+f"(d[62]), "+f"(d[63])
    : "l"(da), "l"(db));
}
DEVI void mma_own_init(float* d, uint32_t a0, uint32_t a1, uint32_t a2, uint32_t a3, uint64_t db) {
  asm volatile("wgmma.mma_async.sync.aligned.m64n128k16.f32.bf16.bf16 {%0, %1, %2, %3, %4, %5, %6, %7, %8, %9, %10, %11, %12, %13, %14, %15, %16, %17, %18, %19, %20, %21, %22, %23, %24, %25, %26, %27, %28, %29, %30, %31, %32, %33, %34, %35, %36, %37, %38, %39, %40, %41, %42, %43, %44, %45, %46, %47, %48, %49, %50, %51, %52, %53, %54, %55, %56, %57, %58, %59, %60, %61, %62, %63}, {%64,%65,%66,%67}, %68, 0, 1, 1, 1;\n"
    : "=f"(d[0]), "=f"(d[1]), "=f"(d[2]), "=f"(d[3]), "=f"(d[4]), "=f"(d[5]), "=f"(d[6]), "=f"(d[7]), "=f"(d[8]), "=f"(d[9]), "=f"(d[10]), "=f"(d[11]), "=f"(d[12]), "=f"(d[13]), "=f"(d[14]), "=f"(d[15]), "=f"(d[16]), "=f"(d[17]), "=f"(d[18]), "=f"(d[19]), "=f"(d[20]), "=f"(d[21]), "=f"(d[22]), "=f"(d[23]), "=f"(d[24]), "=f"(d[25]), "=f"(d[26]), "=f"(d[27]), "=f"(d[28]), "=f"(d[29]), "=f"(d[30]), "=f"(d[31]), "=f"(d[32]), "=f"(d[33]), "=f"(d[34]), "=f"(d[35]), "=f"(d[36]), "=f"(d[37]), "=f"(d[38]), "=f"(d[39]), "=f"(d[40]), "=f"(d[41]), "=f"(d[42]), "=f"(d[43]), "=f"(d[44]), "=f"(d[45]), "=f"(d[46]), "=f"(d[47]), "=f"(d[48]), "=f"(d[49]), "=f"(d[50]), "=f"(d[51]), "=f"(d[52]), "=f"(d[53]), "=f"(d[54]), "=f"(d[55]), "=f"(d[56]), "=f"(d[57]), "=f"(d[58]), "=f"(d[59]), "=f"(d[60]), "=f"(d[61]), "=f"(d[62]), "=f"(d[63])
    : "r"(a0), "r"(a1), "r"(a2), "r"(a3), "l"(db));
}
DEVI void mma_own_acc(float* d, uint32_t a0, uint32_t a1, uint32_t a2, uint32_t a3, uint64_t db) {
  asm volatile("wgmma.mma_async.sync.aligned.m64n128k16.f32.bf16.bf16 {%0, %1, %2, %3, %4, %5, %6, %7, %8, %9, %10, %11, %12, %13, %14, %15, %16, %17, %18, %19, %20, %21, %22, %23, %24, %25, %26, %27, %28, %29, %30, %31, %32, %33, %34, %35, %36, %37, %38, %39, %40, %41, %42, %43, %44, %45, %46, %47, %48, %49, %50, %51, %52, %53, %54, %55, %56, %57, %58, %59, %60, %61, %62, %63}, {%64,%65,%66,%67}, %68, 1, 1, 1, 1;\n"
    : "+f"(d[0]), "+f"(d[1]), "+f"(d[2]), "+f"(d[3]), "+f"(d[4]), "+f"(d[5]), "+f"(d[6]), "+f"(d[7]), "+f"(d[8]), "+f"(d[9]), "+f"(d[10]), "+f"(d[11]), "+f"(d[12]), "+f"(d[13]), "+f"(d[14]), "+f"(d[15]), "+f"(d[16]), "+f"(d[17]), "+f"(d[18]), "+f"(d[19]), "+f"(d[20]), "+f"(d[21]), "+f"(d[22]), "+f"(d[23]), "+f"(d[24]), "+f"(d[25]), "+f"(d[26]), "+f"(d[27]), "+f"(d[28]), "+f"(d[29]), "+f"(d[30]), "+f"(d[31]), "+f"(d[32]), "+f"(d[33]), "+f"(d[34]), "+f"(d[35]), "+f"(d[36]), "+f"(d[37]), "+f"(d[38]), "+f"(d[39]), "+f"(d[40]), "+f"(d[41]), "+f"(d[42]), "+f"(d[43]), "+f"(d[44]), "+f"(d[45]), "+f"(d[46]), "+f"(d[47]), "+f"(d[48]), "+f"(d[49]), "+f"(d[50]), "+f"(d[51]), "+f"(d[52]), "+f"(d[53]), "+f"(d[54]), "+f"(d[55]), "+f"(d[56]), "+f"(d[57]), "+f"(d[58]), "+f"(d[59]), "+f"(d[60]), "+f"(d[61]), "+f"(d[62]), "+f"(d[63])
    : "r"(a0), "r"(a1), "r"(a2), "r"(a3), "l"(db));
}
DEVI void mma_nt256(float* d, uint64_t da, uint64_t db) {
  asm volatile("wgmma.mma_async.sync.aligned.m64n256k16.f32.bf16.bf16 {%0, %1, %2, %3, %4, %5, %6, %7, %8, %9, %10, %11, %12, %13, %14, %15, %16, %17, %18, %19, %20, %21, %22, %23, %24, %25, %26, %27, %28, %29, %30, %31, %32, %33, %34, %35, %36, %37, %38, %39, %40, %41, %42, %43, %44, %45, %46, %47, %48, %49, %50, %51, %52, %53, %54, %55, %56, %57, %58, %59, %60, %61, %62, %63, %64, %65, %66, %67, %68, %69, %70, %71, %72, %73, %74, %75, %76, %77, %78, %79, %80, %81, %82, %83, %84, %85, %86, %87, %88, %89, %90, %91, %92, %93, %94, %95, %96, %97, %98, %99, %100, %101, %102, %103, %104, %105, %106, %107, %108, %109, %110, %111, %112, %113, %114, %115, %116, %117, %118, %119, %120, %121, %122, %123, %124, %125, %126, %127}, %128, %129, 1, 1, 1, 0, 1;\n"
    : "+f"(d[0]), "+f"(d[1]), "+f"(d[2]), "+f"(d[3]), "+f"(d[4]), "+f"(d[5]), "+f"(d[6]), "+f"(d[7]), "+f"(d[8]), "+f"(d[9]), "+f"(d[10]), "+f"(d[11]), "+f"(d[12]), "+f"(d[13]), "+f"(d[14]), "+f"(d[15]), "+f"(d[16]), "+f"(d[17]), "+f"(d[18]), "+f"(d[19]), "+f"(d[20]), "+f"(d[21]), "+f"(d[22]), "+f"(d[23]), "+f"(d[24]), "+f"(d[25]), "+f"(d[26]), "+f"(d[27]), "+f"(d[28]), "+f"(d[29]), "+f"(d[30]), "+f"(d[31]), "+f"(d[32]), "+f"(d[33]), "+f"(d[34]), "+f"(d[35]), "+f"(d[36]), "+f"(d[37]), "+f"(d[38]), "+f"(d[39]), "+f"(d[40]), "+f"(d[41]), "+f"(d[42]), "+f"(d[43]), "+f"(d[44]), "+f"(d[45]), "+f"(d[46]), "+f"(d[47]), "+f"(d[48]), "+f"(d[49]), "+f"(d[50]), "+f"(d[51]), "+f"(d[52]), "+f"(d[53]), "+f"(d[54]), "+f"(d[55]), "+f"(d[56]), "+f"(d[57]), "+f"(d[58]), "+f"(d[59]), "+f"(d[60]), "+f"(d[61]), "+f"(d[62]), "+f"(d[63]), "+f"(d[64]), "+f"(d[65]), "+f"(d[66]), "+f"(d[67]), "+f"(d[68]), "+f"(d[69]), "+f"(d[70]), "+f"(d[71]), "+f"(d[72]), "+f"(d[73]), "+f"(d[74]), "+f"(d[75]), "+f"(d[76]), "+f"(d[77]), "+f"(d[78]), "+f"(d[79]), "+f"(d[80]), "+f"(d[81]), "+f"(d[82]), "+f"(d[83]), "+f"(d[84]), "+f"(d[85]), "+f"(d[86]), "+f"(d[87]), "+f"(d[88]), "+f"(d[89]), "+f"(d[90]), "+f"(d[91]), "+f"(d[92]), "+f"(d[93]), "+f"(d[94]), "+f"(d[95]), "+f"(d[96]), "+f"(d[97]), "+f"(d[98]), "+f"(d[99]), "+f"(d[100]), "+f"(d[101]), "+f"(d[102]), "+f"(d[103]), "+f"(d[104]), "+f"(d[105]), "+f"(d[106]), "+f"(d[107]), "+f"(d[108]), "+f"(d[109]), "+f"(d[110]), "+f"(d[111]), "+f"(d[112]), "+f"(d[113]), "+f"(d[114]), "+f"(d[115]), "+f"(d[116]), "+f"(d[117]), "+f"(d[118]), "+f"(d[119]), "+f"(d[120]), "+f"(d[121]), "+f"(d[122]), "+f"(d[123]), "+f"(d[124]), "+f"(d[125]), "+f"(d[126]), "+f"(d[127])
    : "l"(da), "l"(db));
}
DEVI void mma_kv_init(float* d, uint32_t a0, uint32_t a1, uint32_t a2, uint32_t a3, uint64_t db) {
  asm volatile("wgmma.mma_async.sync.aligned.m64n72k16.f32.bf16.bf16 {%0, %1, %2, %3, %4, %5, %6, %7, %8, %9, %10, %11, %12, %13, %14, %15, %16, %17, %18, %19, %20, %21, %22, %23, %24, %25, %26, %27, %28, %29, %30, %31, %32, %33, %34, %35}, {%36,%37,%38,%39}, %40, 0, 1, 1, 1;\n"
    : "=f"(d[0]), "=f"(d[1]), "=f"(d[2]), "=f"(d[3]), "=f"(d[4]), "=f"(d[5]), "=f"(d[6]), "=f"(d[7]), "=f"(d[8]), "=f"(d[9]), "=f"(d[10]), "=f"(d[11]), "=f"(d[12]), "=f"(d[13]), "=f"(d[14]), "=f"(d[15]), "=f"(d[16]), "=f"(d[17]), "=f"(d[18]), "=f"(d[19]), "=f"(d[20]), "=f"(d[21]), "=f"(d[22]), "=f"(d[23]), "=f"(d[24]), "=f"(d[25]), "=f"(d[26]), "=f"(d[27]), "=f"(d[28]), "=f"(d[29]), "=f"(d[30]), "=f"(d[31]), "=f"(d[32]), "=f"(d[33]), "=f"(d[34]), "=f"(d[35])
    : "r"(a0), "r"(a1), "r"(a2), "r"(a3), "l"(db));
}
DEVI void mma_kv_acc(float* d, uint32_t a0, uint32_t a1, uint32_t a2, uint32_t a3, uint64_t db) {
  asm volatile("wgmma.mma_async.sync.aligned.m64n72k16.f32.bf16.bf16 {%0, %1, %2, %3, %4, %5, %6, %7, %8, %9, %10, %11, %12, %13, %14, %15, %16, %17, %18, %19, %20, %21, %22, %23, %24, %25, %26, %27, %28, %29, %30, %31, %32, %33, %34, %35}, {%36,%37,%38,%39}, %40, 1, 1, 1, 1;\n"
    : "+f"(d[0]), "+f"(d[1]), "+f"(d[2]), "+f"(d[3]), "+f"(d[4]), "+f"(d[5]), "+f"(d[6]), "+f"(d[7]), "+f"(d[8]), "+f"(d[9]), "+f"(d[10]), "+f"(d[11]), "+f"(d[12]), "+f"(d[13]), "+f"(d[14]), "+f"(d[15]), "+f"(d[16]), "+f"(d[17]), "+f"(d[18]), "+f"(d[19]), "+f"(d[20]), "+f"(d[21]), "+f"(d[22]), "+f"(d[23]), "+f"(d[24]), "+f"(d[25]), "+f"(d[26]), "+f"(d[27]), "+f"(d[28]), "+f"(d[29]), "+f"(d[30]), "+f"(d[31]), "+f"(d[32]), "+f"(d[33]), "+f"(d[34]), "+f"(d[35])
    : "r"(a0), "r"(a1), "r"(a2), "r"(a3), "l"(db));
}
DEVI void mma_o_init(float* d, uint32_t a0, uint32_t a1, uint32_t a2, uint32_t a3, uint64_t db) {
  asm volatile("wgmma.mma_async.sync.aligned.m64n40k16.f32.bf16.bf16 {%0, %1, %2, %3, %4, %5, %6, %7, %8, %9, %10, %11, %12, %13, %14, %15, %16, %17, %18, %19}, {%20,%21,%22,%23}, %24, 0, 1, 1, 1;\n"
    : "=f"(d[0]), "=f"(d[1]), "=f"(d[2]), "=f"(d[3]), "=f"(d[4]), "=f"(d[5]), "=f"(d[6]), "=f"(d[7]), "=f"(d[8]), "=f"(d[9]), "=f"(d[10]), "=f"(d[11]), "=f"(d[12]), "=f"(d[13]), "=f"(d[14]), "=f"(d[15]), "=f"(d[16]), "=f"(d[17]), "=f"(d[18]), "=f"(d[19])
    : "r"(a0), "r"(a1), "r"(a2), "r"(a3), "l"(db));
}
DEVI void mma_o_acc(float* d, uint32_t a0, uint32_t a1, uint32_t a2, uint32_t a3, uint64_t db) {
  asm volatile("wgmma.mma_async.sync.aligned.m64n40k16.f32.bf16.bf16 {%0, %1, %2, %3, %4, %5, %6, %7, %8, %9, %10, %11, %12, %13, %14, %15, %16, %17, %18, %19}, {%20,%21,%22,%23}, %24, 1, 1, 1, 1;\n"
    : "+f"(d[0]), "+f"(d[1]), "+f"(d[2]), "+f"(d[3]), "+f"(d[4]), "+f"(d[5]), "+f"(d[6]), "+f"(d[7]), "+f"(d[8]), "+f"(d[9]), "+f"(d[10]), "+f"(d[11]), "+f"(d[12]), "+f"(d[13]), "+f"(d[14]), "+f"(d[15]), "+f"(d[16]), "+f"(d[17]), "+f"(d[18]), "+f"(d[19])
    : "r"(a0), "r"(a1), "r"(a2), "r"(a3), "l"(db));
}
DEVI void fft1_init(uint32_t* d, uint32_t a0, uint32_t a1, uint32_t a2, uint32_t a3, uint64_t db) {
  asm volatile("wgmma.mma_async.sync.aligned.m64n128k16.f16.f16.f16 {%0, %1, %2, %3, %4, %5, %6, %7, %8, %9, %10, %11, %12, %13, %14, %15, %16, %17, %18, %19, %20, %21, %22, %23, %24, %25, %26, %27, %28, %29, %30, %31}, {%32,%33,%34,%35}, %36, 0, 1, 1, 1;\n"
    : "=r"(d[0]), "=r"(d[1]), "=r"(d[2]), "=r"(d[3]), "=r"(d[4]), "=r"(d[5]), "=r"(d[6]), "=r"(d[7]), "=r"(d[8]), "=r"(d[9]), "=r"(d[10]), "=r"(d[11]), "=r"(d[12]), "=r"(d[13]), "=r"(d[14]), "=r"(d[15]), "=r"(d[16]), "=r"(d[17]), "=r"(d[18]), "=r"(d[19]), "=r"(d[20]), "=r"(d[21]), "=r"(d[22]), "=r"(d[23]), "=r"(d[24]), "=r"(d[25]), "=r"(d[26]), "=r"(d[27]), "=r"(d[28]), "=r"(d[29]), "=r"(d[30]), "=r"(d[31])
    : "r"(a0), "r"(a1), "r"(a2), "r"(a3), "l"(db));
}
DEVI void fft1_acc(uint32_t* d, uint32_t a0, uint32_t a1, uint32_t a2, uint32_t a3, uint64_t db) {
  asm volatile("wgmma.mma_async.sync.aligned.m64n128k16.f16.f16.f16 {%0, %1, %2, %3, %4, %5, %6, %7, %8, %9, %10, %11, %12, %13, %14, %15, %16, %17, %18, %19, %20, %21, %22, %23, %24, %25, %26, %27, %28, %29, %30, %31}, {%32,%33,%34,%35}, %36, 1, 1, 1, 1;\n"
    : "+r"(d[0]), "+r"(d[1]), "+r"(d[2]), "+r"(d[3]), "+r"(d[4]), "+r"(d[5]), "+r"(d[6]), "+r"(d[7]), "+r"(d[8]), "+r"(d[9]), "+r"(d[10]), "+r"(d[11]), "+r"(d[12]), "+r"(d[13]), "+r"(d[14]), "+r"(d[15]), "+r"(d[16]), "+r"(d[17]), "+r"(d[18]), "+r"(d[19]), "+r"(d[20]), "+r"(d[21]), "+r"(d[22]), "+r"(d[23]), "+r"(d[24]), "+r"(d[25]), "+r"(d[26]), "+r"(d[27]), "+r"(d[28]), "+r"(d[29]), "+r"(d[30]), "+r"(d[31])
    : "r"(a0), "r"(a1), "r"(a2), "r"(a3), "l"(db));
}
DEVI void fft2_init(uint32_t* d, uint32_t a0, uint32_t a1, uint32_t a2, uint32_t a3, uint64_t db) {
  asm volatile("wgmma.mma_async.sync.aligned.m64n32k16.f16.f16.f16 {%0, %1, %2, %3, %4, %5, %6, %7}, {%8,%9,%10,%11}, %12, 0, 1, 1, 0;\n"
    : "=r"(d[0]), "=r"(d[1]), "=r"(d[2]), "=r"(d[3]), "=r"(d[4]), "=r"(d[5]), "=r"(d[6]), "=r"(d[7])
    : "r"(a0), "r"(a1), "r"(a2), "r"(a3), "l"(db));
}
DEVI void fft2_acc(uint32_t* d, uint32_t a0, uint32_t a1, uint32_t a2, uint32_t a3, uint64_t db) {
  asm volatile("wgmma.mma_async.sync.aligned.m64n32k16.f16.f16.f16 {%0, %1, %2, %3, %4, %5, %6, %7}, {%8,%9,%10,%11}, %12, 1, 1, 1, 0;\n"
    : "+r"(d[0]), "+r"(d[1]), "+r"(d[2]), "+r"(d[3]), "+r"(d[4]), "+r"(d[5]), "+r"(d[6]), "+r"(d[7])
    : "r"(a0), "r"(a1), "r"(a2), "r"(a3), "l"(db));
}
DEVI void fft3_init(float* d, uint32_t a0, uint32_t a1, uint32_t a2, uint32_t a3, uint64_t db) {
  asm volatile("wgmma.mma_async.sync.aligned.m64n32k16.f32.f16.f16 {%0, %1, %2, %3, %4, %5, %6, %7, %8, %9, %10, %11, %12, %13, %14, %15}, {%16,%17,%18,%19}, %20, 0, 1, 1, 0;\n"
    : "=f"(d[0]), "=f"(d[1]), "=f"(d[2]), "=f"(d[3]), "=f"(d[4]), "=f"(d[5]), "=f"(d[6]), "=f"(d[7]), "=f"(d[8]), "=f"(d[9]), "=f"(d[10]), "=f"(d[11]), "=f"(d[12]), "=f"(d[13]), "=f"(d[14]), "=f"(d[15])
    : "r"(a0), "r"(a1), "r"(a2), "r"(a3), "l"(db));
}
DEVI void fft3_acc(float* d, uint32_t a0, uint32_t a1, uint32_t a2, uint32_t a3, uint64_t db) {
  asm volatile("wgmma.mma_async.sync.aligned.m64n32k16.f32.f16.f16 {%0, %1, %2, %3, %4, %5, %6, %7, %8, %9, %10, %11, %12, %13, %14, %15}, {%16,%17,%18,%19}, %20, 1, 1, 1, 0;\n"
    : "+f"(d[0]), "+f"(d[1]), "+f"(d[2]), "+f"(d[3]), "+f"(d[4]), "+f"(d[5]), "+f"(d[6]), "+f"(d[7]), "+f"(d[8]), "+f"(d[9]), "+f"(d[10]), "+f"(d[11]), "+f"(d[12]), "+f"(d[13]), "+f"(d[14]), "+f"(d[15])
    : "r"(a0), "r"(a1), "r"(a2), "r"(a3), "l"(db));
}

__device__ __align__(128) const uint32_t g_tables[2560] = {
0xa11ba1e4,0xa51ba5e4,0x18b61248,0x1cb61648,0x9f12a052,0xa311a452,0x1d7f1bdb,0x217f1fdb,0x9bdb9d7f,0x9fdba17f,0x20521f12,0x24522311,
0x924898b6,0x96489cb6,0x21e4211b,0x25e4251b,0xaa63ab5f,0xae5faf59,0x21e41bdb,0x25e41fdb,0xa86ba967,0xac6aad65,0x26e024e9,0x2ade28e8,
0xa4e9a6e0,0xa8e8aade,0x2967286b,0x2d652c6a,0x9bdba1e4,0x9fdba5e4,0x2b5f2a63,0x2f592e5f,0xadc2aea7,0xb1b6b294,0x254d1f12,0x294d2311,
0xabf6acde,0xafefb0d7,0x2a31286b,0x2e2d2c6a,0xa86baa31,0xac6aae2d,0x2cde2bf6,0x30d72fef,0x9f12a54d,0xa311a94d,0x2ea72dc2,0x329431b6,
0xb02cb0d2,0xb41ab4b7,0x27a9211b,0x2ba7251b,0xadc2af0c,0xb1b6b2f7,0x2c792a63,0x30742e5f,0xaa63ac79,0xae5fb074,0x2f0c2dc2,0x32f731b6,
0xa11ba7a9,0xa51baba7,0x30d2302c,0x34b7341a,0xb17ab257,0xb552b61a,0x290222ad,0x2d0026ad,0xaf8cb09f,0xb371b487,0x2ddc2c2e,0x31cf3029,
0xac2eaddc,0xb029b1cf,0x309f2f8c,0x34873371,0xa2ada902,0xa6adad00,0x3257317a,0x361a3552,0xb2cdb3e3,0xb682b76f,0x2a312420,0x2e2d281f,
0xb0acb1bb,0xb493b58d,0x2f3f2d2a,0x33283122,0xad2aaf3f,0xb122b328,0x31bb30ac,0x358d3493,0xa420aa31,0xa81fae2d,0x33e332cd,0x376f3682,
0xb413b4bc,0xb7a6b85a,0x2b5f24e9,0x2f5928e8,0xb194b2da,0xb56ab68d,0x30522e28,0x343e3219,0xae28b052,0xb219b43e,0x32da3194,0x368d356a,
0xa4e9ab5f,0xa8e8af59,0x34bc3413,0x385a37a6,0xb4c3b58c,0xb85fb8f3,0x2c4725b2,0x304229b1,0xb27eb3fd,0xb63cb785,0x31062f26,0x34e7330f,
0xaf26b106,0xb30fb4e7,0x33fd327e,0x3785363c,0xa5b2ac47,0xa9b1b042,0x358c34c3,0x38f3385f,0xb577b662,0xb8e5b982,0x2cde267b,0x30d72a7a,
0xb36bb493,0xb70ab83a,0x31bb3012,0x358d3402,0xb012b1bb,0xb402b58d,0x3493336b,0x383a370a,0xa67bacde,0xaa7ab0d7,0x36623577,0x398238e5,
0xb630b741,0xb962ba04,0x2d762744,0x316c2b43,0xb42eb52a,0xb7d2b8ad,0x32713092,0x3631347b,0xb092b271,0xb47bb631,0x352a342e,0x38ad37d2,
0xa744ad76,0xab43b16c,0x37413630,0x3a043962,0xb6eeb815,0xb9d6ba7a,0x2e0e2807,0x32012c06,0xb4a7b5c4,0xb84ab91b,0x33293113,0x36d234f3,
0xb113b329,0xb4f3b6d2,0x35c434a7,0x391b384a,0xa807ae0e,0xac06b201,0x381536ee,0x3a7a39d6,0xb7b4b88e,0xba41bae1,0x2ea7286b,0x32942c6a,
0xb523b662,0xb8a8b982,0x33e33194,0x376f356a,0xb194b3e3,0xb56ab76f,0x36623523,0x398238a8,0xa86baea7,0xac6ab294,0x388e37b4,0x3ae13a41,
0xb841b90f,0xbaa2bb3a,0x2f3f28d0,0x33282cce,0xb5a1b705,0xb902b9e3,0x344f3216,0x380535df,0xb216b44f,0xb5dfb805,0x370535a1,0x39e33902,
0xa8d0af3f,0xacceb328,0x390f3841,0x3b3a3aa2,0xb8acb997,0xbaf7bb83,0x2fd82935,0x33ba2d33,0xb621b7ac,0xb958ba3d,0x34ae3298,0x38503654,
0xb298b4ae,0xb654b850,0x37ac3621,0x3a3d3958,0xa935afd8,0xad33b3ba,0x399738ac,0x3b833af7,0xb91cba28,0xbb42bbbc,0x30392999,0x34262d97,
0xb6a4b82d,0xb9aaba90,0x350e331c,0x389936c6,0xb31cb50e,0xb6c6b899,0x382d36a4,0x3a9039aa,0xa999b039,0xad97b426,0x3a28391c,0x3bbc3b42,
0xb992bac3,0xbb81bbe3,0x308529fe,0x346f2dfb,0xb72ab886,0xb9f8badb,0x357033a0,0x38e03737,0xb3a0b570,0xb737b8e0,0x3886372a,0x3adb39f8,
0xa9feb085,0xadfbb46f,0x3ac33992,0x3be33b81,0x39cf3b16,0x3b9c3bf1,0xb0acaa31,0xb493ae2d,0x376f38b4,0x3a1d3afe,0xb5a1b3e3,0xb902b76f,
0x33e335a1,0x376f3902,0xb8b4b76f,0xbafeba1d,0x2a3130ac,0x2e2d3493,0xbb16b9cf,0xbbf1bb9c,0x39563a74,0x3b633bd2,0xb05fa9cc,0xb44badc9,
0x36e73859,0x39d23ab6,0xb53fb35e,0xb8bcb6ff,0x335e353f,0x36ff38bc,0xb859b6e7,0xbab6b9d2,0x29cc305f,0x2dc9344b,0xba74b956,0xbbd2bb63,
0x38e339de,0x3b1e3ba1,0xb012a967,0xb402ad65,0x36623801,0x39823a67,0xb4deb2da,0xb874b68d,0x32da34de,0x368d3874,0xb801b662,0xba67b982,
0x29673012,0x2d653402,0xb9deb8e3,0xbba1bb1e,0x38763952,0x3ace3b60,0xaf8ca902,0xb371ad00,0x35e13758,0x392e3a11,0xb47eb257,0xb82ab61a,
0x3257347e,0x361a382a,0xb758b5e1,0xba11b92e,0x29022f8c,0x2d003371,0xb952b876,0xbb60bace,0x380d38ce,0x3a733b10,0xaef3a89e,0xb2deac9c,
0x356236b3,0x38d639b3,0xb420b1d5,0xb7bdb5a5,0x31d53420,0x35a537bd,0xb6b3b562,0xb9b3b8d6,0x289e2ef3,0x2c9c32de,0xb8ceb80d,0xbb10ba73,
0x37503851,0x3a0d3ab0,0xae5aa839,0xb24bac38,0x34e53613,0x387a394f,0xb386b153,0xb721b52f,0x31533386,0x352f3721,0xb613b4e5,0xb94fb87a,
0x28392e5a,0x2c38324b,0xb851b750,0xbab0ba0d,0x368e37b4,0x399d3a41,0xadc2a7a9,0xb1b6aba7,0x346a3577,0x381a38e5,0xb2cdb0d2,0xb682b4b7,
0x30d232cd,0x34b73682,0xb577b46a,0xb8e5b81a,0x27a92dc2,0x2ba731b6,0xb7b4b68e,0xba41b99d,0x35d236d1,0x392439c5,0xad2aa6e0,0xb122aade,
0x33e334de,0x376f3874,0xb216b052,0xb5dfb43e,0x30523216,0x343e35df,0xb4deb3e3,0xb874b76f,0x26e02d2a,0x2ade3122,0xb6d1b5d2,0xb9c5b924,
0x351c35f6,0x38a3393c,0xac93a617,0xb08daa16,0x32f43448,0x36a437fe,0xb160afa5,0xb53ab389,0x2fa53160,0x3389353a,0xb448b2f4,0xb7feb6a4,
0x26172c93,0x2a16308d,0xb5f6b51c,0xb93cb8a3,0x346a3523,0x381a38a8,0xabf6a54d,0xafefa94d,0x3209336b,0x35d4370a,0xb0acaea7,0xb493b294,
0x2ea730ac,0x32943493,0xb36bb209,0xb70ab5d4,0x254d2bf6,0x294d2fef,0xb523b46a,0xb8a8b81a,0x33783456,0x3715380a,0xaac8a484,0xaec3a884,
0x3120324a,0x34ff360e,0xaff2ada9,0xb3d3b19e,0x2da92ff2,0x319e33d3,0xb24ab120,0xb60eb4ff,0x24842ac8,0x28842ec3,0xb456b378,0xb80ab715,
0x3223331c,0x35eb36c6,0xa999a376,0xad97a776,0x3039312d,0x3426350b,0xae8dacac,0xb27cb0a6,0x2cac2e8d,0x30a6327c,0xb12db039,0xb50bb426,
0x23762999,0x27762d97,0xb31cb223,0xb6c6b5eb,0x30d23194,0x34b7356a,0xa86ba1e4,0xac6aa5e4,0x2ea73012,0x32943402,0xad2aab5f,0xb122af59,
0x2b5f2d2a,0x2f593122,0xb012aea7,0xb402b294,0x21e4286b,0x25e42c6a,0xb194b0d2,0xb56ab4b7,0x2f0c3012,0x32f73402,0xa67ba052,0xaa7aa452,
0x2cde2df5,0x30d731e8,0xab91a967,0xaf8bad65,0x29672b91,0x2d652f8b,0xadf5acde,0xb1e8b0d7,0x2052267b,0x24522a7a,0xb012af0c,0xb402b2f7,
0x2c792d2a,0x30743122,0xa4209d7f,0xa81fa17f,0x2a312b91,0x2e2d2f8b,0xa8d0a6e0,0xacceaade,0x26e028d0,0x2ade2cce,0xab91aa31,0xaf8bae2d,
0x1d7f2420,0x217f281f,0xad2aac79,0xb122b074,0x27a9286b,0x2ba72c6a,0x9f1298b6,0xa3119cb6,0x254d267b,0x294d2a7a,0xa420a1e4,0xa81fa5e4,
0x21e42420,0x25e4281f,0xa67ba54d,0xaa7aa94d,0x18b61f12,0x1cb62311,0xa86ba7a9,0xac6aaba7,0x3f803f80,0x3f803f80,0x3f803f80,0x3f803f80,
0x3f803f80,0x3f803f80,0x3f803f80,0x3f803f80,0x3f803f80,0x3f803f80,0x3f803f80,0x3f803f80,0x3f803f80,0x3f803f80,0x3f803f80,0x3f803f80,
0x3f803f80,0x3f803f80,0x3f803f80,0x3f803f80,0x3f803f80,0x3f803f80,0x3f803f80,0x3f803f80,0x3f803f80,0x3f803f80,0x3f803f80,0x3f803f80,
0x3f803f80,0x3f803f80,0x3f803f80,0x3f803f80,0x3f803f80,0x3f803f80,0x3f803f80,0x3f803f80,0x3f803f80,0x3f803f80,0x3f803f80,0x3f803f80,
0x3f803f80,0x3f803f80,0x3f803f80,0x3f803f80,0x3f803f80,0x3f803f80,0x3f803f80,0x3f803f80,0x3f803f80,0x3f803f80,0x3f803f80,0x3f803f80,
0x3f803f80,0x3f803f80,0x3f803f80,0x3f803f80,0x3f803f80,0x3f803f80,0x3f803f80,0x3f803f80,0x3f803f80,0x3f803f80,0x3f803f80,0x3f803f80,
0x3f803f80,0x3f803f80,0x3f803f80,0x3f803f80,0x3f803f80,0x3f803f80,0x3f803f80,0x3f803f80,0x3f803f80,0x3f803f80,0x3f803f80,0x3f803f80,
0x3f803f80,0x3f803f80,0x3f803f80,0x3f803f80,0x3f803f80,0x3f803f80,0x3f803f80,0x3f803f80,0x3f803f80,0x3f803f80,0x3f803f80,0x3f803f80,
0x3f803f80,0x3f803f80,0x3f803f80,0x3f803f80,0x3f803f80,0x3f803f80,0x3f803f80,0x3f803f80,0x3f803f80,0x3f803f80,0x3f803f80,0x3f803f80,
0x3f803f80,0x3f803f80,0x3f803f80,0x3f803f80,0x3f803f80,0x3f803f80,0x3f803f80,0x3f803f80,0x3f803f80,0x3f803f80,0x3f803f80,0x3f803f80,
0x3f803f80,0x3f803f80,0x3f803f80,0x3f803f80,0x3f803f80,0x3f803f80,0x3f803f80,0x3f803f80,0x3f803f80,0x3f803f80,0x3f803f80,0x3f803f80,
0x3f803f80,0x3f803f80,0x3f803f80,0x3f803f80,0x3f803f80,0x3f803f80,0x3f803f80,0x3f803f80,0x3f803f80,0x3f803f80,0x3f803f80,0x3f803f80,
0x3f803f80,0x3f803f80,0x3f803f80,0x3f803f80,0x3f803f80,0x3f803f80,0x3f803f80,0x3f803f80,0x3f803f80,0x3f803f80,0x3f803f80,0x3f803f80,
0x3f803f80,0x3f803f80,0x3f803f80,0x3f803f80,0x3f803f80,0x3f803f80,0x3f803f80,0x3f803f80,0x3f803f80,0x3f803f80,0x3f803f80,0x3f803f80,
0x3f803f80,0x3f803f80,0x3f803f80,0x3f803f80,0x3f803f80,0x3f803f80,0x3f803f80,0x3f803f80,0x3f803f80,0x3f803f80,0x3f803f80,0x3f803f80,
0x3f803f80,0x3f803f80,0x3f803f80,0x3f803f80,0x3f803f80,0x3f803f80,0x3f803f80,0x3f803f80,0x3f803f80,0x3f803f80,0x3f803f80,0x3f803f80,
0x3f803f80,0x3f803f80,0x3f803f80,0x3f803f80,0x3f803f80,0x3f803f80,0x3f803f80,0x3f803f80,0x3f803f80,0x3f803f80,0x3f803f80,0x3f803f80,
0x3f803f80,0x3f803f80,0x3f803f80,0x3f803f80,0x3f803f80,0x3f803f80,0x3f803f80,0x3f803f80,0x3f803f80,0x3f803f80,0x3f803f80,0x3f803f80,
0x3f803f80,0x3f803f80,0x3f803f80,0x3f803f80,0x3f803f80,0x3f803f80,0x3f803f80,0x3f803f80,0x3f803f80,0x3f803f80,0x3f803f80,0x3f803f80,
0x3f803f80,0x3f803f80,0x3f803f80,0x3f803f80,0x3f803f80,0x3f803f80,0x3f803f80,0x3f803f80,0x3f803f80,0x3f803f80,0x3f803f80,0x3f803f80,
0x3f803f80,0x3f803f80,0x3f803f80,0x3f803f80,0x3f803f80,0x3f803f80,0x3f803f80,0x3f803f80,0x3f803f80,0x3f803f80,0x3f803f80,0x3f803f80,
0x3f803f80,0x3f803f80,0x3f803f80,0x3f803f80,0x3f803f80,0x3f803f80,0x3f803f80,0x3f803f80,0x3f803f80,0x3f803f80,0x3f803f80,0x3f803f80,
0x3f803f80,0x3f803f80,0x3f803f80,0x3f803f80,0x3f803f80,0x3f803f80,0x3f803f80,0x3f803f80,0x3f803f80,0x3f803f80,0x3f803f80,0x3f803f80,
0x3f803f80,0x3f803f80,0x3f803f80,0x3f803f80,0x3f803f80,0x3f803f80,0x3f803f80,0x3f803f80,0x3f803f80,0x3f803f80,0x3f803f80,0x3f803f80,
0x3f803f80,0x3f803f80,0x3f803f80,0x3f803f80,0x3f803f80,0x3f803f80,0x3f803f80,0x3f803f80,0x3f803f80,0x3f803f80,0x3f803f80,0x3f803f80,
0x3f803f80,0x3f803f80,0x3f803f80,0x3f803f80,0x3f803f80,0x3f803f80,0x3f803f80,0x3f803f80,0x3f803f80,0x3f803f80,0x3f803f80,0x3f803f80,
0x3f803f80,0x3f803f80,0x3f803f80,0x3f803f80,0x3f803f80,0x3f803f80,0x3f803f80,0x3f803f80,0x3f803f80,0x3f803f80,0x3f803f80,0x3f803f80,
0x3f803f80,0x3f803f80,0x3f803f80,0x3f803f80,0x3f803f80,0x3f803f80,0x3f803f80,0x3f803f80,0x3f803f80,0x3f803f80,0x3f803f80,0x3f803f80,
0x3f803f80,0x3f803f80,0x3f803f80,0x3f803f80,0x3f803f80,0x3f803f80,0x3f803f80,0x3f803f80,0x3f803f80,0x3f803f80,0x3f803f80,0x3f803f80,
0x3f803f80,0x3f803f80,0x3f803f80,0x3f803f80,0x3f803f80,0x3f803f80,0x3f803f80,0x3f803f80,0x3f803f80,0x3f803f80,0x3f803f80,0x3f803f80,
0x3f803f80,0x3f803f80,0x3f803f80,0x3f803f80,0x3f803f80,0x3f803f80,0x3f803f80,0x3f803f80,0x3f803f80,0x3f803f80,0x3f803f80,0x3f803f80,
0x3f803f80,0x3f803f80,0x3f803f80,0x3f803f80,0x3f803f80,0x3f803f80,0x3f803f80,0x3f803f80,0x3f803f80,0x3f803f80,0x3f803f80,0x3f803f80,
0x3f803f80,0x3f803f80,0x3f803f80,0x3f803f80,0x3f803f80,0x3f803f80,0x3f803f80,0x3f803f80,0x3f803f80,0x3f803f80,0x3f803f80,0x3f803f80,
0x3f803f80,0x3f803f80,0x3f803f80,0x3f803f80,0x3f803f80,0x3f803f80,0x3f803f80,0x3f803f80,0x3f803f80,0x3f803f80,0x3f803f80,0x3f803f80,
0x3f803f80,0x3f803f80,0x3f803f80,0x3f803f80,0x3f803f80,0x3f803f80,0x3f803f80,0x3f803f80,0x3f803f80,0x3f803f80,0x3f803f80,0x3f803f80,
0x3f803f80,0x3f803f80,0x3f803f80,0x3f803f80,0x3f803f80,0x3f803f80,0x3f803f80,0x3f803f80,0x3f803f80,0x3f803f80,0x3f803f80,0x3f803f80,
0x3f803f80,0x3f803f80,0x3f803f80,0x3f803f80,0x3f803f80,0x3f803f80,0x3f803f80,0x3f803f80,0x3f803f80,0x3f803f80,0x3f803f80,0x3f803f80,
0x3f803f80,0x3f803f80,0x3f803f80,0x3f803f80,0x3f803f80,0x3f803f80,0x3f803f80,0x3f803f80,0x3f803f80,0x3f803f80,0x3f803f80,0x3f803f80,
0x3f803f80,0x3f803f80,0x3f803f80,0x3f803f80,0x3f803f80,0x3f803f80,0x3f803f80,0x3f803f80,0x3f803f80,0x3f803f80,0x3f803f80,0x3f803f80,
0x3f803f80,0x3f803f80,0x3f803f80,0x3f803f80,0x3f803f80,0x3f803f80,0x3f803f80,0x3f803f80,0x3f803f80,0x3f803f80,0x3f803f80,0x3f803f80,
0x3f803f80,0x3f803f80,0x3f803f80,0x3f803f80,0x3f803f80,0x3f803f80,0x3f803f80,0x3f803f80,0x3f803f80,0x3f803f80,0x3f803f80,0x3f803f80,
0x3f803f80,0x3f803f80,0x3f803f80,0x3f803f80,0x3f803f80,0x3f803f80,0x3f803f80,0x3f803f80,0x3f803f80,0x3f803f80,0x3f803f80,0x3f803f80,
0x3f803f80,0x3f803f80,0x3f803f80,0x3f803f80,0x3f803f80,0x3f803f80,0x3f803f80,0x3f803f80,0x3f803f80,0x3f803f80,0x3f803f80,0x3f803f80,
0x3f803f80,0x3f803f80,0x3f803f80,0x3f803f80,0x3bf23bff,0x3ba53bd4,0x3b163b65,0x3a493ab6,0x3b7c3bfb,0x38bc3a60,0x2b43356a,0xb7f3b359,
0x3a933bf1,0x9cb63764,0xba9eb785,0xbb73bbf3,0x39463be2,0xb8cc28e8,0xbb42bbc2,0x3328b70a,0x374e3bcf,0xbbabb648,0xaec3baa9,0x3bfa3994,
0x33403bb7,0xbb85b9fc,0x3a64b0be,0x2c6a3b47,0xa4523b9a,0xb86abbae,0x3b6a3911,0xbbd0ad65,0xb4263b78,0x2adebbe6,0x30f03bfd,0xb5b1bbbc,
0x2f5925e4,0x34b73294,0x376f361a,0x38f3385a,0x35a52c9c,0x3a7338d6,0x3bfd3b87,0x3af13bc9,0x388e2fbd,0x3c003b18,0x387f3b10,0xb5d42f27,
0x3a04316c,0x3a673bfe,0xb6bb33d3,0xbbccbb2f,0x3b1e32f7,0x34933b5c,0xbbf5b86f,0x2d00b9bc,0x3bcb343e,0xb576394f,0xb8d1bbe9,0x3bfb36a4,
0x3c0034ff,0xbaac347b,0x3602ba31,0x32de3bf9,0x3bba35bc,0xbbfdb109,0x3be7aa7a,0xbb7a341a,0x394639cd,0x381538b2,0x358136dd,0x3153341a,
0xbb1eb9c9,0xbbf5bbdd,0xba39bb65,0xb4f3b889,0xb340b93c,0x3966340e,0x3bec3b87,0x37213a7e,0x3c003a4d,0x32193a21,0xbb5eb785,0xb894bbb0,
0xb426389e,0xbb37bb45,0x38b7b3d3,0x397d3bfc,0xbafebac1,0x3b13217f,0xadc93aa9,0xba49bb59,0x3979b7e8,0xb0d73b32,0xb6f4bbe9,0x3af139da,
0x38553b24,0xb9a1ba3d,0x3ab03911,0xbb73b759,0x3a043982,0x3ae13a7a,0x3b833b3a,0x3be33bbc,0x374e3986,0xae9131e8,0xb907b61a,0xbb9cba97,
0xbbcbba0d,0xb9e7bbbd,0x3074b56a,0x3b2a38ad,0x2452b8ee,0x3bda3924,0x363c3b10,0xba90b46f,0x3bba3a89,0xb6e836af,0xba76bbc2,0x39d2ac06,
0xb7c8384a,0xb77abc00,0x3bf8386f,0xb8f33654,0xb9d6baf4,0x3be836ff,0xbb3530be,0x37f3b974,0x3abab737,0xb9af3902,0x3865ba31,0xb5d43b1b,
0x32c62fbd,0x363134cf,0x38653785,0x398b38fd,0xb715b16c,0xbae1b970,0xbbfebbc2,0xba85bb92,0x392e32f7,0x3bf53b6c,0x37a63aa9,0xb7422311,
0xba81b43e,0xb9e7bbfc,0x380fb0be,0x3b963b7f,0x3b7134ff,0x32193b04,0xbc00b911,0x319eb929,0xbbefb5bc,0x36e8b8b2,0x382a3bfd,0xbbffb805,
0x3bf23676,0xbb1331e8,0x376fb9aa,0x2f8b3bde,0xbb7cb72c,0x3be8340e,0xbbfdaa16,0x3bb8b122,0xbbd2bbf1,0xbb60bba1,0xbab0bb10,0xb9c5ba41,
0x3b2c3be2,0x381539df,0xa94d33d3,0xb8a3b52f,0xba19bbcf,0x2e91b5f7,0x3b07386f,0x3b213c00,0x38a83bb7,0xb966aba7,0xbae5bbe9,0x3517b599,
0xb5dfbb9a,0x3bda37b2,0x1fdb3a31,0xbbe0ba1d,0x30293b78,0xbb37ba7a,0x3ad5aa7a,0xa7763aeb,0x2f59bb52,0x377a3bdd,0xbb16b9a6,0x3bf231cf,
0xb5a53b27,0x30d7bbbd,0x2b433bfe,0xb432bbe5,0x3a813a0d,0x3b3f3ae8,0x3bbf3b87,0x3bfb3be5,0xb5dfb8ee,0x3263ad97,0x399d3785,0x3bd03b01,
0xbbefba89,0xb958bb81,0x3389b3d3,0x3b7a394a,0xaf59384a,0xbbf7b9b8,0xb4c3baa9,0x3afb35eb,0x3b7c3af4,0xb825353a,0xb9f8bbe9,0x3a542884,
0x388eb737,0x360e3bf4,0xbbdcb911,0x398bb4db,0xb946bb4f,0x3bc03830,0xbb832a7a,0x38a3b8db,0xbb1e35c8,0x3a35b85f,0xb90739aa,0x3742bab6,
0xb8a8b93c,0xb6c6b80a,0xb402b56a,0xac6ab122,0xbb71ba4d,0xbbd7bbf8,0xb9b3bb10,0xb2deb7bd,0x3029389e,0xb9f4b58d,0xbbc6bbc2,0xb5b1ba00,
0x3bf23ac1,0x2dfb3999,0xbba3b86f,0xb7d2bb6f,0x35a5b7e8,0x3ad83b90,0xb95430be,0xb8e5bbff,0xba93bb24,0x3b682ef5,0xb2013a31,0xb9c5bb9f,
0xba043682,0x33ebbad1,0x35813bfd,0xba85ba5c,0x374e3b76,0xb90cbab3,0x3a3939a6,0xbb21b85a,0xb7c83b52,0x391bba9b,0xba2539aa,0x3afbb889,
0xb9793b27,0x3bc5b80a,0xbb8eaa16,0x38e538ad,0xbaba3af7,0x3b60ad97,0xb27cba2d,0xb98b3bb0,0xbb943ac4,0x3815358d,0x39e3bbea,0xba852c06,
0xbbf93a8c,0xae9139b8,0x3bacb874,0x3742bb59,0xbbe43a50,0xb9663b90,0x340233ba,0x3b96b974,0xbb573a11,0xbbda3bf4,0xb99d3b0d,0xb19e3759,
0xba5839cd,0xbb373ad1,0xbbc63b89,0xbbff3bee,0x3afe3676,0xba29b884,0x391f39a6,0xb7d2ba97,0x39d6372c,0xb3a2bae8,0xb5463bfe,0x3a54ba7e,
0x385537dd,0x3631bbf8,0xbbd63916,0x39c5346f,0x35233845,0x3ae1bb81,0xb96bb0a6,0xb8a33bfc,0x2d333899,0x3bf5b999,0x3487baa5,0xbb213654,
0xb13b38ea,0x39e7b53a,0x3bbfbbc3,0x3517b9da,0xb65f3937,0x32192ef5,0x39b3b790,0x3be0bb1b,0xb8e03982,0xb6e83830,0xb389355e,0xa7763042,
0xbb943682,0x3bebb371,0xbbfe2a7a,0x3bcc3042,0xad33bb76,0xb79b3bd4,0x3b07b9aa,0xbbfa32ad,0x3be4b50b,0xb6c6b8d6,0xb80f3bfe,0x3bfbb835,
0xb65f3bb5,0x3bd7b764,0x9fdbba2d,0xbbd03a41,0xba58330f,0xb9f43bfe,0x382a30a6,0x3b7abb92,0x3a45bbe1,0xadfbb648,0xbb163874,0xbafb3c00,
0x3699afef,0x3ad8b94f,0x3bfdbbc3,0x3a54bb7f,0xbbdf3bfa,0xbb683bae,0xba9e3b0d,0xb98b3a1d,0x35233b4f,0xb08dbbc8,0xa94d3bfd,0x3328bbee,
0xbbf935c8,0x3b0a3294,0xb7a6b9a6,0xad003bd3,0x313bbb98,0xbb3f3a60,0x3ae52a16,0xac6abace,0x3b57b44b,0x3263bb18,0xbc003916,0x32de38fd,
0xb8e03bce,0x3958a8e8,0x3ad5bbea,0xb5b1b52f,0xb8f83185,0xbbf73b5c,0xb76f3aa5,0x37d2a311,0x3b4abbf0,0x3825b9fc,0xab43b3ba,0xb8e53599,
0x31b6acce,0x360eb47b,0x387fb790,0x39c5b929,0x3a9337dd,0xb9a1b924,0x387f3a2d,0xb66bbb01,0xb946b845,0x308d3b45,0x36bbbbea,0xbac73a00,
0x374e3899,0x379bbc00,0xbbf53874,0x393335eb,0xb340b8ea,0xbb3f3b32,0x38d133ba,0x3941bbff,0xa4523937,0x3bd7b902,0x3602bb0d,0xbabd34db,
0x3426b982,0xb9583371,0xbbe73b89,0xb68d3a5c,0xb7c839c9,0x2dfb3294,0x391fb625,0x3bb3bab6,0x3979ba0d,0x3825b8d6,0x3546b6d2,0x3010b359,
0x388ebaf7,0xb9af3a21,0x3a9eb916,0xbb5437bd,0xba043ac4,0x3bebb6af,0xbb42b0a6,0x3840394a,0x3b1eba8c,0xbb0aa17f,0x2ec33aa5,0x3a15bb6f,
0xbbcb3a50,0x36c636ff,0x3a64bbc3,0xba09a884,0x3c00ba11,0x3263ba3d,0xbb6a3790,0xb8503b9f,0xbbba39cd,0xb9f43bc8,0x30f0355e,0x3b4cb8db,
0x3afeb986,0x3bf7bbd4,0x3a25bb63,0x3457b85a,0xb9d6393c,0xbad83a60,0xbb8e3b3d,0xbbef3bc9,0x33403b98,0xa9b1bbed,0xb0743bfe,0x3517bbc9,
0x3c00b44b,0xbaa2b4cf,0x363c3a2d,0x319ebbf3,0x3426bbce,0xbb8b39df,0x3a7630a6,0x2776bb2f,0xbafe3185,0xb4b73b6c,0x3bf8b874,0xaf8bb994,
0xb9793bf0,0x38bc2ba7,0x3b35bbc3,0xb432b6a4,0x3855acce,0x3c00bb04,0x3865bb0d,0xb66bad65,0x3b94bbff,0x38ccba7a,0x294db55e,0xb840341a,
0xad33a5e4,0xb49331e8,0xb7a63625,0xb9333889,0x3bcbb50b,0xbbfe305b,0x3bec2a16,0xbb96b359,0x2452bbb5,0xb87a3ba1,0x3b5eb916,0xbbe02f27,
0xbbba330f,0x35523970,0x38b7bbea,0xbbff370a,0xb7c83be1,0x3ba5b5f7,0x2dc9baa5,0xbbf239bc,0x39d6afef,0x3a73bbfc,0xb6f4b3ba,0xbbb83b47,
0x3ababbfa,0x1cb6b7b2,0xbab03790,0xbb543bf9,0xb52326ad,0xba6738b2,0xbbfe3b89,0xbac73bbc,0xbbf93bff,0xbbab3bdd,0xbb073b63,0xba153a97,
0xb8f83986,0xb77a385f,0xb4c33625,0xaf8b32ad,0xb699393c,0x30d7305b,0x3954b6d2,0x3bb8bace,0xb1b638ee,0x39afb4cf,0x3bdcbba7,0x366bba41,
0x2c38389e,0x3bebb970,0x3581bade,0xbac7352f,0x34e7384a,0x3b0abb6c,0xb907b24b,0xb9333c00,0x383a37e8,0x36c6bbfc,0xbbec38c1,0x39413599,
0x39c03737,0xb263bb04,0xb63c3bf6,0x3abdba1d,0x3aee3682,0xb9f4b8b2,0x38b739f0,0xb68dbaeb,0xba4539c9,0xbb133ab3,0xbba33b63,0xbbf23bd3,
0xbb4a3a0d,0xbbe83bed,0xb9f83b3d,0xb4323835,0xbbdf3a4d,0xb9a13ba1,0x320134ab,0x3b54b8fd,0xbbfc3a89,0xb08d39df,0x3b83b81a,0x3840bb92,
0xbb9e3ac1,0x379b35f7,0x3a39bbd8,0xba15a311,0xbacb3af4,0x3b3faba7,0xb074ba6f,0xba093b7f,0xb9903b24,0x3bd7b7b2,0xbb5eae5f,0x38503929,
0xb7fe3b4f,0x3958ba7a,0xba76395d,0x3b4cb805,0x2c3826ad,0x33ebb109,0x36bbb55e,0x38a3b805,0x3b9ebbff,0x390cba9b,0x2ec3b625,0xb74231cf,
0xb83a2c9c,0xbbfe3ae8,0xb8d13b3d,0x35173122,0xb9903bf1,0x387a2d97,0x3b6abba7,0xb19eb7bd,0x3aeeb16c,0x3552bb81,0xbbe7381a,0x27763a00,
0x3463bbcf,0xbba539b8,0x3a25324b,0x2f8bbb6f,0xbbff343e,0x3a73353a,0xb546ba6f,0xb4323bff,0x32c63b9a,0x9cb6bbf4,0xb27c3bf6,0x366bbb9f,
0xbbfc3bff,0xbbc03be6,0xbb423b89,0xba853aeb,0x34e7a5e4,0x3a35b884,0x3bf5bb63,0x3b21bbde,0x3acbbbfb,0x29b1b80a,0xba6436d2,0xbb963be5,
0xb9c02fbd,0xbaa23bf8,0x360234ab,0x3be0bb01,0xb7fe3be2,0x3b8bb58d,0x30f0bade,0xbbff394a,0x3bb2b2f7,0xb4b7b999,0xb91f3bd8,0x3bf2b5eb,
0x281fbbb7,0xb8bc3b90,0x3b8eb8c1,0xbbb82884,0xbbd234ff,0x3c00aef5,0xbbd6ae5f,0x3b5434db,0xbaba3a4d,0xbb683b18,0xbbd63ba7,0xbc003bf3,
0x3b94ba89,0x3bc0bbfe,0x396bbade,0x3153b70a,0xbbf93ac1,0xb90c3b5c,0x3487324b,0x3b9cb994,0x3be4baf4,0x29b1b94f,0xbbbf38c1,0xb7213b47,
0xbb573b24,0x387a347b,0x39b3bbf6,0xba902d65,0x3a58bb4f,0xbb8b3109,0x338939f0,0x397dbbbc,0xb8f83b76,0x3ba5b884,0xbba39648,0x38f33889,
0x3699bb98,0xb8bc3ae8,0x39f8b9eb,0xbaf138ad,0x3855b8ee,0x360eb764,0x327cb4ab,0x251baf27,0xb523389e,0x33eb28e8,0x39e3b81a,0x3be3bb2f,
0x2d33b84a,0xba353648,0xbbac3bd8,0xb4f339bc,0x313b37e8,0x3bfeb9fc,0x3402ba6f,0xbb2a36a4,0xb65fb737,0xbaa23bae,0x399d2e5f,0x3894bbf9,
0x38e03682,0x3552bbe6,0xbbc6395d,0x39d2341a,0xba45b5c8,0x34b73a9b,0x34c3bc00,0xba493a97,0x3b4a350b,0xba73b80a,0x39543962,0xb7f3ba7e,
0xbbe43bfb,0xbb853bbd,0xbae53b3d,0xba093a7e,0xb65f2fbd,0xbaac3924,0xbc003ba7,0xbabd3bb0,0x3a58bbe2,0xaadeb6af,0xbad5381a,0xbb4c3bfc,
0x3a45b2f7,0x3a29bc00,0xb76fb24b,0xbbb33b59,0xb6993bb7,0x3bc5b6ff,0x2b43ba6f,0xbbef39da,0xbbdf34ff,0x36313902,0x387fbbf6,0xbc003759,
0xac38bb78,0xb8153bc8,0x3b42b95d,0xbbe33042,0x3b9eb676,0xbbf53294,0x3bf51648,0xbb9cb2ad,0xb13b2c9c,0xb576340e,0xb80f36d2,0xb94138ad,
0x3b57bbf1,0x386aba21,0x1fdbb4ab,0xb850346f,0x38e0b16c,0x3bfdbb45,0x382abade,0xb68dac06,0xb8f83bcf,0x391ba17f,0x3b16bbd8,0xb457b654,
0xbb4a343e,0xb3a23b32,0x3bfdb8c1,0xb010b974,0x31b6bb9a,0xbb603a3d,0x3a9e2e5f,0x251bbb1b,0x3bfcb5bc,0xbae1b371,0x36bb39f0,0x3153bbee,
0x34e73b52,0xae91bbd4,0xaec33c00,0x34f3bbd3,0x3bb235c8,0xbbf7b1e8,0x3bf81648,0xbbb331cf,0x3bff350b,0xbad8340e,0x36f4b9eb,0x30103be5,
0x3bd2344b,0xb60e3924,0xb865bbf6,0x3c0037bd,0x3b2c330f,0x33eb3b45,0xbbfeb8c7,0x3153b94a,0x3a193185,0x3a353c00,0xb7a63232,0xbb9cbb6f,
0x38a82fef,0x3bfe3b32,0x380f3adb,0xb7212884,0x35df2cce,0x3aa23902,0x3c003ba9,0x3a903b9f,0x302926ad,0x35523371,0x382a36dd,0x397d38db,
0xb4633b76,0x2dfbbbdd,0x2dc93c00,0xb457bbde,0xa81f3b98,0xb825bbbd,0x3b353962,0xbbefb122,0x32c63bb5,0xbb68ba21,0x3ab0ae2d,0xa51b3b01,
0x37153bce,0xbbc0b6af,0xa94dba6b,0x3be33a00,0x392e3be1,0xb90c217f,0xbb07bbd9,0x34f3b5eb,0x3a813bf0,0xa9b136ff,0xbae5b820,0xbb2abbff,
0x3b713bfa,0x387a3a3d,0x9fdb349f,0xb894b4db,0x3bef3bff,0x3b8b3bc8,0x3ad53b3a,0x39d23a5c,0x3b2cb5bc,0xba673830,0x396bb95d,0xb8403a5c,
0xb92ebb52,0x3bab385f,0xbbac9648,0x3933b85a,0xb8a8372c,0xb576bbed,0x3bbf3962,0xba093359,0x3b713af7,0xb86a34cf,0xb99dbbf6,0x3abd2f27,
0x3029b845,0x3bfd39df,0x33893a6b,0xbb4cb70a,0xbbf2ba8c,0xb91bbb6c,0x34c3b232,0x3bb339bc,0x35a538ea,0xb3a22ba7,0xb9f8b820,0xbbefbb47,
0x3a933a11,0x3b603b04,0x3bdc3ba9,0x3c003bf9,0x37153b78,0xb8ccbad1,0x39e339f0,0xbac7b8db,0x3a19b676,0xb4933ab3,0xb487bc00,0x3a153ab6,
0xba81bb27,0x3b85305b,0xb40239eb,0xb941bbc9,0xb5df37dd,0xbaacbba1,0x39b3ae2d,0x38503bf3,0x3bef3ac4,0x2ade3970,0xbbc6b8c7,0xb68dbb2f,
0xaf59b899,0x3a2935f7,0x3ba33bd9,0x34573994,0xbb7cba50,0xbbc5bbfc,0xb954badb,0xb010b6a4,0x388e3937,0x363137b2,0x3201349f,0xa51b2d65,
0xb1b63bb5,0x9cb6bbf8,0x32013bf6,0xb5d4bbb0,0xac38bbce,0x38cc3b81,0xbb83b8c7,0x3bcc2c06,0x34e73be1,0xbbabb999,0x3a39b232,0x2d003b59,
0xb83abbf0,0x3b85353a,0x30743adb,0xbbfbb974,0x39c03bfa,0xb86a2ef5,0xbb5ebba9,0x32deb759,0xbaeebbff,0xaadeb830,0x3a7636dd,0x3b7a3bee,
0x3bb23bff,0x391b3ab3,0x2dc9361a,0xb7d2b2ad,0xbbffbbfb,0xbbc5bbed,0xbb35bb87,0xba54bace,0xbbdfb44b,0x3c002d97,0xbbdc2e2d,0x3b73b46f,
0x3bfc330f,0xba67358d,0x3581ba6b,0x33283bfc,0xbb9eb185,0x3493b9b8,0x39073bd9,0xbbfab654,0x3acb2fef,0x35763b90,0xbbecb820,0x2c6ab9da,
0xb990acce,0xbaacbbf4,0x363cb49f,0x3bd03b1b,0x37fe26ad,0x3bfd3ad1,0x38b73b3a,0xb5b13042,0xb46325e4,0xba29b85f,0xbbf8bb65,0xbafbbbd3,
0x281fac9c,0x33a2305b,0x36f4356a,0x38e53835,0x383a3b27,0xb966ba60,0x3a643962,0xbb2ab835,0xb99037dd,0x3219bb18,0x36023bf6,0xba90ba41,
0xbaeebac4,0x3b3728e8,0xb0f03a6b,0xb9d2bb92,0x3463b899,0x3b133b5c,0xb91f3232,0xb8f3bc00,0x3bff3a50,0x30d739fc,0xbb8eb820,0xb7f3bb7f,
0x32c63937,0xb9a1b47b,0xbbd6bba9,0xb5d4ba1d,0xbb2cb9cd,0xbbebbbe6,0xb9e3bb3a,0xb328b805,0xb92eb9c9,0xb79bb884,0xb487b61a,0xad00b1cf,
0xbacb372c,0x39e7b8d6,0xb8d139eb,0x3721bace,0xb9c0baf7,0x3bda3764,0xbb6a2e2d,0x3894b8fd,0x37feb845,0x36e83bfe,0xbbe7b8c7,0x397db52f,
0x3bb23a8c,0xb77a3648,0xba25bbd9,0x3a492311,0xa81f38ea,0xbbe8b94f,0xb546badb,0x3af13599,0xbbd2ba11,0xb9afbbae,0x327cb49f,0x3b733929,
0xb715b982,0x308db109,0x396b36dd,0x3bcc3aeb,0x3a193986,0x3b0a3a9b,0x3bac3b65,0x3bfa3bde,0x30003000,0x30003000,0x30003000,0x30003000,
0x2f643000,0x2a1f2da8,0xaa1f0000,0xaf64ada8,0x2da83000,0xada80000,0xada8b000,0x2da88000,0x2a1f3000,0xaf64ada8,0x2f648000,0xaa1f2da8,
0x00003000,0x8000b000,0x00003000,0x8000b000,0xaa1f3000,0x2f64ada8,0xaf640000,0x2a1f2da8,0xada83000,0x2da88000,0x2da8b000,0xada80000,
0xaf643000,0xaa1f2da8,0x2a1f8000,0x2f64ada8,0x30003000,0x30003000,0x30003000,0x30003000,0xaf64b000,0xaa1fada8,0x2a1f8000,0x2f642da8,
0x2da83000,0xada80000,0xada8b000,0x2da88000,0xaa1fb000,0x2f642da8,0xaf640000,0x2a1fada8,0x00003000,0x8000b000,0x00003000,0x8000b000,
0x2a1fb000,0xaf642da8,0x2f648000,0xaa1fada8,0xada83000,0x2da88000,0x2da8b000,0xada80000,0x2f64b000,0x2a1fada8,0xaa1f0000,0xaf642da8,
0x80008000,0x80008000,0x80008000,0x80008000,0xaa1f8000,0xaf64ada8,0xaf64b000,0xaa1fada8,0xada88000,0xada8b000,0x2da88000,0x2da83000,
0xaf648000,0x2a1fada8,0x2a1f3000,0xaf64ada8,0xb0008000,0x30008000,0xb0008000,0x30008000,0xaf648000,0x2a1f2da8,0x2a1fb000,0xaf642da8,
0xada88000,0xada83000,0x2da88000,0x2da8b000,0xaa1f8000,0xaf642da8,0xaf643000,0xaa1f2da8,0x80008000,0x80008000,0x80008000,0x80008000,
0x2a1f8000,0x2f642da8,0x2f643000,0x2a1f2da8,0xada88000,0xada8b000,0x2da88000,0x2da83000,0x2f648000,0xaa1f2da8,0xaa1fb000,0x2f642da8,
0xb0008000,0x30008000,0xb0008000,0x30008000,0x2f648000,0xaa1fada8,0xaa1f3000,0x2f64ada8,0xada88000,0xada83000,0x2da88000,0x2da8b000,
0x2a1f8000,0x2f64ada8,0x2f64b000,0x2a1fada8,0xb0003000,0xb0003000,0xb0003000,0xb0003000,0xaf643000,0xaa1f2da8,0x2a1f0000,0x2f64ada8,
0xada83000,0x2da80000,0x2da8b000,0xada88000,0xaa1f3000,0x2f64ada8,0xaf648000,0x2a1f2da8,0x80003000,0x0000b000,0x80003000,0x0000b000,
0x2a1f3000,0xaf64ada8,0x2f640000,0xaa1f2da8,0x2da83000,0xada88000,0xada8b000,0x2da80000,0x2f643000,0x2a1f2da8,0xaa1f8000,0xaf64ada8,
0xb0003000,0xb0003000,0xb0003000,0xb0003000,0x2f64b000,0x2a1fada8,0xaa1f8000,0xaf642da8,0xada83000,0x2da80000,0x2da8b000,0xada88000,
0x2a1fb000,0xaf642da8,0x2f640000,0xaa1fada8,0x80003000,0x0000b000,0x80003000,0x0000b000,0xaa1fb000,0x2f642da8,0xaf648000,0x2a1fada8,
0x2da83000,0xada88000,0xada8b000,0x2da80000,0xaf64b000,0xaa1fada8,0x2a1f0000,0x2f642da8,0x80008000,0x80008000,0x80008000,0x80008000,
0x2a1f8000,0x2f64ada8,0x2f64b000,0x2a1fada8,0x2da88000,0x2da8b000,0xada88000,0xada83000,0x2f648000,0xaa1fada8,0xaa1f3000,0x2f64ada8,
0x30008000,0xb0008000,0x30008000,0xb0008000,0x2f648000,0xaa1f2da8,0xaa1fb000,0x2f642da8,0x2da88000,0x2da83000,0xada88000,0xada8b000,
0x2a1f8000,0x2f642da8,0x2f643000,0x2a1f2da8,0x80008000,0x80008000,0x80008000,0x80008000,0xaa1f8000,0xaf642da8,0xaf643000,0xaa1f2da8,
0x2da88000,0x2da8b000,0xada88000,0xada83000,0xaf648000,0x2a1f2da8,0x2a1fb000,0xaf642da8,0x30008000,0xb0008000,0x30008000,0xb0008000,
0xaf648000,0x2a1fada8,0x2a1f3000,0xaf64ada8,0x2da88000,0x2da83000,0xada88000,0xada8b000,0xaa1f8000,0xaf64ada8,0xaf64b000,0xaa1fada8,
0x00000000,0x00000000,0x00000000,0x00000000,0x2a1f0000,0x2f642da8,0x2f643000,0x2a1f2da8,0x2da80000,0x2da83000,0xada80000,0xada8b000,
0x2f640000,0xaa1f2da8,0xaa1fb000,0x2f642da8,0x30000000,0xb0000000,0x30000000,0xb0000000,0x2f640000,0xaa1fada8,0xaa1f3000,0x2f64ada8,
0x2da80000,0x2da8b000,0xada80000,0xada83000,0x2a1f0000,0x2f64ada8,0x2f64b000,0x2a1fada8,0x00000000,0x00000000,0x00000000,0x00000000,
0xaa1f0000,0xaf64ada8,0xaf64b000,0xaa1fada8,0x2da80000,0x2da83000,0xada80000,0xada8b000,0xaf640000,0x2a1fada8,0x2a1f3000,0xaf64ada8,
0x30000000,0xb0000000,0x30000000,0xb0000000,0xaf640000,0x2a1f2da8,0x2a1fb000,0xaf642da8,0x2da80000,0x2da8b000,0xada80000,0xada83000,
0xaa1f0000,0xaf642da8,0xaf643000,0xaa1f2da8,0x30003000,0x30003000,0x30003000,0x30003000,0x2f643000,0x2a1f2da8,0xaa1f0000,0xaf64ada8,
0x2da83000,0xada80000,0xada8b000,0x2da88000,0x2a1f3000,0xaf64ada8,0x2f648000,0xaa1f2da8,0x00003000,0x8000b000,0x00003000,0x8000b000,
0xaa1f3000,0x2f64ada8,0xaf640000,0x2a1f2da8,0xada83000,0x2da88000,0x2da8b000,0xada80000,0xaf643000,0xaa1f2da8,0x2a1f8000,0x2f64ada8,
0x30003000,0x30003000,0x30003000,0x30003000,0xaf64b000,0xaa1fada8,0x2a1f8000,0x2f642da8,0x2da83000,0xada80000,0xada8b000,0x2da88000,
0xaa1fb000,0x2f642da8,0xaf640000,0x2a1fada8,0x00003000,0x8000b000,0x00003000,0x8000b000,0x2a1fb000,0xaf642da8,0x2f648000,0xaa1fada8,
0xada83000,0x2da88000,0x2da8b000,0xada80000,0x2f64b000,0x2a1fada8,0xaa1f0000,0xaf642da8,0x00000000,0x00000000,0x00000000,0x00000000,
0xaa1f0000,0xaf642da8,0xaf643000,0xaa1f2da8,0xada80000,0xada83000,0x2da80000,0x2da8b000,0xaf640000,0x2a1f2da8,0x2a1fb000,0xaf642da8,
0xb0000000,0x30000000,0xb0000000,0x30000000,0xaf640000,0x2a1fada8,0x2a1f3000,0xaf64ada8,0xada80000,0xada8b000,0x2da80000,0x2da83000,
0xaa1f0000,0xaf64ada8,0xaf64b000,0xaa1fada8,0x00000000,0x00000000,0x00000000,0x00000000,0x2a1f0000,0x2f64ada8,0x2f64b000,0x2a1fada8,
0xada80000,0xada83000,0x2da80000,0x2da8b000,0x2f640000,0xaa1fada8,0xaa1f3000,0x2f64ada8,0xb0000000,0x30000000,0xb0000000,0x30000000,
0x2f640000,0xaa1f2da8,0xaa1fb000,0x2f642da8,0xada80000,0xada8b000,0x2da80000,0x2da83000,0x2a1f0000,0x2f642da8,0x2f643000,0x2a1f2da8,
0xb0003000,0xb0003000,0xb0003000,0xb0003000,0xaf643000,0xaa1f2da8,0x2a1f0000,0x2f64ada8,0xada83000,0x2da80000,0x2da8b000,0xada88000,
0xaa1f3000,0x2f64ada8,0xaf648000,0x2a1f2da8,0x80003000,0x0000b000,0x80003000,0x0000b000,0x2a1f3000,0xaf64ada8,0x2f640000,0xaa1f2da8,
0x2da83000,0xada88000,0xada8b000,0x2da80000,0x2f643000,0x2a1f2da8,0xaa1f8000,0xaf64ada8,0xb0003000,0xb0003000,0xb0003000,0xb0003000,
0x2f64b000,0x2a1fada8,0xaa1f8000,0xaf642da8,0xada83000,0x2da80000,0x2da8b000,0xada88000,0x2a1fb000,0xaf642da8,0x2f640000,0xaa1fada8,
0x80003000,0x0000b000,0x80003000,0x0000b000,0xaa1fb000,0x2f642da8,0xaf648000,0x2a1fada8,0x2da83000,0xada88000,0xada8b000,0x2da80000,
0xaf64b000,0xaa1fada8,0x2a1f0000,0x2f642da8};

constexpr int kThreads = 384;
constexpr int kCtas = 128;

constexpr uint32_t SM_BASE = 1024;
constexpr uint32_t QKV_STAGE = 32768;
constexpr uint32_t SLOT = 16384;
constexpr uint32_t SM_KV = 2 * SLOT;
constexpr uint32_t SM_SIG = 131072;
constexpr uint32_t SM_STG = 196608;
constexpr uint32_t SM_Q = SM_STG;
constexpr uint32_t SM_Y0 = 3 * SLOT;
constexpr uint32_t SM_YT = SM_STG + 16384;
constexpr uint32_t SM_TW = SM_STG + 24576, SM_ONES = SM_TW + 2048, SM_F1 = SM_ONES + 2048, SM_F2 = SM_F1 + 4096;
constexpr uint32_t SM_BAR = SM_F2 + 2048;
constexpr uint32_t SM_SC = SM_BAR + 640;
constexpr uint32_t SM_TOTAL = 232448;
constexpr uint32_t A_SLOTS = 0xA02B1, B_SLOTS = 0x97654;

enum Bar { B_QKV_EMPTY = 0, B_QKV_DONE = 4,
           B_OUT_EMPTY = 8,
           B_H_FULL = 16, B_YIN = 19, B_RDY0 = 21, B_Q_FULL = 22, B_ZEROED = 23,
           B_OUT_FULL = 24, B_PREP_FULL = 29,
           B_RDY1 = 32, B_STG_FREE = 33, B_OT_FREE = 36, B_Y_READY = 38, B_FLAGS1 = 39,
           B_SEG = 40, B_SIG_READY = 44,
           B_KVP = 48, B_O_WRITTEN = 49, B_SLOT_FREE = 51, B_CONV_DONE = 52,
           B_PREP_EMPTY = 56, B_KV_READY = 59,
           B_QKV_FULL = 64, B_FIRST = 68 };
constexpr uint32_t BAR_LOG2 = 0x13200044;

constexpr int KV_SLICE = 640;
constexpr int XCH_FLAG = 2 * SLOT + 17 * KV_SLICE;
constexpr int XCH_BYTES = 11 * 4096;

struct Params {
  CUtensorMap x, w, wk, wo, outa, k, v, q;
  const __nv_bfloat16* shift_k;
  const __nv_bfloat16* ssm_k;
  const __nv_bfloat16* ssm_d;
  const __nv_bfloat16* q_ptr;
  __nv_bfloat16* out_ptr;
  const __nv_bfloat16* wo_ptr;
  int zero;
};

__device__ __align__(128) uint8_t g_xch[kCtas][XCH_BYTES];
__device__ unsigned g_ready, g_epoch[kCtas];

#define TSTAMP(cond, i) do { } while (0)
#define GSTAMP(cond, i) do { } while (0)
#define LOOPSTAMP(id, cond, i) do { } while (0)

constexpr int kSpinLimit = 1 << 17;

DEVI void mbar_init(uint32_t a, uint32_t c) { asm volatile("mbarrier.init.shared::cta.b64 [%0], %1;" :: "r"(a), "r"(c) : "memory"); }
DEVI void mbar_expect(uint32_t a, uint32_t b) { asm volatile("mbarrier.arrive.expect_tx.shared::cta.b64 _, [%0], %1;" :: "r"(a), "r"(b) : "memory"); }
DEVI void mbar_arrive(uint32_t a) { asm volatile("mbarrier.arrive.shared::cta.b64 _, [%0];" :: "r"(a) : "memory"); }
DEVI void mbar_arrive_if(uint32_t a, bool pred) {
  asm volatile("{\n.reg .pred p;\nsetp.ne.b32 p, %1, 0;\n@p mbarrier.arrive.shared::cta.b64 _, [%0];\n}" :: "r"(a), "r"((int)pred) : "memory");
}
DEVI void mbar_wait(uint32_t a, uint32_t parity) {
  asm volatile("{\n.reg .pred p;\n.reg .u32 n;\nmov.u32 n, 0;\nW_LOOP:\n"
               "mbarrier.try_wait.parity.shared::cta.b64 p, [%0], %1;\nadd.u32 n, n, 1;\n"
               "setp.lt.and.u32 p, n, %2, !p;\n@p bra W_LOOP;\n}"
               :: "r"(a), "r"(parity), "n"(kSpinLimit) : "memory");
}
DEVI bool mbar_test(uint32_t a, uint32_t parity) {
  uint32_t ok;
  asm volatile("{\n.reg .pred p;\nmbarrier.test_wait.parity.shared::cta.b64 p, [%1], %2;\nselp.u32 %0, 1, 0, p;\n}" : "=r"(ok) : "r"(a), "r"(parity) : "memory");
  return ok;
}
DEVI bool elect() {
  uint32_t ok;
  asm volatile("{\n.reg .pred p;\nelect.sync _|p, 0xffffffff;\nselp.u32 %0, 1, 0, p;\n}" : "=r"(ok));
  return ok;
}
DEVI void flag_wait(const unsigned* p, unsigned target) {
  int n = 0; unsigned v;
  do {
    asm volatile("ld.acquire.gpu.global.u32 %0, [%1];" : "=r"(v) : "l"(p) : "memory");
  } while ((int)(v - target) < 0 && ++n < kSpinLimit);
}
DEVI uint32_t clock32() { uint32_t t; asm volatile("mov.u32 %0, %%clock;" : "=r"(t) :: "memory"); return t; }
DEVI void delay(uint32_t cycles) { const uint32_t t = clock32(); while (clock32() - t < cycles) { } }
DEVI void st_relaxed(void* p, uint32_t v) { asm volatile("st.relaxed.gpu.global.b32 [%0], %1;" :: "l"(p), "r"(v) : "memory"); }
DEVI uint32_t ld_relaxed(const void* p) { uint32_t v; asm volatile("ld.relaxed.gpu.global.b32 %0, [%1];" : "=r"(v) : "l"(p) : "memory"); return v; }
DEVI void ld_relaxed4(uint32_t* v, const void* p) {
  asm volatile("ld.relaxed.gpu.global.v4.b32 {%0,%1,%2,%3}, [%4];" : "=r"(v[0]), "=r"(v[1]), "=r"(v[2]), "=r"(v[3]) : "l"(p) : "memory");
}
template <int N> DEVI uint32_t umax(const uint32_t* v) {
  if constexpr (N == 1) return v[0];
  else if constexpr (N == 2) return max(v[0], v[1]);
  else if constexpr (N <= 6) return __vimax3_u32(v[0], v[1], umax<N - 2>(v + 2));
  else return __vimax3_u32(umax<N / 3 | 1>(v), umax<N / 3 | 1>(v + (N / 3 | 1)), umax<N - 2 * (N / 3 | 1)>(v + 2 * (N / 3 | 1)));
}
template <int N> DEVI bool all_arrived(const uint32_t* v) { return __all_sync(0xffffffffu, umax<N>(v) != 0xffffffffu); }
DEVI void flag_add(unsigned* p) {
  asm volatile("fence.release.gpu;\nred.relaxed.gpu.global.add.u32 [%0], 1;" :: "l"(p) : "memory");
}
DEVI void fence_async_smem() { asm volatile("fence.proxy.async.shared::cta;" ::: "memory"); }
DEVI void bar_sync(int id, int n) { asm volatile("bar.sync %0, %1;" :: "r"(id), "r"(n) : "memory"); }
DEVI void cluster_arrive() { asm volatile("barrier.cluster.arrive.relaxed.aligned;" ::: "memory"); }
DEVI void cluster_wait() { asm volatile("barrier.cluster.wait.aligned;" ::: "memory"); }
DEVI void wg_fence() { asm volatile("wgmma.fence.sync.aligned;" ::: "memory"); }
DEVI void wg_commit() { asm volatile("wgmma.commit_group.sync.aligned;" ::: "memory"); }
template <int N> DEVI void wg_wait() { asm volatile("wgmma.wait_group.sync.aligned %0;" :: "n"(N) : "memory"); }
template <int N> DEVI void pin(uint32_t* r) {
#pragma unroll
  for (int i = 0; i < N; i++) asm volatile("" : "+r"(r[i]) :: "memory");
}
template <int N> DEVI void pin(float* r) {
#pragma unroll
  for (int i = 0; i < N; i++) asm volatile("" : "+f"(r[i]) :: "memory");
}

DEVI void sched_fence(int zero, int id) { asm volatile("{\n.reg .pred p;\nsetp.eq.b32 p, %0, %1;\nS_LOOP:\n@p st.volatile.shared.b32 [%0], %0;\n@p bra S_LOOP;\n}" :: "r"(zero), "r"(id + 1) : "memory"); }
DEVI void pin_range(float* r, int i0, int i1) {
#pragma unroll
  for (int i = i0; i < i1; i++) asm volatile("" : "+f"(r[i]) :: "memory");
}
DEVI void keep(uint32_t& x) { asm volatile("" : "+r"(x) :: "memory"); }
DEVI void keep(int& x) { asm volatile("" : "+r"(x) :: "memory"); }
template <class T> DEVI void keep(T*& x) { asm volatile("" : "+l"(x) :: "memory"); }

DEVI void tma2d(uint32_t dst, const CUtensorMap* m, int c0, int c1, uint32_t bar) {
  asm volatile("cp.async.bulk.tensor.2d.shared::cluster.global.mbarrier::complete_tx::bytes [%0], [%1, {%3, %4}], [%2];"
               :: "r"(dst), "l"(m), "r"(bar), "r"(c0), "r"(c1) : "memory");
}
DEVI void tma2d_mc(uint32_t dst, const CUtensorMap* m, int c0, int c1, uint32_t bar) {
  asm volatile("cp.async.bulk.tensor.2d.shared::cluster.global.mbarrier::complete_tx::bytes.multicast::cluster [%0], [%1, {%3, %4}], [%2], %5;"
               :: "r"(dst), "l"(m), "r"(bar), "r"(c0), "r"(c1), "h"((uint16_t)3) : "memory");
}
DEVI void tma3d(uint32_t dst, const CUtensorMap* m, int c0, int c1, int c2, uint32_t bar) {
  asm volatile("cp.async.bulk.tensor.3d.shared::cluster.global.mbarrier::complete_tx::bytes [%0], [%1, {%3, %4, %5}], [%2];"
               :: "r"(dst), "l"(m), "r"(bar), "r"(c0), "r"(c1), "r"(c2) : "memory");
}
DEVI void tma3d_mc(uint32_t dst, const CUtensorMap* m, int c0, int c1, int c2, uint32_t bar) {
  asm volatile("cp.async.bulk.tensor.3d.shared::cluster.global.mbarrier::complete_tx::bytes.multicast::cluster [%0], [%1, {%3, %4, %5}], [%2], %6;"
               :: "r"(dst), "l"(m), "r"(bar), "r"(c0), "r"(c1), "r"(c2), "h"((uint16_t)3) : "memory");
}
DEVI void tma2d_store(const CUtensorMap* m, uint32_t src, int c0, int c1) {
  asm volatile("cp.async.bulk.tensor.2d.global.shared::cta.bulk_group [%0, {%2, %3}], [%1];" :: "l"(m), "r"(src), "r"(c0), "r"(c1) : "memory");
}
DEVI void bulk_load(uint32_t dst, const void* src, uint32_t bytes, uint32_t bar) {
  asm volatile("cp.async.bulk.shared::cluster.global.mbarrier::complete_tx::bytes [%0], [%1], %2, [%3];" :: "r"(dst), "l"(src), "r"(bytes), "r"(bar) : "memory");
}
DEVI void bulk_store(void* dst, uint32_t src, uint32_t bytes) {
  asm volatile("cp.async.bulk.global.shared::cta.bulk_group [%0], [%1], %2;" :: "l"(dst), "r"(src), "r"(bytes) : "memory");
}
DEVI uint32_t peer_addr(uint32_t a, int rank) { uint32_t r; asm("mapa.shared::cluster.u32 %0, %1, %2;" : "=r"(r) : "r"(a), "r"(rank)); return r; }
DEVI void bulk_to_peer(uint32_t dst, uint32_t src, uint32_t bytes, uint32_t bar, int rank) {
  asm volatile("cp.async.bulk.shared::cluster.shared::cta.mbarrier::complete_tx::bytes [%0], [%1], %2, [%3];"
               :: "r"(peer_addr(dst, rank)), "r"(src), "r"(bytes), "r"(peer_addr(bar, rank)) : "memory");
}
DEVI void l2_prefetch(const void* p, uint32_t bytes) {
  asm volatile("cp.async.bulk.prefetch.L2.global [%0], %1;" :: "l"(p), "r"(bytes) : "memory");
}
DEVI void l2_prefetch2d(const CUtensorMap* m, int c0, int c1) {
  asm volatile("cp.async.bulk.prefetch.tensor.2d.L2.global [%0, {%1, %2}];" :: "l"(m), "r"(c0), "r"(c1) : "memory");
}
DEVI void l2_prefetch3d(const CUtensorMap* m, int c0, int c1, int c2) {
  asm volatile("cp.async.bulk.prefetch.tensor.3d.L2.global [%0, {%1, %2, %3}];" :: "l"(m), "r"(c0), "r"(c1), "r"(c2) : "memory");
}
DEVI void bulk_commit() { asm volatile("cp.async.bulk.commit_group;" ::: "memory"); }
DEVI void bulk_wait_read() { asm volatile("cp.async.bulk.wait_group.read 0;" ::: "memory"); }
DEVI void prefetch_map(const CUtensorMap* m) { asm volatile("prefetch.tensormap [%0];" :: "l"(m) : "memory"); }
DEVI void arrive_both(uint32_t bar, int lane, bool pred = true) {
  asm volatile("{\n.reg .pred p;\n.reg .b32 r;\nsetp.ne.b32 p, %2, 0;\nmapa.shared::cluster.u32 r, %0, %1;\n@p mbarrier.arrive.shared::cluster.b64 _, [r];\n}"
               :: "r"(bar), "r"(lane & 1), "r"((int)(pred && lane < 2)) : "memory");
}

DEVI uint64_t make_desc(uint32_t off, uint32_t lbo, uint32_t sbo, uint32_t mode) {
  const uint32_t lo = (off >> 4) + (SM_BASE >> 4) + ((lbo >> 4) << 16), hi = (sbo >> 4) | (mode << 30);
  return ((uint64_t)hi << 32) | lo;
}
DEVI uint32_t pack_bf16(float lo, float hi) { uint32_t r; asm("cvt.rn.bf16x2.f32 %0, %1, %2;" : "=r"(r) : "f"(hi), "f"(lo)); return r; }
DEVI void stsm4(uint32_t addr, uint32_t r0, uint32_t r1, uint32_t r2, uint32_t r3) {
  asm volatile("stmatrix.sync.aligned.m8n8.x4.shared.b16 [%0], {%1,%2,%3,%4};" :: "r"(addr), "r"(r0), "r"(r1), "r"(r2), "r"(r3) : "memory");
}
DEVI void stsm4_t(uint32_t addr, uint32_t r0, uint32_t r1, uint32_t r2, uint32_t r3) {
  asm volatile("stmatrix.sync.aligned.m8n8.x4.trans.shared.b16 [%0], {%1,%2,%3,%4};" :: "r"(addr), "r"(r0), "r"(r1), "r"(r2), "r"(r3) : "memory");
}
DEVI void ldsm4(uint32_t* r, uint32_t addr) {
  asm volatile("ldmatrix.sync.aligned.m8n8.x4.shared.b16 {%0,%1,%2,%3}, [%4];" : "=r"(r[0]), "=r"(r[1]), "=r"(r[2]), "=r"(r[3]) : "r"(addr) : "memory");
}
DEVI void ldsm4_t(uint32_t* r, uint32_t addr) {
  asm volatile("ldmatrix.sync.aligned.m8n8.x4.trans.shared.b16 {%0,%1,%2,%3}, [%4];" : "=r"(r[0]), "=r"(r[1]), "=r"(r[2]), "=r"(r[3]) : "r"(addr) : "memory");
}
DEVI uint4 lds128(uint32_t a) {
  uint4 v; asm volatile("ld.shared.v4.b32 {%0,%1,%2,%3}, [%4];" : "=r"(v.x), "=r"(v.y), "=r"(v.z), "=r"(v.w) : "r"(a) : "memory"); return v;
}
DEVI uint32_t bmul2(uint32_t a, uint32_t b) { uint32_t r; asm("mul.rn.bf16x2 %0, %1, %2;" : "=r"(r) : "r"(a), "r"(b)); return r; }
DEVI uint32_t bfma2(uint32_t a, uint32_t b, uint32_t c) { uint32_t r; asm("fma.rn.bf16x2 %0, %1, %2, %3;" : "=r"(r) : "r"(a), "r"(b), "r"(c)); return r; }
DEVI float bf_lo(uint32_t w) { return __uint_as_float(w << 16); }
DEVI float bf_hi(uint32_t w) { return __uint_as_float(w & 0xffff0000u); }
DEVI uint32_t elu1(float a0, float a1) {
  constexpr float L = 1.4426950408889634f;
  float e0, e1;
  asm("ex2.approx.ftz.f32 %0, %1;" : "=f"(e0) : "f"(-fabsf(fmaf(a0, L, -L))));
  asm("ex2.approx.ftz.f32 %0, %1;" : "=f"(e1) : "f"(-fabsf(fmaf(a1, L, -L))));
  return pack_bf16(fmaxf(e0, a0), fmaxf(e1, a1));
}
DEVI float rcp(float x) { float r; asm("rcp.approx.ftz.f32 %0, %1;" : "=f"(r) : "f"(x)); return r; }
DEVI uint32_t add_eps(uint32_t x) { uint32_t r; asm("add.rn.bf16x2 %0, %1, %2;" : "=r"(r) : "r"(x), "r"(0x35863586u)); return r; }

DEVI uint32_t hmul(uint32_t a, uint32_t b) { uint32_t r; asm("mul.rn.f16x2 %0, %1, %2;" : "=r"(r) : "r"(a), "r"(b)); return r; }
DEVI uint32_t hfma(uint32_t a, uint32_t b, uint32_t c) { uint32_t r; asm("fma.rn.f16x2 %0, %1, %2, %3;" : "=r"(r) : "r"(a), "r"(b), "r"(c)); return r; }
DEVI uint32_t hneg(uint32_t a) { uint32_t r; asm("neg.f16x2 %0, %1;" : "=r"(r) : "r"(a)); return r; }
DEVI uint32_t hadd(uint32_t a, uint32_t b) { uint32_t r; asm("add.rn.f16x2 %0, %1, %2;" : "=r"(r) : "r"(a), "r"(b)); return r; }
DEVI uint32_t hsub(uint32_t a, uint32_t b) { uint32_t r; asm("sub.rn.f16x2 %0, %1, %2;" : "=r"(r) : "r"(a), "r"(b)); return r; }
struct Cx { uint32_t re, im; };
DEVI Cx cmul(Cx a, Cx b) { return {hfma(a.re, b.re, hneg(hmul(a.im, b.im))), hfma(a.re, b.im, hmul(a.im, b.re))}; }
DEVI Cx cfma(Cx a, Cx b, Cx c) { return {hfma(a.re, b.re, hfma(hneg(a.im), b.im, c.re)), hfma(a.re, b.im, hfma(a.im, b.re, c.im))}; }
DEVI Cx rot(Cx a, Cx t) {
  const uint32_t x = hfma(hneg(t.re), a.im, a.re), y = hfma(t.im, x, a.im);
  return {hfma(hneg(t.re), y, x), y};
}
struct Fft {
  uint32_t fa[8];
  Cx tw[2];
  uint32_t vld;
  uint64_t dF2a, dF2b;
  uint32_t vst;
  DEVI void stage1(uint32_t* d1, uint32_t slot) const {
    wg_fence();
    fft1_init(d1, fa[0], fa[1], fa[2], fa[3], make_desc(slot, 4096, 1024, 1));
    fft1_acc(d1, fa[4], fa[5], fa[6], fa[7], make_desc(slot + 2048, 4096, 1024, 1));
    wg_commit();
  }
  DEVI void stage2(uint32_t* d, const Cx* t) const {
    wg_fence();
    fft2_init(d, t[0].re, t[1].re, t[2].re, t[3].re, dF2a);
    fft2_acc(d, t[0].im, t[1].im, t[2].im, t[3].im, dF2b);
    wg_commit();
  }
  template <int PR> DEVI void fwd(const uint32_t* d1, uint32_t* d2) const {
    Cx t[4];
#pragma unroll
    for (int e = 0; e < 4; e++) {
      const int j = 8 * (PR & 1) + 4 * (e >> 1) + 2 * (PR >> 1) + (e & 1);
      t[e] = rot({d1[2 * j], d1[2 * j + 1]}, tw[e >> 1]);
    }
    stage2(d2 + 8 * PR, t);
  }
  static DEVI Cx U(const uint32_t* d2, int p, int hi) { return {d2[16 * (p >> 1) + 2 * hi + (p & 1)], d2[16 * (p >> 1) + 4 + 2 * hi + (p & 1)]}; }
  static DEVI Cx H(const uint32_t* d2, int p, int hi) { return U(d2 + 8, p, hi); }
  DEVI void prod01(const uint32_t* d2, Cx* p1, uint32_t* d3) const {
    Cx z[4];
#pragma unroll
    for (int hi = 0; hi < 2; hi++) {
      const Cx p0 = cmul(H(d2, 0, hi), U(d2, 0, hi));
      p1[hi] = cfma(H(d2, 1, hi), U(d2, 0, hi), cmul(H(d2, 0, hi), U(d2, 1, hi)));
      z[2 * hi] = {p0.im, p0.re};
      z[2 * hi + 1] = {hsub(p1[hi].im, p0.re), hadd(p1[hi].re, p0.im)};
    }
    stage2(d3, z);
  }
  DEVI void prod23(const uint32_t* d2, const Cx* p1, uint32_t* d3) const {
    Cx z[4];
#pragma unroll
    for (int hi = 0; hi < 2; hi++) {
      const Cx p2 = cfma(H(d2, 2, hi), U(d2, 0, hi), cfma(H(d2, 0, hi), U(d2, 2, hi), cmul(H(d2, 1, hi), U(d2, 1, hi))));
      const Cx z3 = cfma(H(d2, 3, hi), U(d2, 0, hi), cfma(H(d2, 2, hi), U(d2, 1, hi),
                    cfma(H(d2, 1, hi), U(d2, 2, hi), cfma(H(d2, 0, hi), U(d2, 3, hi), {p2.im, hneg(p2.re)}))));
      z[2 * hi] = {hsub(p2.im, p1[hi].re), hadd(p2.re, p1[hi].im)};
      z[2 * hi + 1] = {z3.im, z3.re};
    }
    stage2(d3 + 8, z);
  }
  template <int PB> DEVI void inv(const uint32_t* d3, uint32_t slot) const {
    Cx v[4];
#pragma unroll
    for (int e = 0; e < 4; e++) {
      const int r = 8 * PB + 2 * (e & 1) + (e >> 1);
      v[e] = rot({d3[r], d3[r + 4]}, tw[e & 1]);
    }
    stsm4(slot + (vst ^ (PB * 64)), v[0].im, v[1].im, v[2].im, v[3].im);
    stsm4(slot + 1024 + (vst ^ (PB * 64)), v[0].re, v[1].re, v[2].re, v[3].re);
  }
  DEVI void last_load(uint32_t* a, uint32_t slot, int wg) const {
    bar_sync(2 + wg, 128);
#pragma unroll
    for (int ks = 0; ks < 4; ks++) ldsm4_t(a + 4 * ks, vld + slot + ks * 2048);
  }
  DEVI void last_mma(float* dy, const uint32_t* a) const {
    wg_fence();
    fft3_init(dy, a[0], a[1], a[2], a[3], make_desc(SM_F1, 128, 1024, 0));
#pragma unroll
    for (int ks = 1; ks < 4; ks++) fft3_acc(dy, a[4 * ks], a[4 * ks + 1], a[4 * ks + 2], a[4 * ks + 3], make_desc(SM_F1 + ks * 256, 128, 1024, 0));
    wg_commit();
  }
  DEVI void last(float* dy, uint32_t slot, int wg) const { uint32_t a[16]; last_load(a, slot, wg); last_mma(dy, a); }
  static DEVI void store_y(const float* dy, uint32_t a) {
    stsm4_t(a, pack_bf16(dy[0], dy[1]), pack_bf16(dy[2], dy[3]), pack_bf16(dy[4], dy[5]), pack_bf16(dy[6], dy[7]));
    stsm4_t(a + 512, pack_bf16(dy[8], dy[9]), pack_bf16(dy[10], dy[11]), pack_bf16(dy[12], dy[13]), pack_bf16(dy[14], dy[15]));
  }
};
DEVI uint32_t normalize(uint32_t* x, uint32_t dst) {
  uint32_t m = x[0];
#pragma unroll
  for (int i = 1; i < 32; i++) asm("max.xorsign.abs.bf16x2 %0, %0, %1;" : "+r"(m) : "r"(x[i]));
  const uint32_t e = min(__reduce_max_sync(0xffffffffu, max(m & 0x7fffu, (m >> 16) & 0x7fffu)) >> 7, 252u);
  if (e > 140) {
#pragma unroll
    for (int i = 0; i < 32; i++) x[i] = bmul2(x[i], 15u * 0x00800080u);
  }
  const uint32_t sc = (e > 140 ? 253u - e : 141u - e) * 0x00800080u;
#pragma unroll
  for (int i = 0; i < 8; i++) {
    uint32_t y[4];
#pragma unroll
    for (int n = 0; n < 4; n++) {
      const uint32_t w = bmul2(x[4 * i + n], sc);
      y[n] = (w & 0x7fff7fffu) * 7u + w;
    }
    stsm4((dst ^ ((i >> 1) << 4)) + (i & 1) * 2048, y[0], y[1], y[2], y[3]);
  }
  return e;
}
#define HSTART 3
#define PSTART 5
#define PF0 28
#define PD1 600
#define PD2 500
#define PD3 900
#define FDELAY 100
#define C1DELAY 200
#define FORCE_REDO 0
static_assert(HSTART <= 4 && PF0 >= HSTART + 19 && PF0 <= 28, "producer schedule");

__global__ void __cluster_dims__(2, 1, 1) __launch_bounds__(kThreads, 1)
fused_kernel(const __grid_constant__ Params P) {
  extern __shared__ __align__(1024) uint8_t smem[];
  if (threadIdx.x == 0) { prefetch_map(&P.x); prefetch_map(&P.w); prefetch_map(&P.wk); prefetch_map(blockIdx.x & 1 ? &P.v : &P.k); }
  const uint32_t sb = __shfl_sync(0xffffffffu, (uint32_t)__cvta_generic_to_shared(smem), 0);
  const int tid = threadIdx.x, lane = tid & 31;
  const int warp = __shfl_sync(0xffffffffu, tid >> 5, 0);
  const int bc = blockIdx.x >> 1, late = ((bc - 36) * 37) >> 8;
  const int rp = bc < 4 ? 0 : bc < 36 ? (bc - 4) & 7 : bc - 35 - 7 * late, j = bc < 4 ? 4 + bc : bc < 36 ? (bc - 4) >> 3 : 4 + late;
  const int rho = blockIdx.x & 1, cl = 8 * rp + j, cta = 2 * cl + rho, r = rp * 2 + rho;
  auto bar = [&](int i) { return sb + SM_BAR + 8u * i; };
  TSTAMP(tid == 0, 0); GSTAMP(tid == 0, 30);
  auto load_stage = [&](int it) {
    const uint32_t st = sb + (it & 3) * QKV_STAGE, fb = bar(B_QKV_FULL + (it & 3));
    mbar_expect(fb, QKV_STAGE);
    tma2d_mc(st + 24576 + rho * 4096, &P.wk, 1024 + 128 * j + 64 * rho, 32 * it, fb);
    tma3d_mc(st + 8192 + rho * 8192, &P.w, 0, 32 * it, 32 * rho + 2 * j, fb);
    tma2d(st, &P.x, 32 * it, 128 * r, fb);
  };
  if (warp == 8 && elect()) {
    mbar_init(bar(B_FIRST), 1);
    mbar_expect(bar(B_FIRST), 16384);
    tma2d(sb, &P.x, 0, 128 * r, bar(B_FIRST));
    tma3d(sb + 24576, &P.w, 0, 0, 16 + 2 * j, bar(B_FIRST));
    mbar_init(bar(B_QKV_FULL), 1);
    mbar_expect(bar(B_QKV_FULL), 16384);
    tma3d(sb + 8192, &P.w, 0, 0, 2 * j, bar(B_QKV_FULL));
    tma3d(sb + 16384, &P.w, 0, 0, 32 + 2 * j, bar(B_QKV_FULL));
    for (int i = 1; i < 4; i++) mbar_init(bar(B_QKV_FULL + i), 1);
    asm volatile("fence.mbarrier_init.release.cluster;" ::: "memory");
  }
  LOOPSTAMP(3, tid == 256, 13);
  __syncwarp();
  cluster_arrive();

  if (warp < 8) {
    asm volatile("setmaxnreg.inc.sync.aligned.u32 224;");
    const int wg = warp >> 2, wq = warp & 3;
    const int zero = __shfl_sync(0xffffffffu, P.zero, 0);
    const uint32_t orow = wq * 2048 + (lane & 15) * 128, ox = ((lane >> 4) ^ (lane & 7)) << 4;
    float aq[64];
    Fft F;
    uint32_t a1[32];
    {
      float ak[64], avq[128];
      auto k_step = [&](uint32_t st, int kk) {
        mma_tn(ak, make_desc(st + 24576 + wg * 4096 + kk * 2048, 4096, 1024, 1), make_desc(st + kk * 32, 16, 512, 2));
      };
      auto vq_step = [&](uint32_t st, int kk) {
        mma_nt256(avq, make_desc(st + wg * 4096 + kk * 32, 16, 512, 2), make_desc(st + 8192 + kk * 2048, 4096, 1024, 1));
      };
#pragma unroll
      for (int i = 0; i < 64; i++) { ak[i] = 1.f; avq[i] = 1.f; avq[64 + i] = 0.f; }
      pin<64>(ak); pin<128>(avq);
      cluster_wait();
      cluster_arrive();
      cluster_wait();
      LOOPSTAMP(3, tid == 0, 17);
      mbar_wait(bar(B_FIRST), 0);
      TSTAMP(tid == 0, 1);
      wg_fence();
      k_step(0, 0); k_step(0, 1);
      wg_commit();
      mbar_wait(bar(B_QKV_FULL), 0);
      wg_fence();
      vq_step(0, 0); vq_step(0, 1);
      wg_commit();
#pragma unroll 1
      for (int it = 1; it < 29; ++it) {
        mbar_wait(bar(B_QKV_FULL + (it & 3)), (it >> 2) & 1);
        TSTAMP(tid == 0 && it == 4, 6); TSTAMP(tid == 0 && it == 12, 29); LOOPSTAMP(1, tid == 0 && it < 27, 1 + it); LOOPSTAMP(3, tid == 0 && it < 12, 1 + it);
        const uint32_t st = (it & 3) * QKV_STAGE;
        wg_fence();
        k_step(st, 0);
        wg_commit();
        wg_wait<1>();
        arrive_both(bar(B_QKV_EMPTY + ((it - 1) & 3)), lane);
        wg_fence();
        vq_step(st, 0);
        k_step(st, 1);
        vq_step(st, 1);
        wg_commit();
      }
#pragma unroll 1
      for (int s = 1; s < 4; ++s) {
        mbar_wait(bar(B_QKV_FULL + s), 1);
        wg_fence();
        k_step(s * QKV_STAGE, 0);
        k_step(s * QKV_STAGE, 1);
        wg_commit();
      }
      uint32_t pk[32];
      auto phi_k = [&](int i0, int i1) {
#pragma unroll
        for (int i = i0; i < i1; i++) { pk[i] = elu1(ak[2 * i], ak[2 * i + 1]); asm volatile("" : "+r"(pk[i]) :: "memory"); }
        sched_fence(zero, i0);
      };
#pragma unroll
      for (int n = 0; n < 6; n++) {
        wg_fence();
        vq_step((1 + (n >> 1)) * QKV_STAGE, n & 1);
        wg_commit();
        if (n == 0) {
          wg_wait<1>();
          pin<64>(ak);
          TSTAMP(tid == 0, 2);
          bar_sync(1, 256);
        }
        phi_k(n ? 6 * n - 4 : 0, 6 * n + 2);
      }
      mbar_wait(bar(B_SIG_READY), 0);
      ldsm4_t(F.fa, sb + SM_F1 + (lane >> 4) * 1024 + wq * 256 + (lane & 15) * 16);
      ldsm4_t(F.fa + 4, sb + SM_F1 + 2048 + (lane >> 4) * 1024 + wq * 256 + (lane & 15) * 16);
      const uint4 tw = lds128(sb + SM_TW + (tid & 127) * 16);
      F.tw[0] = {tw.x, tw.y}; F.tw[1] = {tw.z, tw.w};
      F.vld = sb + ((lane >> 4) * 8 + (lane & 7)) * 128 + (((2 * wq + ((lane >> 3) & 1)) ^ (lane & 7)) << 4);
      F.dF2a = make_desc(SM_F2, 128, 512, 0) + (uint64_t)zero * 0x100000001ull;
      F.dF2b = F.dF2a + 16;
      F.vst = sb + (16 * wq + (lane & 7)) * 128 + (((lane >> 3) ^ (lane & 7)) << 4);
      wg_wait<0>();
      pin<128>(avq);
      arrive_both(bar(B_QKV_DONE), lane);
      TSTAMP(tid == 0, 3);
#pragma unroll
      for (int t = 0; t < 8; t++) {
        const float* b = avq + 64 + 8 * t;
        stsm4(sb + (t >> 2) * SLOT + wg * 8192 + orow + (ox ^ ((t & 3) << 5)), pack_bf16(b[0], b[1]), pack_bf16(b[2], b[3]), pack_bf16(b[4], b[5]), pack_bf16(b[6], b[7]));
      }
#pragma unroll
      for (int i = 0; i < 64; i++) aq[i] = avq[i];
      fence_async_smem();
      bar_sync(1, 256);
      float dkv[36];
#pragma unroll
      for (int ks = 0; ks < 8; ks++) {
        const uint32_t va = wg * SLOT + ks * 2048;
        const uint64_t db = make_desc(va, SM_ONES - va, 1024, 1);
        uint32_t a[4];
        pin<4>(pk + 4 * ks);
#pragma unroll
        for (int i = 0; i < 4; i++) a[i] = add_eps(pk[4 * ks + i]);
        wg_fence();
        if (ks == 0) mma_kv_init(dkv, a[0], a[1], a[2], a[3], db);
        else mma_kv_acc(dkv, a[0], a[1], a[2], a[3], db);
      }
      wg_commit();
      uint8_t* box = g_xch[warp * 16 + j] + 2 * SLOT + r * KV_SLICE + lane * 16;
      uint8_t* zbox = box + (lane & 1) * 8 * XCH_BYTES + 512 + (lane & 28) - lane * 16;
      keep(box); keep(zbox);
      mbar_wait(bar(B_ZEROED), 0);
      wg_wait<0>();
      pin<36>(dkv);
      F.stage1(a1, SM_SIG + wg * 8192);
      TSTAMP(tid == 0, 4);
      auto put = [&](const float* d) {
#pragma unroll
        for (int m = 0; m < 2; m++)
          asm volatile("st.relaxed.gpu.global.v4.b32 [%0], {%1,%2,%3,%4};" :: "l"(box + m * 8 * XCH_BYTES), "r"(pack_bf16(d[2 * m], d[2 * m + 1])),
                       "r"(pack_bf16(d[2 * m + 4], d[2 * m + 5])), "r"(pack_bf16(d[2 * m + 8], d[2 * m + 9])), "r"(pack_bf16(d[2 * m + 12], d[2 * m + 13])) : "memory");
      };
      if (wq < 2) put(dkv); else put(dkv + 16);
      asm volatile("{\n.reg .pred p;\nsetp.eq.b32 p, %2, 0;\n@p st.relaxed.gpu.global.b32 [%0], %1;\n}" :: "l"(zbox), "f"(lane & 1 ? dkv[34] : dkv[32]), "r"(lane & 2) : "memory");
      __syncwarp();
      mbar_arrive_if(bar(B_KVP), lane == 0);
      TSTAMP(tid == 0, 5);
    }

    uint32_t pq[32];
    auto phi_q = [&](int i0, int i1) {
      pin_range(aq, 2 * i0, 2 * i1);
#pragma unroll
      for (int i = i0; i < i1; i++) { pq[i] = add_eps(elu1(aq[2 * i], aq[2 * i + 1])); keep(pq[i]); }
    };
    uint32_t a2[32];
    float by[16];
    auto conv_pair = [&](uint32_t sa, uint32_t ya, uint32_t first) {
      const uint32_t sc = sa + SLOT;
      uint32_t b1[32], b2[32], a3[16], b3[16];
      float ay[16];
      Cx pa[2], pb[2];
      F.stage1(b1, sc);
      F.prod01(a2, pa, a3);
      F.prod23(a2, pa, a3);
      uint32_t va[16];
      wg_wait<1>(); pin<32>(b1); pin<8>(a3);
      F.fwd<0>(b1, b2); F.fwd<1>(b1, b2);
      F.inv<0>(a3, sa);
      F.fwd<2>(b1, b2);
      wg_wait<3>(); pin<8>(a3 + 8);
      F.inv<1>(a3, sa);
      F.fwd<3>(b1, b2);
      F.last_load(va, sa, wg);
      wg_wait<2>(); pin<16>(b2);
      F.prod01(b2, pb, b3);
      F.last_mma(ay, va);
      wg_wait<2>(); pin<16>(b2 + 16);
      F.prod23(b2, pb, b3);
      mbar_wait(bar(B_RDY1), first);
      wg_wait<1>(); pin<8>(b3); pin<16>(ay);
      mbar_arrive_if(bar(B_SLOT_FREE), lane == 0);
      F.inv<0>(b3, sc);
      Fft::store_y(ay, ya);
      wg_wait<0>(); pin<8>(b3 + 8);
      F.inv<1>(b3, sc);
    };
    const bool ylocal = (wq >> 1) == rho;
    const uint32_t yoff = sb + (wq & 1) * 1024 + ((lane ^ wg ^ (2 * rho)) << 4);
    const uint32_t ya0 = yoff + (ylocal ? SM_Y0 + wg * 8192 : SM_YT + wg * 4096), ya1 = (yoff ^ 64) + (ylocal ? SM_SIG + wg * 8192 : SM_YT + wg * 4096);
    auto pair_done = [&](uint32_t ya, int seg) {
      pin<16>(by);
      Fft::store_y(by, (ya ^ 32) + 2048);
      __syncwarp();
      mbar_arrive_if(bar(B_SEG + 2 * seg + wg), lane == 0);
    };
    const uint32_t s0 = SM_SIG + wg * 8192, s1 = s0 + 2 * SLOT;
    phi_q(0, 2);
    wg_wait<0>(); pin<32>(a1);
    bar_sync(2 + wg, 128);
    F.fwd<0>(a1, a2); phi_q(2, 5);
    F.fwd<1>(a1, a2); phi_q(5, 8);
    F.fwd<2>(a1, a2); phi_q(8, 11);
    F.fwd<3>(a1, a2); phi_q(11, 13);
    wg_wait<0>(); pin<32>(a2);
#pragma unroll 1
    for (uint32_t sa = s0;; sa += 2 * SLOT + P.zero) {
      conv_pair(sa, sa == s1 ? ya1 : ya0, sa != s1);
      if (sa == s1) break;
      F.stage1(a1, s1);
      phi_q(13, 17);
      F.last(by, s0 + SLOT, wg);
      phi_q(17, 32);
      wg_wait<0>();
      pair_done(ya0, 0);
      TSTAMP(tid == 0, 7);
      float dn[4][20];
      pin<32>(a1);
      bar_sync(2 + wg, 128);
      F.fwd<0>(a1, a2); F.fwd<1>(a1, a2); F.fwd<2>(a1, a2);
      mbar_wait(bar(B_KV_READY), 0);
      TSTAMP(tid == 0, 8);
      auto head_mma = [&](int h) {
        wg_fence();
        const uint64_t db = make_desc(SM_KV + h * 2560, 640, 128, 0);
        const uint32_t* a = pq + 8 * h;
        mma_o_init(dn[h], a[0], a[1], a[2], a[3], db);
        mma_o_acc(dn[h], a[4], a[5], a[6], a[7], db + (1280 >> 4));
        wg_commit();
      };
      auto head_store = [&](int h) {
        pin<20>(dn[h]);
        const float i0 = rcp(dn[h][16] + 1e-6f), i1 = rcp(dn[h][18] + 1e-6f);
        const uint32_t p0 = pack_bf16(i0, i0), p1 = pack_bf16(i1, i1);
#pragma unroll
        for (int hf = 0; hf < 2; hf++) {
          const float* a = dn[h] + 8 * hf;
          const uint32_t dst = sb + (h >> 1) * SLOT + wg * 8192 + orow + (ox ^ (((h & 1) * 2 + hf) << 5));
          uint32_t o[4];
#pragma unroll
          for (int i = 0; i < 4; i++) o[i] = bmul2(pack_bf16(a[2 * i], a[2 * i + 1]), i & 1 ? p1 : p0);
          stsm4(dst, o[0], o[1], o[2], o[3]);
#pragma unroll
          for (int i = 0; i < 4; i++) pq[8 * h + 4 * hf + i] = o[i];
        }
        if (h & 1) { __syncwarp(); mbar_arrive_if(bar(B_O_WRITTEN + (h >> 1)), lane == 0); }
      };
      head_mma(0); head_mma(1);
      wg_wait<1>(); head_store(0);
      mbar_wait(bar(B_KV_READY + 1), 0);
      head_mma(2);
      wg_wait<1>(); head_store(1);
      head_mma(3);
      wg_wait<1>(); head_store(2);
      F.fwd<3>(a1, a2);
      wg_wait<1>(); head_store(3);
      wg_wait<0>();
      pin<32>(a2);
    }

    float acc[64];
    auto stage_mma = [&](int s, int kk) {
      mma_nt(acc, make_desc(((A_SLOTS >> (4 * s)) & 15) * SLOT + wg * 8192 + kk * 32, 16, 1024, 1),
             make_desc(((B_SLOTS >> (4 * s)) & 15) * SLOT + kk * 2048, 8192, 1024, 1));
    };
    {
      auto own_mma = [&](int n) {
        const uint64_t db = make_desc((4 + (n >> 2)) * SLOT + (n & 3) * 2048, 8192, 1024, 1);
        if (n == 0) mma_own_init(acc, pq[0], pq[1], pq[2], pq[3], db);
        else mma_own_acc(acc, pq[4 * n], pq[4 * n + 1], pq[4 * n + 2], pq[4 * n + 3], db);
      };
      mbar_wait(bar(B_OUT_FULL), 0);
      wg_fence();
      own_mma(0);
      wg_commit();
      F.last(by, s1 + SLOT, wg);
      wg_fence();
      own_mma(1);
      wg_commit();
      wg_wait<1>();
      pair_done(ya1, 1);
      mbar_arrive_if(bar(B_CONV_DONE), lane == 0);
      cluster_arrive();
      wg_fence();
      own_mma(2); own_mma(3);
      wg_commit();
      mbar_wait(bar(B_OUT_FULL + 1), 0);
      wg_fence();
      own_mma(4);
      wg_commit();
      wg_wait<1>();
      arrive_both(bar(B_OUT_EMPTY), lane);
      wg_fence();
      own_mma(5); own_mma(6); own_mma(7);
      wg_commit();
      int s = 2, sprev = 1;
      uint32_t ph = 0;
#pragma unroll 1
      for (int ks = 2; ks < 12; ++ks) {
        mbar_wait(bar(B_OUT_FULL + s), ph);
        LOOPSTAMP(2, tid == 0, 1 + ks);
        TSTAMP(tid == 0 && ks == 2, 13); TSTAMP(tid == 0 && ks == 9, 14);
        wg_fence();
        stage_mma(s, 0);
        wg_commit();
        wg_wait<1>();
        arrive_both(bar(B_OUT_EMPTY + sprev), lane);
        wg_fence();
#pragma unroll
        for (int kk = 1; kk < 4; kk++) stage_mma(s, kk);
        wg_commit();
        sprev = s;
        if (++s == 5) { s = 0; ph ^= 1; }
      }
      asm volatile("{\n.reg .pred p;\nsetp.ne.b32 p, %0, 0;\n@p bar.sync 1, 256;\n}" :: "r"(wg) : "memory");
#pragma unroll 1
      for (int ks = 12; ks < 16; ++ks) {
        mbar_wait(bar(B_OUT_FULL + s), ks == 15);
        wg_fence();
#pragma unroll
        for (int kk = 0; kk < 4; kk++) stage_mma(s, kk);
        wg_commit();
        if (++s == 5) s = 0;
      }
      asm volatile("{\n.reg .pred p;\nsetp.eq.b32 p, %0, 0;\n@p bar.arrive 1, 256;\n}" :: "r"(wg) : "memory");
    }
    wg_wait<0>(); pin<64>(acc);
    TSTAMP(tid == 0, 15); TSTAMP(tid == 128, 16);
#pragma unroll
    for (int hf = 0; hf < 2; hf++) {
      const uint32_t dst = sb + hf * SLOT + wg * 8192;
#pragma unroll
      for (int t = 0; t < 4; t++) {
        const float* a = acc + 32 * hf + 8 * t;
        stsm4(dst + orow + (ox ^ (t << 5)), pack_bf16(a[0], a[1]), pack_bf16(a[2], a[3]), pack_bf16(a[4], a[5]), pack_bf16(a[6], a[7]));
      }
      fence_async_smem();
      __syncwarp();
      if (elect()) { tma2d_store(&P.outa, dst + wq * 2048, 128 * j + 64 * hf, 128 * r + 16 * warp); bulk_commit(); }
    }
    const bool stale = __any_sync(0xffffffffu, acc[0] != acc[0] || acc[2] != acc[2] || FORCE_REDO);
    if (elect()) bulk_wait_read();
    TSTAMP(tid == 128, 17);
    __syncwarp();
    cluster_wait();
    TSTAMP(tid == 128, 28); GSTAMP(tid == 128, 31);
    if (stale) {
      __threadfence();
#pragma unroll
      for (int i = 0; i < 64; i++) acc[i] = 0.f;
      const int row = warp * 16 + (lane >> 2);
#pragma unroll 1
      for (int k = 0; k < 1024; k += 2) {
        const uint8_t* src = g_xch[r * 8 + (k >> 7)] + ((k >> 6) & 1) * SLOT + row * 128 + ((((k >> 3) ^ row) & 7) << 4) + (k & 7) * 2;
        uint32_t a[2];
        int n = 0;
        do { a[0] = ld_relaxed(src); a[1] = ld_relaxed(src + 1024); } while (!all_arrived<2>(a) && ++n < kSpinLimit);
#pragma unroll 1
        for (int e = 0; e < 2; e++) {
          const float a0 = e ? bf_hi(a[0]) : bf_lo(a[0]), a1 = e ? bf_hi(a[1]) : bf_lo(a[1]);
          const uint32_t* wrow = reinterpret_cast<const uint32_t*>(P.wo_ptr + (k + e) * 1024 + 128 * j) + (lane & 3);
#pragma unroll
          for (int i = 0; i < 16; i++) {
            const uint32_t w = __ldg(wrow + 4 * i);
            acc[4 * i] += a0 * bf_lo(w); acc[4 * i + 1] += a0 * bf_hi(w);
            acc[4 * i + 2] += a1 * bf_lo(w); acc[4 * i + 3] += a1 * bf_hi(w);
          }
        }
      }
      uint32_t* op = reinterpret_cast<uint32_t*>(P.out_ptr + (128 * r + row) * 2048 + 128 * j) + (lane & 3);
#pragma unroll
      for (int i = 0; i < 32; i++) op[(i & 1) * 8192 + (i >> 1) * 4] = pack_bf16(acc[2 * i], acc[2 * i + 1]);
    }
  } else {
    asm volatile("setmaxnreg.dec.sync.aligned.u32 56;");
    auto fetch_stage = [&](int it) {
      if ((it & 7) == rp && elect()) {
        l2_prefetch2d(&P.wk, 1024 + 128 * j + 64 * rho, 32 * it);
        l2_prefetch3d(&P.w, 0, 32 * it, 32 * rho + 2 * j);
      }
      if ((it & 7) == j && elect()) l2_prefetch2d(&P.x, 32 * it, 128 * r);
    };
    if (warp == 8) {
      cluster_wait();
      cluster_arrive();
      LOOPSTAMP(3, tid == 256, 15);
#pragma unroll 1
      for (int it = 1; it < 4; it++) {
        if (elect()) load_stage(it);
        fetch_stage(it + 3);
      }
      LOOPSTAMP(3, tid == 256, 16);
      __syncwarp();
      cluster_wait();
    } else {
      if (elect()) {
#pragma unroll 1
        for (int g = warp - 9; g < 8; g += 3)
          for (int i = 0; i < 8; i++) mbar_init(bar(8 * g + i), 1u << ((BAR_LOG2 >> (4 * g)) & 7));
        if (warp == 11) for (int i = 0; i < 7; i++) mbar_expect(bar(B_H_FULL + i), i < 2 ? 12288 : i < 5 ? 8192 : i == 5 ? 16 : 16384);
        asm volatile("fence.mbarrier_init.release.cluster;" ::: "memory");
      }
      LOOPSTAMP(3, tid == 288, 14);
      __syncwarp();
      cluster_wait();
      cluster_arrive();
#pragma unroll
      for (int i = 0; i < 3; i++) asm volatile("st.shared.v4.b32 [%0], {%1,%1,%1,%1};" :: "r"(sb + SM_F1 + i * 1536 + (tid - 288) * 16), "r"(0xffffffffu) : "memory");
      fence_async_smem();
      asm volatile("bar.arrive 5, 128;" ::: "memory");
      if ((sb & 0xffffff) != SM_BASE) __trap();
      cluster_wait();
    }
    auto chunk = [&](int ks) { const int c = ks >= 9, t = ks - 2 - 7 * c; return ks < 2 ? 2 * j + ks : 2 * (t + (t >= j)) + c; };
    auto load_wo = [&](uint32_t dst, int c, uint32_t bytes, uint32_t fb) {
      mbar_expect(fb, bytes);
      tma2d_mc(dst + rho * 8192, &P.wo, 128 * j + 64 * rho, c * 64, fb);
    };
    uint8_t* const xch = g_xch[r * 8 + j];
    if (warp == 8) {
      int ck = 0, cw = 0, cph = 1;
      const CUtensorMap* kvmap = rho ? &P.v : &P.k;
#pragma unroll 1
      for (int it = HSTART; it < 32 || (ck < 20 && it < kSpinLimit); ++it) {
        if (it >= 4 && it < 32) {
          mbar_wait(bar(B_QKV_EMPTY + (it & 3)), ((it >> 2) - 1) & 1);
          if (elect()) load_stage(it);
          LOOPSTAMP(3, lane == 0 && it < 12, 15 + it);
        }
        if (it >= 4 && it < 29) fetch_stage(it + 3);
        const int n = it - HSTART;
        if (n >= 0 && n < 8) {
          if (elect()) bulk_load(sb + SM_SIG + n * 8192 + 4096, P.ssm_k + (size_t)(cta * 8 + n) * 2048, 4096, bar(B_H_FULL + (n >= 3) + (n >= 6)));
        } else if (n >= 8 && n < 19) {
          if (n == 8) bar_sync(5, 128);
          if (elect()) bulk_store(xch + (n - 8) * 4096, sb + SM_F1, 4096);
        } else if (it >= PF0 && it < PF0 + 4) {
          if (elect()) l2_prefetch(it < PF0 + 2 ? P.wo_ptr + cta * 8192 + (it - PF0) * 4096 : P.q_ptr + (512 + (it - PF0 - 2) * 1024 + cta * 4) * 1024, 8192);
        }
        if (ck < 16 && it >= PSTART && __all_sync(0xffffffffu, mbar_test(bar(B_PREP_EMPTY + cw), cph))) {
          if (elect()) {
            mbar_expect(bar(B_PREP_FULL + cw), 8704);
            tma3d_mc(sb + SM_STG + cw * 8704 + rho * 4608, kvmap, cl * 16, ck * 8 - 1 + rho, 0, bar(B_PREP_FULL + cw));
          }
          ++ck;
          if (++cw == 3) { cw = 0; cph ^= 1; }
        } else if (ck >= 16 && ck < 20 && __all_sync(0xffffffffu, mbar_test(bar(B_STG_FREE), 0))) {
          if (elect()) tma2d(sb + SM_Q + (ck - 16) * 4096, &P.q, cl * 16, rho * 1024 + (ck - 16) * 128, bar(B_Q_FULL));
          ++ck;
        }
      }
      if (elect()) {
        bulk_commit();
        bulk_wait_read();
        mbar_expect(bar(B_SIG_READY), 10240);
        bulk_load(sb + SM_TW, g_tables, 10240, bar(B_SIG_READY));
        TSTAMP(true, 9);
        flag_add(&g_ready);
        TSTAMP(true, 10);
        prefetch_map(&P.wo); prefetch_map(&P.outa);
        const unsigned epoch = ld_relaxed(&g_epoch[cta]) + 1;
        g_epoch[cta] = epoch;
        flag_wait(&g_ready, kCtas * epoch);
        mbar_arrive(bar(B_ZEROED));
        TSTAMP(true, 11);
      }
      __syncwarp();
      mbar_wait(bar(B_QKV_DONE), 0);
#pragma unroll 1
      for (int ks = 0; ks < 4; ++ks) if (elect()) load_wo(sb + (4 + ks) * SLOT, chunk(ks), ks < 2 ? SLOT : 2 * SLOT, bar(B_OUT_FULL + ks));
    } else {
      const int at = tid - 288, aw = warp - 9, ch0 = cta * 8;
      {
        const uint32_t stg = sb + SM_STG + aw * 8704, pf = bar(B_PREP_FULL + aw), pe = bar(B_PREP_EMPTY + aw);
        const uint4 wv = __ldg(reinterpret_cast<const uint4*>(P.shift_k + (ch0 + 2 * (lane & 3)) * 4));
        const float skip = __bfloat162float(P.ssm_d[ch0 + (lane & 7)]);
        const uint32_t w0 = __byte_perm(wv.x, wv.z, 0x5410), w1 = __byte_perm(wv.x, wv.z, 0x7632);
        const uint32_t w2 = __byte_perm(wv.y, wv.w, 0x5410), w3 = __byte_perm(wv.y, wv.w, 0x7632);
        auto swz32 = [](uint32_t a) { return a ^ ((a >> 3) & 16); };
        const uint32_t kl = (lane >> 3) * 288 + (lane & 7) * 32 + rho * 16;
        const uint32_t ka = stg + swz32(kl + 32), kh = stg + swz32(kl + 12 * 288), va = stg + 4608 + swz32(lane * 32 + rho * 16);
        const uint32_t ua = sb + SM_SIG + (lane & 7) * 8192 + (((lane >> 3) ^ (lane & 7)) << 4);
        if (at == 0) prefetch_map(&P.q);
        uint32_t eh = 0;
#pragma unroll 1
        for (int ck = aw, rd = 0; rd < 9; ck += 3, ++rd) {
          if (rd == 6) {
            bar_sync(4, 96);
            if (at == 64) mbar_arrive(bar(B_STG_FREE));
          }
          const int c = rd < 6 ? ck : ck - 18;
          if (c < 8) {
            uint32_t x[32], dst = sb + SM_SIG + c * 8192;
            if (rd < 6) {
              mbar_wait(bar(B_H_FULL + rd), 0);
#pragma unroll
              for (int i = 0; i < 8; i++) ldsm4(x + 4 * i, dst + 4096 + i * 512 + lane * 16);
              const float d = __shfl_sync(0xffffffffu, skip, c);
              if (lane == 0) x[0] = pack_bf16(bf_lo(x[0]) + d, bf_hi(x[0]));
              dst += 4096 + (lane >> 1) * 128 + ((((lane & 1) * 4) ^ ((lane >> 1) & 7)) << 4);
            } else {
#pragma unroll
              for (int i = 0; i < 8; i++) ldsm4_t(x + 4 * i, dst + i * 512 + ((lane ^ c) << 4));
              dst += (lane >> 4) * 1024 + (lane & 7) * 128 + ((((lane >> 1) & 4) ^ (lane & 7)) << 4);
            }
            const uint32_t e = normalize(x, dst);
            if (rd < 6) {
              eh |= e << (8 * rd);
            } else {
              const int f = min(max((int)(e + (eh & 255)) - 125, 0), 254);
              eh >>= 8;
              if (lane == 0) asm volatile("st.shared.b16 [%0], %1;" :: "r"(sb + SM_SC + rho * 16 + 2 * c), "h"((uint16_t)(f << 7)) : "memory");
            }
          }
          if (ck < 16) {
            mbar_wait(pf, rd & 1);
            uint32_t k[20], v[16];
            ldsm4(k, kh);
#pragma unroll
            for (int m = 0; m < 4; m++) { ldsm4(k + 4 + 4 * m, (ka ^ ((m & 1) << 4)) + m * 1152); ldsm4(v + 4 * m, va + m * 1024); }
            arrive_both(pe + ((k[3] | k[4] | k[8] | k[12] | k[16] | v[0] | v[4] | v[8] | v[12]) & P.zero), lane, ck < 13);
#pragma unroll
            for (int m = 0; m < 4; m++) {
              uint32_t u[4];
#pragma unroll
              for (int n = 0; n < 4; n++) {
                const uint32_t* kk = k + 4 + 4 * m + n;
                u[n] = bmul2(bfma2(kk[0], w0, bfma2(kk[-1], w1, bfma2(kk[-2], w2, bmul2(kk[-3], w3)))), v[4 * m + n]);
              }
              stsm4_t((ua ^ (m << 6)) + ck * 256, u[0], u[1], u[2], u[3]);
            }
          }
        }
        fence_async_smem();
        __syncwarp();
        if (lane == 0) mbar_arrive(bar(B_SIG_READY));
        bar_sync(4, 96);
        if (at == 32) {
          const uint4 s = lds128(sb + SM_SC + rho * 16);
          asm volatile("st.async.weak.shared::cluster.mbarrier::complete_tx::bytes.v4.b32 [%0], {%1,%2,%3,%4}, [%5];"
                       :: "r"(peer_addr(sb + SM_SC + rho * 16, rho ^ 1)), "r"(s.x), "r"(s.y), "r"(s.z), "r"(s.w), "r"(peer_addr(bar(B_RDY0), rho ^ 1)) : "memory");
        }
        TSTAMP(at == 0, 20);
      }
    }
    __syncwarp();
    {
      const int a4 = warp - 8;
      const uint8_t* part = xch + 2 * SLOT + (lane >> 3) * 4 * KV_SLICE + (a4 * 8 + (lane & 7)) * 16;
      const uint8_t* zpart = xch + 2 * SLOT + (lane & 15) * KV_SLICE + 512 + (a4 * 2 + (lane >> 4)) * 4;
      uint8_t* red = xch + 2 * SLOT + 16 * KV_SLICE + (a4 * 8 + (lane & 7)) * 16 + (lane >> 3) * 4;
      uint8_t* zred = xch + 2 * SLOT + 16 * KV_SLICE + 512 + (a4 * 2 + (lane >> 4)) * 4;
      const uint8_t* all = g_xch[a4 * 32 + j] + 2 * SLOT + 16 * KV_SLICE + lane * 16;
      const uint8_t* zall = all + 512 + (lane & 28) - lane * 16;
      keep(part); keep(zpart); keep(red); keep(zred); keep(all); keep(zall);
      uint32_t v[20];
      int n = 0;
      mbar_wait(bar(B_KVP), 0);
      delay(PD1);
      auto load1 = [&](uint32_t* d) {
#pragma unroll
        for (int i = 0; i < 4; i++) ld_relaxed4(d + 4 * i, part + i * KV_SLICE);
        d[16] = ld_relaxed(zpart);
      };
      do load1(v); while (!all_arrived<17>(v) && ++n < kSpinLimit);
      TSTAMP(tid == 288, 21);
      float lo[4], hi[4], z = __uint_as_float(v[16]);
#pragma unroll
      for (int b = 0; b < 4; b++) {
        lo[b] = (bf_lo(v[b]) + bf_lo(v[4 + b])) + (bf_lo(v[8 + b]) + bf_lo(v[12 + b]));
        hi[b] = (bf_hi(v[b]) + bf_hi(v[4 + b])) + (bf_hi(v[8 + b]) + bf_hi(v[12 + b]));
      }
      const bool u16 = lane & 16, u8 = lane & 8;
#pragma unroll
      for (int b = 0; b < 2; b++) {
        lo[b] = (u16 ? lo[b + 2] : lo[b]) + __shfl_xor_sync(0xffffffffu, u16 ? lo[b] : lo[b + 2], 16);
        hi[b] = (u16 ? hi[b + 2] : hi[b]) + __shfl_xor_sync(0xffffffffu, u16 ? hi[b] : hi[b + 2], 16);
      }
      const float l = (u8 ? lo[1] : lo[0]) + __shfl_xor_sync(0xffffffffu, u8 ? lo[0] : lo[1], 8);
      const float h = (u8 ? hi[1] : hi[0]) + __shfl_xor_sync(0xffffffffu, u8 ? hi[0] : hi[1], 8);
      st_relaxed(red, pack_bf16(l, h));
#pragma unroll
      for (int o = 8; o; o >>= 1) z += __shfl_xor_sync(0xffffffffu, z, o);
      if ((lane & 15) == 0) st_relaxed(zred, pack_bf16(z, z));
      TSTAMP(tid == 288, 22);
      n = 0;
      delay(PD2);
      auto load2 = [&](uint32_t* d) {
#pragma unroll
        for (int i = 0; i < 4; i++) {
          ld_relaxed4(d + 4 * i, all + i * 8 * XCH_BYTES);
          d[16 + i] = ld_relaxed(zall + i * 8 * XCH_BYTES);
        }
      };
      do load2(v); while (!all_arrived<20>(v) && ++n < kSpinLimit);
#pragma unroll
      for (int i = 0; i < 4; i++) {
        const uint32_t dst = sb + SM_KV + (a4 * 4 + i) * 640;
        stsm4(dst + lane * 16, v[4 * i], v[4 * i + 1], v[4 * i + 2], v[4 * i + 3]);
        asm volatile("st.shared.b32 [%0], %1;" :: "r"(dst + 512 + lane * 4), "r"(v[16 + i]) : "memory");
      }
      fence_async_smem();
      __syncwarp();
      if (lane == 0) mbar_arrive(bar(B_KV_READY + (a4 >> 1)));
      TSTAMP(tid == 288, 23);
    }
    if (warp != 10) cluster_arrive();
    if (warp == 8) {
      int s = 4;
      uint32_t ph = 1;
#pragma unroll 1
      for (int ks = 4; ks < 16; ++ks) {
        uint32_t fb = bar(B_OUT_FULL + s), dst = sb + ((B_SLOTS >> (4 * s)) & 15) * SLOT;
        int c = chunk(ks);
        keep(fb); keep(dst); keep(c);
        mbar_wait(bar(ks == 4 ? B_RDY1 : B_OUT_EMPTY + s), ks == 4 ? 0 : ph);
        if (elect()) load_wo(dst, c, 2 * SLOT, fb);
        if (++s == 5) { s = 0; ph ^= 1; }
      }
    } else {
      auto wait_chunks = [&](unsigned mask) {
        unsigned ready;
        int n = 0;
        do {
          ready = __ballot_sync(0xffffffffu, ld_relaxed(g_xch[r * 8 + ((lane >> 1) & 7)] + XCH_FLAG) + 1 > (lane & 1));
        } while ((~ready & mask) && ++n < kSpinLimit);
        return ready;
      };
      if (warp == 9) {
        if (elect()) {
#pragma unroll 1
          for (int c = 0; c < 2; c++) {
            mbar_wait(bar(B_O_WRITTEN + c), 0);
            TSTAMP(c == 0, 19);
            fence_async_smem();
            bulk_store(xch + c * SLOT, sb + c * SLOT, SLOT);
            bulk_commit();
            bulk_wait_read();
            mbar_arrive(bar(B_OT_FREE + c));
            delay(FDELAY);
            st_relaxed(xch + XCH_FLAG, c);
            if (!c) delay(C1DELAY);
            TSTAMP(c == 1, 25);
          }
        }
        __syncwarp();
        wait_chunks(0xaaaa);
        if (lane == 0) mbar_arrive(bar(B_FLAGS1));
      } else if (warp == 10) {
        mbar_wait(bar(B_Q_FULL), 0);
        mbar_wait(bar(B_RDY0), 0);
        mbar_wait(bar(B_QKV_DONE), 0);
#pragma unroll 1
        for (int n = 0; n < 4; n++) {
          const int w = n & 1;
          mbar_wait(bar(B_SEG + n), 0);
          fence_async_smem();
          if (elect()) bulk_to_peer(sb + (n < 2 ? SM_Y0 : SM_SIG) + w * 8192 + 4096, sb + SM_YT + w * 4096, 4096, bar(B_YIN + (n >> 1)), rho ^ 1);
          if (w) {
            mbar_wait(bar(B_YIN + (n >> 1)), 0);
            if (lane == 0) asm volatile("mbarrier.arrive.shared::cluster.b64 _, [%0];" :: "r"(n < 2 ? peer_addr(bar(B_RDY1), rho ^ 1) : bar(B_Y_READY)) : "memory");
          }
        }
        __syncwarp();
        cluster_arrive();
        TSTAMP(lane == 0, 26);
      } else {
        mbar_wait(bar(B_OUT_FULL), 0);
        mbar_wait(bar(B_OUT_FULL + 1), 0);
        mbar_wait(bar(B_O_WRITTEN), 0);
        delay(PD3);
        unsigned ready = 0;
        int s = 2;
        uint32_t ph = 1;
#pragma unroll 1
        for (int ks = 2; ks < 16; ++ks) {
          const int c = chunk(ks);
          uint32_t fb = bar(B_OUT_FULL + s), dst = sb + ((A_SLOTS >> (4 * s)) & 15) * SLOT;
          uint8_t* src = g_xch[r * 8 + (c >> 1)] + (c & 1) * SLOT;
          keep(fb); keep(dst); keep(src);
          if (ks < 5 || ks == 9) {
            const unsigned need = ks < 4 ? 1u << c : 0x5555u;
            if (ks == 9) mbar_wait(bar(B_FLAGS1), 0);
            else if (~ready & need) ready = wait_chunks(need);
          }
          constexpr uint64_t kFirst = (B_O_WRITTEN + 1) | B_OT_FREE << 8 | B_SLOT_FREE << 16 | (B_OT_FREE + 1) << 24 | (uint64_t)B_CONV_DONE << 32;
          mbar_wait(bar(ks < 7 ? (int)(kFirst >> (8 * ks - 16)) & 255 : B_OUT_EMPTY + s), ks < 7 ? ks == 4 : ph);
          if (ks == 4 || ks == 6) fence_async_smem();
          if (elect()) bulk_load(dst, src, SLOT, fb);
          TSTAMP(ks == 2 && lane == 0, 18); LOOPSTAMP(2, lane == 0, 11 + ks);
          if (++s == 5) { s = 0; ph ^= 1; }
        }
      }
    }
    if (warp == 9 || warp == 10) {
      const int yc = (lane & 1) + ((lane >> 2) & 2) + (lane & 2) * 2, ysrc = (lane >> 2) & 1;
      const uint32_t ya = sb + (yc & 4 ? SM_SIG : SM_Y0) + (yc & 1) * 8192 + (yc & 2) * 1024 + (ysrc ^ rho) * 4096 +
                          (lane >> 4) * 128 + ((yc ^ (2 * ysrc)) << 4);
      uint32_t s0, s1;
      mbar_wait(bar(B_Y_READY), 0);
      asm volatile("ld.shared.v2.b32 {%0,%1}, [%2];" : "=r"(s0), "=r"(s1) : "r"(sb + SM_SC + (lane & 3) * 8) : "memory");
#pragma unroll 1
      for (int n = warp - 9; n < 8; n += 2) {
        __nv_bfloat16* op = P.out_ptr + (rho * 1024 + n * 128 + (lane >> 2)) * 2048 + 1024 + cl * 16 + (lane & 3) * 4;
        const uint32_t qa = sb + SM_Q + (n & 3) * 4096 + lane * 8;
        asm volatile("cp.async.wait_group 1;" ::: "memory");
        __syncwarp();
#pragma unroll 1
        for (int u0 = 0; u0 < 8; u0 += 2) {
          uint32_t y[2][4], q[2][4];
#pragma unroll
          for (int u = 0; u < 2; u++) {
            ldsm4_t(y[u], (ya ^ ((u0 + u) << 4)) + n * 256);
#pragma unroll
            for (int m = 0; m < 2; m++)
              asm volatile("ld.shared.v2.b32 {%0,%1}, [%2];" : "=r"(q[u][2 * m]), "=r"(q[u][2 * m + 1]) : "r"(qa + (u0 + u) * 512 + m * 256) : "memory");
          }
#pragma unroll
          for (int u = 0; u < 2; u++)
#pragma unroll
            for (int m = 0; m < 2; m++)
              asm volatile("st.global.v2.b32 [%0], {%1,%2};" :: "l"(op + (u * 16 + m * 8) * 2048),
                           "r"(bmul2(q[u][2 * m], bmul2(y[u][2 * m], s0))), "r"(bmul2(q[u][2 * m + 1], bmul2(y[u][2 * m + 1], s1))) : "memory");
          op += 32 * 2048;
        }
        __syncwarp();
        if (n < 4) {
          const __nv_bfloat16* qp = P.q_ptr + (rho * 1024 + n * 128 + 512 + (lane >> 1)) * 1024 + cl * 16 + (lane & 1) * 8;
#pragma unroll
          for (int i = 0; i < 8; i++)
            asm volatile("cp.async.cg.shared.global [%0], [%1], 16;" :: "r"(qa + lane * 8 + i * 512), "l"(qp + i * 16384) : "memory");
        }
        asm volatile("cp.async.commit_group;" ::: "memory");
      }
      TSTAMP(tid == 320, 24);
    }
    __syncwarp();
    cluster_wait();
  }
}

typedef CUresult (*EncodeFn)(CUtensorMap*, CUtensorMapDataType, cuuint32_t, void*, const cuuint64_t*, const cuuint64_t*,
                             const cuuint32_t*, const cuuint32_t*, CUtensorMapInterleave, CUtensorMapSwizzle,
                             CUtensorMapL2promotion, CUtensorMapFloatOOBfill);

void encode(EncodeFn fn, CUtensorMap* m, const void* p, int rank, const cuuint64_t* dims, const cuuint64_t* strides,
            const cuuint32_t* box, CUtensorMapSwizzle sw) {
  const cuuint32_t es[3] = {1, 1, 1};
  fn(m, CU_TENSOR_MAP_DATA_TYPE_BFLOAT16, rank, const_cast<void*>(p), dims, strides, box, es, CU_TENSOR_MAP_INTERLEAVE_NONE, sw,
     CU_TENSOR_MAP_L2_PROMOTION_NONE, CU_TENSOR_MAP_FLOAT_OOB_FILL_NONE);
}
void encode2d(EncodeFn fn, CUtensorMap* m, const void* p, uint64_t cols, uint64_t rows, uint32_t bc, uint32_t br, CUtensorMapSwizzle sw) {
  const cuuint64_t dims[2] = {cols, rows}, strides[1] = {cols * 2};
  const cuuint32_t box[2] = {bc, br};
  encode(fn, m, p, 2, dims, strides, box, sw);
}
void encode3d(EncodeFn fn, CUtensorMap* m, const void* p, uint32_t nblk) {
  const cuuint64_t dims[3] = {1024, 128, 16}, strides[2] = {2048 * 16, 2048};
  const cuuint32_t box[3] = {16, nblk, 16};
  encode(fn, m, p, 3, dims, strides, box, CU_TENSOR_MAP_SWIZZLE_32B);
}

}

extern "C" void kernel_launch(void* const* d_in, const int* in_sizes, int n_in, void* d_out, int out_size) {
  static EncodeFn fn = nullptr;
  if (!fn) {
    cudaDriverEntryPointQueryResult qr;
    cudaGetDriverEntryPoint("cuTensorMapEncodeTiled", (void**)&fn, cudaEnableDefault, &qr);
    cudaFuncSetAttribute(fused_kernel, cudaFuncAttributeMaxDynamicSharedMemorySize, SM_TOTAL);
  }
  Params P;
  encode2d(fn, &P.x, d_in[0], 1024, 2048, 32, 128, CU_TENSOR_MAP_SWIZZLE_64B);
  {
    const cuuint64_t dims[3] = {64, 1024, 48}, strides[2] = {6144, 128};
    const cuuint32_t box[3] = {64, 32, 2};
    encode(fn, &P.w, d_in[1], 3, dims, strides, box, CU_TENSOR_MAP_SWIZZLE_128B);
  }
  encode2d(fn, &P.wk, d_in[1], 3072, 1024, 64, 32, CU_TENSOR_MAP_SWIZZLE_128B);
  encode2d(fn, &P.wo, d_in[2], 1024, 1024, 64, 64, CU_TENSOR_MAP_SWIZZLE_128B);
  encode2d(fn, &P.outa, d_out, 2048, 2048, 64, 16, CU_TENSOR_MAP_SWIZZLE_128B);
  encode3d(fn, &P.k, d_in[4], 9);
  encode3d(fn, &P.v, d_in[5], 8);
  encode2d(fn, &P.q, d_in[3], 1024, 2048, 16, 128, CU_TENSOR_MAP_SWIZZLE_NONE);
  P.shift_k = (const __nv_bfloat16*)d_in[6];
  P.ssm_k = (const __nv_bfloat16*)d_in[7];
  P.ssm_d = (const __nv_bfloat16*)d_in[8];
  P.zero = 0;
  P.q_ptr = (const __nv_bfloat16*)d_in[3];
  P.out_ptr = (__nv_bfloat16*)d_out;
  P.wo_ptr = (const __nv_bfloat16*)d_in[2];
  fused_kernel<<<kCtas, kThreads, SM_TOTAL>>>(P);
}
```

```cpp
#include <cuda.h>
#include <cuda_runtime.h>
#include <cuda_bf16.h>
#include <stdint.h>

#define DEVI __device__ __forceinline__

namespace {

DEVI void mma_nt(float* d, uint64_t da, uint64_t db) {
  asm volatile("wgmma.mma_async.sync.aligned.m64n128k16.f32.bf16.bf16 {%0, %1, %2, %3, %4, %5, %6, %7, %8, %9, %10, %11, %12, %13, %14, %15, %16, %17, %18, %19, %20, %21, %22, %23, %24, %25, %26, %27, %28, %29, %30, %31, %32, %33, %34, %35, %36, %37, %38, %39, %40, %41, %42, %43, %44, %45, %46, %47, %48, %49, %50, %51, %52, %53, %54, %55, %56, %57, %58, %59, %60, %61, %62, %63}, %64, %65, 1, 1, 1, 0, 1;\n"
    : "+f"(d[0]), "+f"(d[1]), "+f"(d[2]), "+f"(d[3]), "+f"(d[4]), "+f"(d[5]), "+f"(d[6]), "+f"(d[7]), "+f"(d[8]), "+f"(d[9]), "+f"(d[10]), "+f"(d[11]), "+f"(d[12]), "+f"(d[13]), "+f"(d[14]), "+f"(d[15]), "+f"(d[16]), "+f"(d[17]), "+f"(d[18]), "+f"(d[19]), "+f"(d[20]), "+f"(d[21]), "+f"(d[22]), "+f"(d[23]), "+f"(d[24]), "+f"(d[25]), "+f"(d[26]), "+f"(d[27]), "+f"(d[28]), "+f"(d[29]), "+f"(d[30]), "+f"(d[31]), "+f"(d[32]), "+f"(d[33]), "+f"(d[34]), "+f"(d[35]), "+f"(d[36]), "+f"(d[37]), "+f"(d[38]), "+f"(d[39]), "+f"(d[40]), "+f"(d[41]), "+f"(d[42]), "+f"(d[43]), "+f"(d[44]), "+f"(d[45]), "+f"(d[46]), "+f"(d[47]), "+f"(d[48]), "+f"(d[49]), "+f"(d[50]), "+f"(d[51]), "+f"(d[52]), "+f"(d[53]), "+f"(d[54]), "+f"(d[55]), "+f"(d[56]), "+f"(d[57]), "+f"(d[58]), "+f"(d[59]), "+f"(d[60]), "+f"(d[61]), "+f"(d[62]), "+f"(d[63])
    : "l"(da), "l"(db));
}
DEVI void mma_tn(float* d, uint64_t da, uint64_t db) {
  asm volatile("wgmma.mma_async.sync.aligned.m64n128k16.f32.bf16.bf16 {%0, %1, %2, %3, %4, %5, %6, %7, %8, %9, %10, %11, %12, %13, %14, %15, %16, %17, %18, %19, %20, %21, %22, %23, %24, %25, %26, %27, %28, %29, %30, %31, %32, %33, %34, %35, %36, %37, %38, %39, %40, %41, %42, %43, %44, %45, %46, %47, %48, %49, %50, %51, %52, %53, %54, %55, %56, %57, %58, %59, %60, %61, %62, %63}, %64, %65, 1, 1, 1, 1, 0;\n"
    : "+f"(d[0]), "+f"(d[1]), "+f"(d[2]), "+f"(d[3]), "+f"(d[4]), "+f"(d[5]), "+f"(d[6]), "+f"(d[7]), "+f"(d[8]), "+f"(d[9]), "+f"(d[10]), "+f"(d[11]), "+f"(d[12]), "+f"(d[13]), "+f"(d[14]), "+f"(d[15]), "+f"(d[16]), "+f"(d[17]), "+f"(d[18]), "+f"(d[19]), "+f"(d[20]), "+f"(d[21]), "+f"(d[22]), "+f"(d[23]), "+f"(d[24]), "+f"(d[25]), "+f"(d[26]), "+f"(d[27]), "+f"(d[28]), "+f"(d[29]), "+f"(d[30]), "+f"(d[31]), "+f"(d[32]), "+f"(d[33]), "+f"(d[34]), "+f"(d[35]), "+f"(d[36]), "+f"(d[37]), "+f"(d[38]), "+f"(d[39]), "+f"(d[40]), "+f"(d[41]), "+f"(d[42]), "+f"(d[43]), "+f"(d[44]), "+f"(d[45]), "+f"(d[46]), "+f"(d[47]), "+f"(d[48]), "+f"(d[49]), "+f"(d[50]), "+f"(d[51]), "+f"(d[52]), "+f"(d[53]), "+f"(d[54]), "+f"(d[55]), "+f"(d[56]), "+f"(d[57]), "+f"(d[58]), "+f"(d[59]), "+f"(d[60]), "+f"(d[61]), "+f"(d[62]), "+f"(d[63])
    : "l"(da), "l"(db));
}
DEVI void mma_own_init(float* d, uint32_t a0, uint32_t a1, uint32_t a2, uint32_t a3, uint64_t db) {
  asm volatile("wgmma.mma_async.sync.aligned.m64n128k16.f32.bf16.bf16 {%0, %1, %2, %3, %4, %5, %6, %7, %8, %9, %10, %11, %12, %13, %14, %15, %16, %17, %18, %19, %20, %21, %22, %23, %24, %25, %26, %27, %28, %29, %30, %31, %32, %33, %34, %35, %36, %37, %38, %39, %40, %41, %42, %43, %44, %45, %46, %47, %48, %49, %50, %51, %52, %53, %54, %55, %56, %57, %58, %59, %60, %61, %62, %63}, {%64,%65,%66,%67}, %68, 0, 1, 1, 1;\n"
    : "=f"(d[0]), "=f"(d[1]), "=f"(d[2]), "=f"(d[3]), "=f"(d[4]), "=f"(d[5]), "=f"(d[6]), "=f"(d[7]), "=f"(d[8]), "=f"(d[9]), "=f"(d[10]), "=f"(d[11]), "=f"(d[12]), "=f"(d[13]), "=f"(d[14]), "=f"(d[15]), "=f"(d[16]), "=f"(d[17]), "=f"(d[18]), "=f"(d[19]), "=f"(d[20]), "=f"(d[21]), "=f"(d[22]), "=f"(d[23]), "=f"(d[24]), "=f"(d[25]), "=f"(d[26]), "=f"(d[27]), "=f"(d[28]), "=f"(d[29]), "=f"(d[30]), "=f"(d[31]), "=f"(d[32]), "=f"(d[33]), "=f"(d[34]), "=f"(d[35]), "=f"(d[36]), "=f"(d[37]), "=f"(d[38]), "=f"(d[39]), "=f"(d[40]), "=f"(d[41]), "=f"(d[42]), "=f"(d[43]), "=f"(d[44]), "=f"(d[45]), "=f"(d[46]), "=f"(d[47]), "=f"(d[48]), "=f"(d[49]), "=f"(d[50]), "=f"(d[51]), "=f"(d[52]), "=f"(d[53]), "=f"(d[54]), "=f"(d[55]), "=f"(d[56]), "=f"(d[57]), "=f"(d[58]), "=f"(d[59]), "=f"(d[60]), "=f"(d[61]), "=f"(d[62]), "=f"(d[63])
    : "r"(a0), "r"(a1), "r"(a2), "r"(a3), "l"(db));
}
DEVI void mma_own_acc(float* d, uint32_t a0, uint32_t a1, uint32_t a2, uint32_t a3, uint64_t db) {
  asm volatile("wgmma.mma_async.sync.aligned.m64n128k16.f32.bf16.bf16 {%0, %1, %2, %3, %4, %5, %6, %7, %8, %9, %10, %11, %12, %13, %14, %15, %16, %17, %18, %19, %20, %21, %22, %23, %24, %25, %26, %27, %28, %29, %30, %31, %32, %33, %34, %35, %36, %37, %38, %39, %40, %41, %42, %43, %44, %45, %46, %47, %48, %49, %50, %51, %52, %53, %54, %55, %56, %57, %58, %59, %60, %61, %62, %63}, {%64,%65,%66,%67}, %68, 1, 1, 1, 1;\n"
    : "+f"(d[0]), "+f"(d[1]), "+f"(d[2]), "+f"(d[3]), "+f"(d[4]), "+f"(d[5]), "+f"(d[6]), "+f"(d[7]), "+f"(d[8]), "+f"(d[9]), "+f"(d[10]), "+f"(d[11]), "+f"(d[12]), "+f"(d[13]), "+f"(d[14]), "+f"(d[15]), "+f"(d[16]), "+f"(d[17]), "+f"(d[18]), "+f"(d[19]), "+f"(d[20]), "+f"(d[21]), "+f"(d[22]), "+f"(d[23]), "+f"(d[24]), "+f"(d[25]), "+f"(d[26]), "+f"(d[27]), "+f"(d[28]), "+f"(d[29]), "+f"(d[30]), "+f"(d[31]), "+f"(d[32]), "+f"(d[33]), "+f"(d[34]), "+f"(d[35]), "+f"(d[36]), "+f"(d[37]), "+f"(d[38]), "+f"(d[39]), "+f"(d[40]), "+f"(d[41]), "+f"(d[42]), "+f"(d[43]), "+f"(d[44]), "+f"(d[45]), "+f"(d[46]), "+f"(d[47]), "+f"(d[48]), "+f"(d[49]), "+f"(d[50]), "+f"(d[51]), "+f"(d[52]), "+f"(d[53]), "+f"(d[54]), "+f"(d[55]), "+f"(d[56]), "+f"(d[57]), "+f"(d[58]), "+f"(d[59]), "+f"(d[60]), "+f"(d[61]), "+f"(d[62]), "+f"(d[63])
    : "r"(a0), "r"(a1), "r"(a2), "r"(a3), "l"(db));
}
DEVI void mma_nt256(float* d, uint64_t da, uint64_t db) {
  asm volatile("wgmma.mma_async.sync.aligned.m64n256k16.f32.bf16.bf16 {%0, %1, %2, %3, %4, %5, %6, %7, %8, %9, %10, %11, %12, %13, %14, %15, %16, %17, %18, %19, %20, %21, %22, %23, %24, %25, %26, %27, %28, %29, %30, %31, %32, %33, %34, %35, %36, %37, %38, %39, %40, %41, %42, %43, %44, %45, %46, %47, %48, %49, %50, %51, %52, %53, %54, %55, %56, %57, %58, %59, %60, %61, %62, %63, %64, %65, %66, %67, %68, %69, %70, %71, %72, %73, %74, %75, %76, %77, %78, %79, %80, %81, %82, %83, %84, %85, %86, %87, %88, %89, %90, %91, %92, %93, %94, %95, %96, %97, %98, %99, %100, %101, %102, %103, %104, %105, %106, %107, %108, %109, %110, %111, %112, %113, %114, %115, %116, %117, %118, %119, %120, %121, %122, %123, %124, %125, %126, %127}, %128, %129, 1, 1, 1, 0, 1;\n"
    : "+f"(d[0]), "+f"(d[1]), "+f"(d[2]), "+f"(d[3]), "+f"(d[4]), "+f"(d[5]), "+f"(d[6]), "+f"(d[7]), "+f"(d[8]), "+f"(d[9]), "+f"(d[10]), "+f"(d[11]), "+f"(d[12]), "+f"(d[13]), "+f"(d[14]), "+f"(d[15]), "+f"(d[16]), "+f"(d[17]), "+f"(d[18]), "+f"(d[19]), "+f"(d[20]), "+f"(d[21]), "+f"(d[22]), "+f"(d[23]), "+f"(d[24]), "+f"(d[25]), "+f"(d[26]), "+f"(d[27]), "+f"(d[28]), "+f"(d[29]), "+f"(d[30]), "+f"(d[31]), "+f"(d[32]), "+f"(d[33]), "+f"(d[34]), "+f"(d[35]), "+f"(d[36]), "+f"(d[37]), "+f"(d[38]), "+f"(d[39]), "+f"(d[40]), "+f"(d[41]), "+f"(d[42]), "+f"(d[43]), "+f"(d[44]), "+f"(d[45]), "+f"(d[46]), "+f"(d[47]), "+f"(d[48]), "+f"(d[49]), "+f"(d[50]), "+f"(d[51]), "+f"(d[52]), "+f"(d[53]), "+f"(d[54]), "+f"(d[55]), "+f"(d[56]), "+f"(d[57]), "+f"(d[58]), "+f"(d[59]), "+f"(d[60]), "+f"(d[61]), "+f"(d[62]), "+f"(d[63]), "+f"(d[64]), "+f"(d[65]), "+f"(d[66]), "+f"(d[67]), "+f"(d[68]), "+f"(d[69]), "+f"(d[70]), "+f"(d[71]), "+f"(d[72]), "+f"(d[73]), "+f"(d[74]), "+f"(d[75]), "+f"(d[76]), "+f"(d[77]), "+f"(d[78]), "+f"(d[79]), "+f"(d[80]), "+f"(d[81]), "+f"(d[82]), "+f"(d[83]), "+f"(d[84]), "+f"(d[85]), "+f"(d[86]), "+f"(d[87]), "+f"(d[88]), "+f"(d[89]), "+f"(d[90]), "+f"(d[91]), "+f"(d[92]), "+f"(d[93]), "+f"(d[94]), "+f"(d[95]), "+f"(d[96]), "+f"(d[97]), "+f"(d[98]), "+f"(d[99]), "+f"(d[100]), "+f"(d[101]), "+f"(d[102]), "+f"(d[103]), "+f"(d[104]), "+f"(d[105]), "+f"(d[106]), "+f"(d[107]), "+f"(d[108]), "+f"(d[109]), "+f"(d[110]), "+f"(d[111]), "+f"(d[112]), "+f"(d[113]), "+f"(d[114]), "+f"(d[115]), "+f"(d[116]), "+f"(d[117]), "+f"(d[118]), "+f"(d[119]), "+f"(d[120]), "+f"(d[121]), "+f"(d[122]), "+f"(d[123]), "+f"(d[124]), "+f"(d[125]), "+f"(d[126]), "+f"(d[127])
    : "l"(da), "l"(db));
}
DEVI void mma_kv_init(float* d, uint32_t a0, uint32_t a1, uint32_t a2, uint32_t a3, uint64_t db) {
  asm volatile("wgmma.mma_async.sync.aligned.m64n72k16.f32.bf16.bf16 {%0, %1, %2, %3, %4, %5, %6, %7, %8, %9, %10, %11, %12, %13, %14, %15, %16, %17, %18, %19, %20, %21, %22, %23, %24, %25, %26, %27, %28, %29, %30, %31, %32, %33, %34, %35}, {%36,%37,%38,%39}, %40, 0, 1, 1, 1;\n"
    : "=f"(d[0]), "=f"(d[1]), "=f"(d[2]), "=f"(d[3]), "=f"(d[4]), "=f"(d[5]), "=f"(d[6]), "=f"(d[7]), "=f"(d[8]), "=f"(d[9]), "=f"(d[10]), "=f"(d[11]), "=f"(d[12]), "=f"(d[13]), "=f"(d[14]), "=f"(d[15]), "=f"(d[16]), "=f"(d[17]), "=f"(d[18]), "=f"(d[19]), "=f"(d[20]), "=f"(d[21]), "=f"(d[22]), "=f"(d[23]), "=f"(d[24]), "=f"(d[25]), "=f"(d[26]), "=f"(d[27]), "=f"(d[28]), "=f"(d[29]), "=f"(d[30]), "=f"(d[31]), "=f"(d[32]), "=f"(d[33]), "=f"(d[34]), "=f"(d[35])
    : "r"(a0), "r"(a1), "r"(a2), "r"(a3), "l"(db));
}
DEVI void mma_kv_acc(float* d, uint32_t a0, uint32_t a1, uint32_t a2, uint32_t a3, uint64_t db) {
  asm volatile("wgmma.mma_async.sync.aligned.m64n72k16.f32.bf16.bf16 {%0, %1, %2, %3, %4, %5, %6, %7, %8, %9, %10, %11, %12, %13, %14, %15, %16, %17, %18, %19, %20, %21, %22, %23, %24, %25, %26, %27, %28, %29, %30, %31, %32, %33, %34, %35}, {%36,%37,%38,%39}, %40, 1, 1, 1, 1;\n"
    : "+f"(d[0]), "+f"(d[1]), "+f"(d[2]), "+f"(d[3]), "+f"(d[4]), "+f"(d[5]), "+f"(d[6]), "+f"(d[7]), "+f"(d[8]), "+f"(d[9]), "+f"(d[10]), "+f"(d[11]), "+f"(d[12]), "+f"(d[13]), "+f"(d[14]), "+f"(d[15]), "+f"(d[16]), "+f"(d[17]), "+f"(d[18]), "+f"(d[19]), "+f"(d[20]), "+f"(d[21]), "+f"(d[22]), "+f"(d[23]), "+f"(d[24]), "+f"(d[25]), "+f"(d[26]), "+f"(d[27]), "+f"(d[28]), "+f"(d[29]), "+f"(d[30]), "+f"(d[31]), "+f"(d[32]), "+f"(d[33]), "+f"(d[34]), "+f"(d[35])
    : "r"(a0), "r"(a1), "r"(a2), "r"(a3), "l"(db));
}
DEVI void mma_o_init(float* d, uint32_t a0, uint32_t a1, uint32_t a2, uint32_t a3, uint64_t db) {
  asm volatile("wgmma.mma_async.sync.aligned.m64n40k16.f32.bf16.bf16 {%0, %1, %2, %3, %4, %5, %6, %7, %8, %9, %10, %11, %12, %13, %14, %15, %16, %17, %18, %19}, {%20,%21,%22,%23}, %24, 0, 1, 1, 1;\n"
    : "=f"(d[0]), "=f"(d[1]), "=f"(d[2]), "=f"(d[3]), "=f"(d[4]), "=f"(d[5]), "=f"(d[6]), "=f"(d[7]), "=f"(d[8]), "=f"(d[9]), "=f"(d[10]), "=f"(d[11]), "=f"(d[12]), "=f"(d[13]), "=f"(d[14]), "=f"(d[15]), "=f"(d[16]), "=f"(d[17]), "=f"(d[18]), "=f"(d[19])
    : "r"(a0), "r"(a1), "r"(a2), "r"(a3), "l"(db));
}
DEVI void mma_o_acc(float* d, uint32_t a0, uint32_t a1, uint32_t a2, uint32_t a3, uint64_t db) {
  asm volatile("wgmma.mma_async.sync.aligned.m64n40k16.f32.bf16.bf16 {%0, %1, %2, %3, %4, %5, %6, %7, %8, %9, %10, %11, %12, %13, %14, %15, %16, %17, %18, %19}, {%20,%21,%22,%23}, %24, 1, 1, 1, 1;\n"
    : "+f"(d[0]), "+f"(d[1]), "+f"(d[2]), "+f"(d[3]), "+f"(d[4]), "+f"(d[5]), "+f"(d[6]), "+f"(d[7]), "+f"(d[8]), "+f"(d[9]), "+f"(d[10]), "+f"(d[11]), "+f"(d[12]), "+f"(d[13]), "+f"(d[14]), "+f"(d[15]), "+f"(d[16]), "+f"(d[17]), "+f"(d[18]), "+f"(d[19])
    : "r"(a0), "r"(a1), "r"(a2), "r"(a3), "l"(db));
}
DEVI void fft1_init(uint32_t* d, uint32_t a0, uint32_t a1, uint32_t a2, uint32_t a3, uint64_t db) {
  asm volatile("wgmma.mma_async.sync.aligned.m64n128k16.f16.f16.f16 {%0, %1, %2, %3, %4, %5, %6, %7, %8, %9, %10, %11, %12, %13, %14, %15, %16, %17, %18, %19, %20, %21, %22, %23, %24, %25, %26, %27, %28, %29, %30, %31}, {%32,%33,%34,%35}, %36, 0, 1, 1, 1;\n"
    : "=r"(d[0]), "=r"(d[1]), "=r"(d[2]), "=r"(d[3]), "=r"(d[4]), "=r"(d[5]), "=r"(d[6]), "=r"(d[7]), "=r"(d[8]), "=r"(d[9]), "=r"(d[10]), "=r"(d[11]), "=r"(d[12]), "=r"(d[13]), "=r"(d[14]), "=r"(d[15]), "=r"(d[16]), "=r"(d[17]), "=r"(d[18]), "=r"(d[19]), "=r"(d[20]), "=r"(d[21]), "=r"(d[22]), "=r"(d[23]), "=r"(d[24]), "=r"(d[25]), "=r"(d[26]), "=r"(d[27]), "=r"(d[28]), "=r"(d[29]), "=r"(d[30]), "=r"(d[31])
    : "r"(a0), "r"(a1), "r"(a2), "r"(a3), "l"(db));
}
DEVI void fft1_acc(uint32_t* d, uint32_t a0, uint32_t a1, uint32_t a2, uint32_t a3, uint64_t db) {
  asm volatile("wgmma.mma_async.sync.aligned.m64n128k16.f16.f16.f16 {%0, %1, %2, %3, %4, %5, %6, %7, %8, %9, %10, %11, %12, %13, %14, %15, %16, %17, %18, %19, %20, %21, %22, %23, %24, %25, %26, %27, %28, %29, %30, %31}, {%32,%33,%34,%35}, %36, 1, 1, 1, 1;\n"
    : "+r"(d[0]), "+r"(d[1]), "+r"(d[2]), "+r"(d[3]), "+r"(d[4]), "+r"(d[5]), "+r"(d[6]), "+r"(d[7]), "+r"(d[8]), "+r"(d[9]), "+r"(d[10]), "+r"(d[11]), "+r"(d[12]), "+r"(d[13]), "+r"(d[14]), "+r"(d[15]), "+r"(d[16]), "+r"(d[17]), "+r"(d[18]), "+r"(d[19]), "+r"(d[20]), "+r"(d[21]), "+r"(d[22]), "+r"(d[23]), "+r"(d[24]), "+r"(d[25]), "+r"(d[26]), "+r"(d[27]), "+r"(d[28]), "+r"(d[29]), "+r"(d[30]), "+r"(d[31])
    : "r"(a0), "r"(a1), "r"(a2), "r"(a3), "l"(db));
}
DEVI void fft2_init(uint32_t* d, uint32_t a0, uint32_t a1, uint32_t a2, uint32_t a3, uint64_t db) {
  asm volatile("wgmma.mma_async.sync.aligned.m64n32k16.f16.f16.f16 {%0, %1, %2, %3, %4, %5, %6, %7}, {%8,%9,%10,%11}, %12, 0, 1, 1, 0;\n"
    : "=r"(d[0]), "=r"(d[1]), "=r"(d[2]), "=r"(d[3]), "=r"(d[4]), "=r"(d[5]), "=r"(d[6]), "=r"(d[7])
    : "r"(a0), "r"(a1), "r"(a2), "r"(a3), "l"(db));
}
DEVI void fft2_acc(uint32_t* d, uint32_t a0, uint32_t a1, uint32_t a2, uint32_t a3, uint64_t db) {
  asm volatile("wgmma.mma_async.sync.aligned.m64n32k16.f16.f16.f16 {%0, %1, %2, %3, %4, %5, %6, %7}, {%8,%9,%10,%11}, %12, 1, 1, 1, 0;\n"
    : "+r"(d[0]), "+r"(d[1]), "+r"(d[2]), "+r"(d[3]), "+r"(d[4]), "+r"(d[5]), "+r"(d[6]), "+r"(d[7])
    : "r"(a0), "r"(a1), "r"(a2), "r"(a3), "l"(db));
}
DEVI void fft3_init(float* d, uint32_t a0, uint32_t a1, uint32_t a2, uint32_t a3, uint64_t db) {
  asm volatile("wgmma.mma_async.sync.aligned.m64n32k16.f32.f16.f16 {%0, %1, %2, %3, %4, %5, %6, %7, %8, %9, %10, %11, %12, %13, %14, %15}, {%16,%17,%18,%19}, %20, 0, 1, 1, 0;\n"
    : "=f"(d[0]), "=f"(d[1]), "=f"(d[2]), "=f"(d[3]), "=f"(d[4]), "=f"(d[5]), "=f"(d[6]), "=f"(d[7]), "=f"(d[8]), "=f"(d[9]), "=f"(d[10]), "=f"(d[11]), "=f"(d[12]), "=f"(d[13]), "=f"(d[14]), "=f"(d[15])
    : "r"(a0), "r"(a1), "r"(a2), "r"(a3), "l"(db));
}
DEVI void fft3_acc(float* d, uint32_t a0, uint32_t a1, uint32_t a2, uint32_t a3, uint64_t db) {
  asm volatile("wgmma.mma_async.sync.aligned.m64n32k16.f32.f16.f16 {%0, %1, %2, %3, %4, %5, %6, %7, %8, %9, %10, %11, %12, %13, %14, %15}, {%16,%17,%18,%19}, %20, 1, 1, 1, 0;\n"
    : "+f"(d[0]), "+f"(d[1]), "+f"(d[2]), "+f"(d[3]), "+f"(d[4]), "+f"(d[5]), "+f"(d[6]), "+f"(d[7]), "+f"(d[8]), "+f"(d[9]), "+f"(d[10]), "+f"(d[11]), "+f"(d[12]), "+f"(d[13]), "+f"(d[14]), "+f"(d[15])
    : "r"(a0), "r"(a1), "r"(a2), "r"(a3), "l"(db));
}

__device__ __align__(128) const uint32_t g_tables[2560] = {
0xa11ba1e4,0xa51ba5e4,0x18b61248,0x1cb61648,0x9f12a052,0xa311a452,0x1d7f1bdb,0x217f1fdb,0x9bdb9d7f,0x9fdba17f,0x20521f12,0x24522311,
0x924898b6,0x96489cb6,0x21e4211b,0x25e4251b,0xaa63ab5f,0xae5faf59,0x21e41bdb,0x25e41fdb,0xa86ba967,0xac6aad65,0x26e024e9,0x2ade28e8,
0xa4e9a6e0,0xa8e8aade,0x2967286b,0x2d652c6a,0x9bdba1e4,0x9fdba5e4,0x2b5f2a63,0x2f592e5f,0xadc2aea7,0xb1b6b294,0x254d1f12,0x294d2311,
0xabf6acde,0xafefb0d7,0x2a31286b,0x2e2d2c6a,0xa86baa31,0xac6aae2d,0x2cde2bf6,0x30d72fef,0x9f12a54d,0xa311a94d,0x2ea72dc2,0x329431b6,
0xb02cb0d2,0xb41ab4b7,0x27a9211b,0x2ba7251b,0xadc2af0c,0xb1b6b2f7,0x2c792a63,0x30742e5f,0xaa63ac79,0xae5fb074,0x2f0c2dc2,0x32f731b6,
0xa11ba7a9,0xa51baba7,0x30d2302c,0x34b7341a,0xb17ab257,0xb552b61a,0x290222ad,0x2d0026ad,0xaf8cb09f,0xb371b487,0x2ddc2c2e,0x31cf3029,
0xac2eaddc,0xb029b1cf,0x309f2f8c,0x34873371,0xa2ada902,0xa6adad00,0x3257317a,0x361a3552,0xb2cdb3e3,0xb682b76f,0x2a312420,0x2e2d281f,
0xb0acb1bb,0xb493b58d,0x2f3f2d2a,0x33283122,0xad2aaf3f,0xb122b328,0x31bb30ac,0x358d3493,0xa420aa31,0xa81fae2d,0x33e332cd,0x376f3682,
0xb413b4bc,0xb7a6b85a,0x2b5f24e9,0x2f5928e8,0xb194b2da,0xb56ab68d,0x30522e28,0x343e3219,0xae28b052,0xb219b43e,0x32da3194,0x368d356a,
0xa4e9ab5f,0xa8e8af59,0x34bc3413,0x385a37a6,0xb4c3b58c,0xb85fb8f3,0x2c4725b2,0x304229b1,0xb27eb3fd,0xb63cb785,0x31062f26,0x34e7330f,
0xaf26b106,0xb30fb4e7,0x33fd327e,0x3785363c,0xa5b2ac47,0xa9b1b042,0x358c34c3,0x38f3385f,0xb577b662,0xb8e5b982,0x2cde267b,0x30d72a7a,
0xb36bb493,0xb70ab83a,0x31bb3012,0x358d3402,0xb012b1bb,0xb402b58d,0x3493336b,0x383a370a,0xa67bacde,0xaa7ab0d7,0x36623577,0x398238e5,
0xb630b741,0xb962ba04,0x2d762744,0x316c2b43,0xb42eb52a,0xb7d2b8ad,0x32713092,0x3631347b,0xb092b271,0xb47bb631,0x352a342e,0x38ad37d2,
0xa744ad76,0xab43b16c,0x37413630,0x3a043962,0xb6eeb815,0xb9d6ba7a,0x2e0e2807,0x32012c06,0xb4a7b5c4,0xb84ab91b,0x33293113,0x36d234f3,
0xb113b329,0xb4f3b6d2,0x35c434a7,0x391b384a,0xa807ae0e,0xac06b201,0x381536ee,0x3a7a39d6,0xb7b4b88e,0xba41bae1,0x2ea7286b,0x32942c6a,
0xb523b662,0xb8a8b982,0x33e33194,0x376f356a,0xb194b3e3,0xb56ab76f,0x36623523,0x398238a8,0xa86baea7,0xac6ab294,0x388e37b4,0x3ae13a41,
0xb841b90f,0xbaa2bb3a,0x2f3f28d0,0x33282cce,0xb5a1b705,0xb902b9e3,0x344f3216,0x380535df,0xb216b44f,0xb5dfb805,0x370535a1,0x39e33902,
0xa8d0af3f,0xacceb328,0x390f3841,0x3b3a3aa2,0xb8acb997,0xbaf7bb83,0x2fd82935,0x33ba2d33,0xb621b7ac,0xb958ba3d,0x34ae3298,0x38503654,
0xb298b4ae,0xb654b850,0x37ac3621,0x3a3d3958,0xa935afd8,0xad33b3ba,0x399738ac,0x3b833af7,0xb91cba28,0xbb42bbbc,0x30392999,0x34262d97,
0xb6a4b82d,0xb9aaba90,0x350e331c,0x389936c6,0xb31cb50e,0xb6c6b899,0x382d36a4,0x3a9039aa,0xa999b039,0xad97b426,0x3a28391c,0x3bbc3b42,
0xb992bac3,0xbb81bbe3,0x308529fe,0x346f2dfb,0xb72ab886,0xb9f8badb,0x357033a0,0x38e03737,0xb3a0b570,0xb737b8e0,0x3886372a,0x3adb39f8,
0xa9feb085,0xadfbb46f,0x3ac33992,0x3be33b81,0x39cf3b16,0x3b9c3bf1,0xb0acaa31,0xb493ae2d,0x376f38b4,0x3a1d3afe,0xb5a1b3e3,0xb902b76f,
0x33e335a1,0x376f3902,0xb8b4b76f,0xbafeba1d,0x2a3130ac,0x2e2d3493,0xbb16b9cf,0xbbf1bb9c,0x39563a74,0x3b633bd2,0xb05fa9cc,0xb44badc9,
0x36e73859,0x39d23ab6,0xb53fb35e,0xb8bcb6ff,0x335e353f,0x36ff38bc,0xb859b6e7,0xbab6b9d2,0x29cc305f,0x2dc9344b,0xba74b956,0xbbd2bb63,
0x38e339de,0x3b1e3ba1,0xb012a967,0xb402ad65,0x36623801,0x39823a67,0xb4deb2da,0xb874b68d,0x32da34de,0x368d3874,0xb801b662,0xba67b982,
0x29673012,0x2d653402,0xb9deb8e3,0xbba1bb1e,0x38763952,0x3ace3b60,0xaf8ca902,0xb371ad00,0x35e13758,0x392e3a11,0xb47eb257,0xb82ab61a,
0x3257347e,0x361a382a,0xb758b5e1,0xba11b92e,0x29022f8c,0x2d003371,0xb952b876,0xbb60bace,0x380d38ce,0x3a733b10,0xaef3a89e,0xb2deac9c,
0x356236b3,0x38d639b3,0xb420b1d5,0xb7bdb5a5,0x31d53420,0x35a537bd,0xb6b3b562,0xb9b3b8d6,0x289e2ef3,0x2c9c32de,0xb8ceb80d,0xbb10ba73,
0x37503851,0x3a0d3ab0,0xae5aa839,0xb24bac38,0x34e53613,0x387a394f,0xb386b153,0xb721b52f,0x31533386,0x352f3721,0xb613b4e5,0xb94fb87a,
0x28392e5a,0x2c38324b,0xb851b750,0xbab0ba0d,0x368e37b4,0x399d3a41,0xadc2a7a9,0xb1b6aba7,0x346a3577,0x381a38e5,0xb2cdb0d2,0xb682b4b7,
0x30d232cd,0x34b73682,0xb577b46a,0xb8e5b81a,0x27a92dc2,0x2ba731b6,0xb7b4b68e,0xba41b99d,0x35d236d1,0x392439c5,0xad2aa6e0,0xb122aade,
0x33e334de,0x376f3874,0xb216b052,0xb5dfb43e,0x30523216,0x343e35df,0xb4deb3e3,0xb874b76f,0x26e02d2a,0x2ade3122,0xb6d1b5d2,0xb9c5b924,
0x351c35f6,0x38a3393c,0xac93a617,0xb08daa16,0x32f43448,0x36a437fe,0xb160afa5,0xb53ab389,0x2fa53160,0x3389353a,0xb448b2f4,0xb7feb6a4,
0x26172c93,0x2a16308d,0xb5f6b51c,0xb93cb8a3,0x346a3523,0x381a38a8,0xabf6a54d,0xafefa94d,0x3209336b,0x35d4370a,0xb0acaea7,0xb493b294,
0x2ea730ac,0x32943493,0xb36bb209,0xb70ab5d4,0x254d2bf6,0x294d2fef,0xb523b46a,0xb8a8b81a,0x33783456,0x3715380a,0xaac8a484,0xaec3a884,
0x3120324a,0x34ff360e,0xaff2ada9,0xb3d3b19e,0x2da92ff2,0x319e33d3,0xb24ab120,0xb60eb4ff,0x24842ac8,0x28842ec3,0xb456b378,0xb80ab715,
0x3223331c,0x35eb36c6,0xa999a376,0xad97a776,0x3039312d,0x3426350b,0xae8dacac,0xb27cb0a6,0x2cac2e8d,0x30a6327c,0xb12db039,0xb50bb426,
0x23762999,0x27762d97,0xb31cb223,0xb6c6b5eb,0x30d23194,0x34b7356a,0xa86ba1e4,0xac6aa5e4,0x2ea73012,0x32943402,0xad2aab5f,0xb122af59,
0x2b5f2d2a,0x2f593122,0xb012aea7,0xb402b294,0x21e4286b,0x25e42c6a,0xb194b0d2,0xb56ab4b7,0x2f0c3012,0x32f73402,0xa67ba052,0xaa7aa452,
0x2cde2df5,0x30d731e8,0xab91a967,0xaf8bad65,0x29672b91,0x2d652f8b,0xadf5acde,0xb1e8b0d7,0x2052267b,0x24522a7a,0xb012af0c,0xb402b2f7,
0x2c792d2a,0x30743122,0xa4209d7f,0xa81fa17f,0x2a312b91,0x2e2d2f8b,0xa8d0a6e0,0xacceaade,0x26e028d0,0x2ade2cce,0xab91aa31,0xaf8bae2d,
0x1d7f2420,0x217f281f,0xad2aac79,0xb122b074,0x27a9286b,0x2ba72c6a,0x9f1298b6,0xa3119cb6,0x254d267b,0x294d2a7a,0xa420a1e4,0xa81fa5e4,
0x21e42420,0x25e4281f,0xa67ba54d,0xaa7aa94d,0x18b61f12,0x1cb62311,0xa86ba7a9,0xac6aaba7,0x3f803f80,0x3f803f80,0x3f803f80,0x3f803f80,
0x3f803f80,0x3f803f80,0x3f803f80,0x3f803f80,0x3f803f80,0x3f803f80,0x3f803f80,0x3f803f80,0x3f803f80,0x3f803f80,0x3f803f80,0x3f803f80,
0x3f803f80,0x3f803f80,0x3f803f80,0x3f803f80,0x3f803f80,0x3f803f80,0x3f803f80,0x3f803f80,0x3f803f80,0x3f803f80,0x3f803f80,0x3f803f80,
0x3f803f80,0x3f803f80,0x3f803f80,0x3f803f80,0x3f803f80,0x3f803f80,0x3f803f80,0x3f803f80,0x3f803f80,0x3f803f80,0x3f803f80,0x3f803f80,
0x3f803f80,0x3f803f80,0x3f803f80,0x3f803f80,0x3f803f80,0x3f803f80,0x3f803f80,0x3f803f80,0x3f803f80,0x3f803f80,0x3f803f80,0x3f803f80,
0x3f803f80,0x3f803f80,0x3f803f80,0x3f803f80,0x3f803f80,0x3f803f80,0x3f803f80,0x3f803f80,0x3f803f80,0x3f803f80,0x3f803f80,0x3f803f80,
0x3f803f80,0x3f803f80,0x3f803f80,0x3f803f80,0x3f803f80,0x3f803f80,0x3f803f80,0x3f803f80,0x3f803f80,0x3f803f80,0x3f803f80,0x3f803f80,
0x3f803f80,0x3f803f80,0x3f803f80,0x3f803f80,0x3f803f80,0x3f803f80,0x3f803f80,0x3f803f80,0x3f803f80,0x3f803f80,0x3f803f80,0x3f803f80,
0x3f803f80,0x3f803f80,0x3f803f80,0x3f803f80,0x3f803f80,0x3f803f80,0x3f803f80,0x3f803f80,0x3f803f80,0x3f803f80,0x3f803f80,0x3f803f80,
0x3f803f80,0x3f803f80,0x3f803f80,0x3f803f80,0x3f803f80,0x3f803f80,0x3f803f80,0x3f803f80,0x3f803f80,0x3f803f80,0x3f803f80,0x3f803f80,
0x3f803f80,0x3f803f80,0x3f803f80,0x3f803f80,0x3f803f80,0x3f803f80,0x3f803f80,0x3f803f80,0x3f803f80,0x3f803f80,0x3f803f80,0x3f803f80,
0x3f803f80,0x3f803f80,0x3f803f80,0x3f803f80,0x3f803f80,0x3f803f80,0x3f803f80,0x3f803f80,0x3f803f80,0x3f803f80,0x3f803f80,0x3f803f80,
0x3f803f80,0x3f803f80,0x3f803f80,0x3f803f80,0x3f803f80,0x3f803f80,0x3f803f80,0x3f803f80,0x3f803f80,0x3f803f80,0x3f803f80,0x3f803f80,
0x3f803f80,0x3f803f80,0x3f803f80,0x3f803f80,0x3f803f80,0x3f803f80,0x3f803f80,0x3f803f80,0x3f803f80,0x3f803f80,0x3f803f80,0x3f803f80,
0x3f803f80,0x3f803f80,0x3f803f80,0x3f803f80,0x3f803f80,0x3f803f80,0x3f803f80,0x3f803f80,0x3f803f80,0x3f803f80,0x3f803f80,0x3f803f80,
0x3f803f80,0x3f803f80,0x3f803f80,0x3f803f80,0x3f803f80,0x3f803f80,0x3f803f80,0x3f803f80,0x3f803f80,0x3f803f80,0x3f803f80,0x3f803f80,
0x3f803f80,0x3f803f80,0x3f803f80,0x3f803f80,0x3f803f80,0x3f803f80,0x3f803f80,0x3f803f80,0x3f803f80,0x3f803f80,0x3f803f80,0x3f803f80,
0x3f803f80,0x3f803f80,0x3f803f80,0x3f803f80,0x3f803f80,0x3f803f80,0x3f803f80,0x3f803f80,0x3f803f80,0x3f803f80,0x3f803f80,0x3f803f80,
0x3f803f80,0x3f803f80,0x3f803f80,0x3f803f80,0x3f803f80,0x3f803f80,0x3f803f80,0x3f803f80,0x3f803f80,0x3f803f80,0x3f803f80,0x3f803f80,
0x3f803f80,0x3f803f80,0x3f803f80,0x3f803f80,0x3f803f80,0x3f803f80,0x3f803f80,0x3f803f80,0x3f803f80,0x3f803f80,0x3f803f80,0x3f803f80,
0x3f803f80,0x3f803f80,0x3f803f80,0x3f803f80,0x3f803f80,0x3f803f80,0x3f803f80,0x3f803f80,0x3f803f80,0x3f803f80,0x3f803f80,0x3f803f80,
0x3f803f80,0x3f803f80,0x3f803f80,0x3f803f80,0x3f803f80,0x3f803f80,0x3f803f80,0x3f803f80,0x3f803f80,0x3f803f80,0x3f803f80,0x3f803f80,
0x3f803f80,0x3f803f80,0x3f803f80,0x3f803f80,0x3f803f80,0x3f803f80,0x3f803f80,0x3f803f80,0x3f803f80,0x3f803f80,0x3f803f80,0x3f803f80,
0x3f803f80,0x3f803f80,0x3f803f80,0x3f803f80,0x3f803f80,0x3f803f80,0x3f803f80,0x3f803f80,0x3f803f80,0x3f803f80,0x3f803f80,0x3f803f80,
0x3f803f80,0x3f803f80,0x3f803f80,0x3f803f80,0x3f803f80,0x3f803f80,0x3f803f80,0x3f803f80,0x3f803f80,0x3f803f80,0x3f803f80,0x3f803f80,
0x3f803f80,0x3f803f80,0x3f803f80,0x3f803f80,0x3f803f80,0x3f803f80,0x3f803f80,0x3f803f80,0x3f803f80,0x3f803f80,0x3f803f80,0x3f803f80,
0x3f803f80,0x3f803f80,0x3f803f80,0x3f803f80,0x3f803f80,0x3f803f80,0x3f803f80,0x3f803f80,0x3f803f80,0x3f803f80,0x3f803f80,0x3f803f80,
0x3f803f80,0x3f803f80,0x3f803f80,0x3f803f80,0x3f803f80,0x3f803f80,0x3f803f80,0x3f803f80,0x3f803f80,0x3f803f80,0x3f803f80,0x3f803f80,
0x3f803f80,0x3f803f80,0x3f803f80,0x3f803f80,0x3f803f80,0x3f803f80,0x3f803f80,0x3f803f80,0x3f803f80,0x3f803f80,0x3f803f80,0x3f803f80,
0x3f803f80,0x3f803f80,0x3f803f80,0x3f803f80,0x3f803f80,0x3f803f80,0x3f803f80,0x3f803f80,0x3f803f80,0x3f803f80,0x3f803f80,0x3f803f80,
0x3f803f80,0x3f803f80,0x3f803f80,0x3f803f80,0x3f803f80,0x3f803f80,0x3f803f80,0x3f803f80,0x3f803f80,0x3f803f80,0x3f803f80,0x3f803f80,
0x3f803f80,0x3f803f80,0x3f803f80,0x3f803f80,0x3f803f80,0x3f803f80,0x3f803f80,0x3f803f80,0x3f803f80,0x3f803f80,0x3f803f80,0x3f803f80,
0x3f803f80,0x3f803f80,0x3f803f80,0x3f803f80,0x3f803f80,0x3f803f80,0x3f803f80,0x3f803f80,0x3f803f80,0x3f803f80,0x3f803f80,0x3f803f80,
0x3f803f80,0x3f803f80,0x3f803f80,0x3f803f80,0x3f803f80,0x3f803f80,0x3f803f80,0x3f803f80,0x3f803f80,0x3f803f80,0x3f803f80,0x3f803f80,
0x3f803f80,0x3f803f80,0x3f803f80,0x3f803f80,0x3f803f80,0x3f803f80,0x3f803f80,0x3f803f80,0x3f803f80,0x3f803f80,0x3f803f80,0x3f803f80,
0x3f803f80,0x3f803f80,0x3f803f80,0x3f803f80,0x3f803f80,0x3f803f80,0x3f803f80,0x3f803f80,0x3f803f80,0x3f803f80,0x3f803f80,0x3f803f80,
0x3f803f80,0x3f803f80,0x3f803f80,0x3f803f80,0x3f803f80,0x3f803f80,0x3f803f80,0x3f803f80,0x3f803f80,0x3f803f80,0x3f803f80,0x3f803f80,
0x3f803f80,0x3f803f80,0x3f803f80,0x3f803f80,0x3f803f80,0x3f803f80,0x3f803f80,0x3f803f80,0x3f803f80,0x3f803f80,0x3f803f80,0x3f803f80,
0x3f803f80,0x3f803f80,0x3f803f80,0x3f803f80,0x3f803f80,0x3f803f80,0x3f803f80,0x3f803f80,0x3f803f80,0x3f803f80,0x3f803f80,0x3f803f80,
0x3f803f80,0x3f803f80,0x3f803f80,0x3f803f80,0x3f803f80,0x3f803f80,0x3f803f80,0x3f803f80,0x3f803f80,0x3f803f80,0x3f803f80,0x3f803f80,
0x3f803f80,0x3f803f80,0x3f803f80,0x3f803f80,0x3f803f80,0x3f803f80,0x3f803f80,0x3f803f80,0x3f803f80,0x3f803f80,0x3f803f80,0x3f803f80,
0x3f803f80,0x3f803f80,0x3f803f80,0x3f803f80,0x3f803f80,0x3f803f80,0x3f803f80,0x3f803f80,0x3f803f80,0x3f803f80,0x3f803f80,0x3f803f80,
0x3f803f80,0x3f803f80,0x3f803f80,0x3f803f80,0x3f803f80,0x3f803f80,0x3f803f80,0x3f803f80,0x3f803f80,0x3f803f80,0x3f803f80,0x3f803f80,
0x3f803f80,0x3f803f80,0x3f803f80,0x3f803f80,0x3bf23bff,0x3ba53bd4,0x3b163b65,0x3a493ab6,0x3b7c3bfb,0x38bc3a60,0x2b43356a,0xb7f3b359,
0x3a933bf1,0x9cb63764,0xba9eb785,0xbb73bbf3,0x39463be2,0xb8cc28e8,0xbb42bbc2,0x3328b70a,0x374e3bcf,0xbbabb648,0xaec3baa9,0x3bfa3994,
0x33403bb7,0xbb85b9fc,0x3a64b0be,0x2c6a3b47,0xa4523b9a,0xb86abbae,0x3b6a3911,0xbbd0ad65,0xb4263b78,0x2adebbe6,0x30f03bfd,0xb5b1bbbc,
0x2f5925e4,0x34b73294,0x376f361a,0x38f3385a,0x35a52c9c,0x3a7338d6,0x3bfd3b87,0x3af13bc9,0x388e2fbd,0x3c003b18,0x387f3b10,0xb5d42f27,
0x3a04316c,0x3a673bfe,0xb6bb33d3,0xbbccbb2f,0x3b1e32f7,0x34933b5c,0xbbf5b86f,0x2d00b9bc,0x3bcb343e,0xb576394f,0xb8d1bbe9,0x3bfb36a4,
0x3c0034ff,0xbaac347b,0x3602ba31,0x32de3bf9,0x3bba35bc,0xbbfdb109,0x3be7aa7a,0xbb7a341a,0x394639cd,0x381538b2,0x358136dd,0x3153341a,
0xbb1eb9c9,0xbbf5bbdd,0xba39bb65,0xb4f3b889,0xb340b93c,0x3966340e,0x3bec3b87,0x37213a7e,0x3c003a4d,0x32193a21,0xbb5eb785,0xb894bbb0,
0xb426389e,0xbb37bb45,0x38b7b3d3,0x397d3bfc,0xbafebac1,0x3b13217f,0xadc93aa9,0xba49bb59,0x3979b7e8,0xb0d73b32,0xb6f4bbe9,0x3af139da,
0x38553b24,0xb9a1ba3d,0x3ab03911,0xbb73b759,0x3a043982,0x3ae13a7a,0x3b833b3a,0x3be33bbc,0x374e3986,0xae9131e8,0xb907b61a,0xbb9cba97,
0xbbcbba0d,0xb9e7bbbd,0x3074b56a,0x3b2a38ad,0x2452b8ee,0x3bda3924,0x363c3b10,0xba90b46f,0x3bba3a89,0xb6e836af,0xba76bbc2,0x39d2ac06,
0xb7c8384a,0xb77abc00,0x3bf8386f,0xb8f33654,0xb9d6baf4,0x3be836ff,0xbb3530be,0x37f3b974,0x3abab737,0xb9af3902,0x3865ba31,0xb5d43b1b,
0x32c62fbd,0x363134cf,0x38653785,0x398b38fd,0xb715b16c,0xbae1b970,0xbbfebbc2,0xba85bb92,0x392e32f7,0x3bf53b6c,0x37a63aa9,0xb7422311,
0xba81b43e,0xb9e7bbfc,0x380fb0be,0x3b963b7f,0x3b7134ff,0x32193b04,0xbc00b911,0x319eb929,0xbbefb5bc,0x36e8b8b2,0x382a3bfd,0xbbffb805,
0x3bf23676,0xbb1331e8,0x376fb9aa,0x2f8b3bde,0xbb7cb72c,0x3be8340e,0xbbfdaa16,0x3bb8b122,0xbbd2bbf1,0xbb60bba1,0xbab0bb10,0xb9c5ba41,
0x3b2c3be2,0x381539df,0xa94d33d3,0xb8a3b52f,0xba19bbcf,0x2e91b5f7,0x3b07386f,0x3b213c00,0x38a83bb7,0xb966aba7,0xbae5bbe9,0x3517b599,
0xb5dfbb9a,0x3bda37b2,0x1fdb3a31,0xbbe0ba1d,0x30293b78,0xbb37ba7a,0x3ad5aa7a,0xa7763aeb,0x2f59bb52,0x377a3bdd,0xbb16b9a6,0x3bf231cf,
0xb5a53b27,0x30d7bbbd,0x2b433bfe,0xb432bbe5,0x3a813a0d,0x3b3f3ae8,0x3bbf3b87,0x3bfb3be5,0xb5dfb8ee,0x3263ad97,0x399d3785,0x3bd03b01,
0xbbefba89,0xb958bb81,0x3389b3d3,0x3b7a394a,0xaf59384a,0xbbf7b9b8,0xb4c3baa9,0x3afb35eb,0x3b7c3af4,0xb825353a,0xb9f8bbe9,0x3a542884,
0x388eb737,0x360e3bf4,0xbbdcb911,0x398bb4db,0xb946bb4f,0x3bc03830,0xbb832a7a,0x38a3b8db,0xbb1e35c8,0x3a35b85f,0xb90739aa,0x3742bab6,
0xb8a8b93c,0xb6c6b80a,0xb402b56a,0xac6ab122,0xbb71ba4d,0xbbd7bbf8,0xb9b3bb10,0xb2deb7bd,0x3029389e,0xb9f4b58d,0xbbc6bbc2,0xb5b1ba00,
0x3bf23ac1,0x2dfb3999,0xbba3b86f,0xb7d2bb6f,0x35a5b7e8,0x3ad83b90,0xb95430be,0xb8e5bbff,0xba93bb24,0x3b682ef5,0xb2013a31,0xb9c5bb9f,
0xba043682,0x33ebbad1,0x35813bfd,0xba85ba5c,0x374e3b76,0xb90cbab3,0x3a3939a6,0xbb21b85a,0xb7c83b52,0x391bba9b,0xba2539aa,0x3afbb889,
0xb9793b27,0x3bc5b80a,0xbb8eaa16,0x38e538ad,0xbaba3af7,0x3b60ad97,0xb27cba2d,0xb98b3bb0,0xbb943ac4,0x3815358d,0x39e3bbea,0xba852c06,
0xbbf93a8c,0xae9139b8,0x3bacb874,0x3742bb59,0xbbe43a50,0xb9663b90,0x340233ba,0x3b96b974,0xbb573a11,0xbbda3bf4,0xb99d3b0d,0xb19e3759,
0xba5839cd,0xbb373ad1,0xbbc63b89,0xbbff3bee,0x3afe3676,0xba29b884,0x391f39a6,0xb7d2ba97,0x39d6372c,0xb3a2bae8,0xb5463bfe,0x3a54ba7e,
0x385537dd,0x3631bbf8,0xbbd63916,0x39c5346f,0x35233845,0x3ae1bb81,0xb96bb0a6,0xb8a33bfc,0x2d333899,0x3bf5b999,0x3487baa5,0xbb213654,
0xb13b38ea,0x39e7b53a,0x3bbfbbc3,0x3517b9da,0xb65f3937,0x32192ef5,0x39b3b790,0x3be0bb1b,0xb8e03982,0xb6e83830,0xb389355e,0xa7763042,
0xbb943682,0x3bebb371,0xbbfe2a7a,0x3bcc3042,0xad33bb76,0xb79b3bd4,0x3b07b9aa,0xbbfa32ad,0x3be4b50b,0xb6c6b8d6,0xb80f3bfe,0x3bfbb835,
0xb65f3bb5,0x3bd7b764,0x9fdbba2d,0xbbd03a41,0xba58330f,0xb9f43bfe,0x382a30a6,0x3b7abb92,0x3a45bbe1,0xadfbb648,0xbb163874,0xbafb3c00,
0x3699afef,0x3ad8b94f,0x3bfdbbc3,0x3a54bb7f,0xbbdf3bfa,0xbb683bae,0xba9e3b0d,0xb98b3a1d,0x35233b4f,0xb08dbbc8,0xa94d3bfd,0x3328bbee,
0xbbf935c8,0x3b0a3294,0xb7a6b9a6,0xad003bd3,0x313bbb98,0xbb3f3a60,0x3ae52a16,0xac6abace,0x3b57b44b,0x3263bb18,0xbc003916,0x32de38fd,
0xb8e03bce,0x3958a8e8,0x3ad5bbea,0xb5b1b52f,0xb8f83185,0xbbf73b5c,0xb76f3aa5,0x37d2a311,0x3b4abbf0,0x3825b9fc,0xab43b3ba,0xb8e53599,
0x31b6acce,0x360eb47b,0x387fb790,0x39c5b929,0x3a9337dd,0xb9a1b924,0x387f3a2d,0xb66bbb01,0xb946b845,0x308d3b45,0x36bbbbea,0xbac73a00,
0x374e3899,0x379bbc00,0xbbf53874,0x393335eb,0xb340b8ea,0xbb3f3b32,0x38d133ba,0x3941bbff,0xa4523937,0x3bd7b902,0x3602bb0d,0xbabd34db,
0x3426b982,0xb9583371,0xbbe73b89,0xb68d3a5c,0xb7c839c9,0x2dfb3294,0x391fb625,0x3bb3bab6,0x3979ba0d,0x3825b8d6,0x3546b6d2,0x3010b359,
0x388ebaf7,0xb9af3a21,0x3a9eb916,0xbb5437bd,0xba043ac4,0x3bebb6af,0xbb42b0a6,0x3840394a,0x3b1eba8c,0xbb0aa17f,0x2ec33aa5,0x3a15bb6f,
0xbbcb3a50,0x36c636ff,0x3a64bbc3,0xba09a884,0x3c00ba11,0x3263ba3d,0xbb6a3790,0xb8503b9f,0xbbba39cd,0xb9f43bc8,0x30f0355e,0x3b4cb8db,
0x3afeb986,0x3bf7bbd4,0x3a25bb63,0x3457b85a,0xb9d6393c,0xbad83a60,0xbb8e3b3d,0xbbef3bc9,0x33403b98,0xa9b1bbed,0xb0743bfe,0x3517bbc9,
0x3c00b44b,0xbaa2b4cf,0x363c3a2d,0x319ebbf3,0x3426bbce,0xbb8b39df,0x3a7630a6,0x2776bb2f,0xbafe3185,0xb4b73b6c,0x3bf8b874,0xaf8bb994,
0xb9793bf0,0x38bc2ba7,0x3b35bbc3,0xb432b6a4,0x3855acce,0x3c00bb04,0x3865bb0d,0xb66bad65,0x3b94bbff,0x38ccba7a,0x294db55e,0xb840341a,
0xad33a5e4,0xb49331e8,0xb7a63625,0xb9333889,0x3bcbb50b,0xbbfe305b,0x3bec2a16,0xbb96b359,0x2452bbb5,0xb87a3ba1,0x3b5eb916,0xbbe02f27,
0xbbba330f,0x35523970,0x38b7bbea,0xbbff370a,0xb7c83be1,0x3ba5b5f7,0x2dc9baa5,0xbbf239bc,0x39d6afef,0x3a73bbfc,0xb6f4b3ba,0xbbb83b47,
0x3ababbfa,0x1cb6b7b2,0xbab03790,0xbb543bf9,0xb52326ad,0xba6738b2,0xbbfe3b89,0xbac73bbc,0xbbf93bff,0xbbab3bdd,0xbb073b63,0xba153a97,
0xb8f83986,0xb77a385f,0xb4c33625,0xaf8b32ad,0xb699393c,0x30d7305b,0x3954b6d2,0x3bb8bace,0xb1b638ee,0x39afb4cf,0x3bdcbba7,0x366bba41,
0x2c38389e,0x3bebb970,0x3581bade,0xbac7352f,0x34e7384a,0x3b0abb6c,0xb907b24b,0xb9333c00,0x383a37e8,0x36c6bbfc,0xbbec38c1,0x39413599,
0x39c03737,0xb263bb04,0xb63c3bf6,0x3abdba1d,0x3aee3682,0xb9f4b8b2,0x38b739f0,0xb68dbaeb,0xba4539c9,0xbb133ab3,0xbba33b63,0xbbf23bd3,
0xbb4a3a0d,0xbbe83bed,0xb9f83b3d,0xb4323835,0xbbdf3a4d,0xb9a13ba1,0x320134ab,0x3b54b8fd,0xbbfc3a89,0xb08d39df,0x3b83b81a,0x3840bb92,
0xbb9e3ac1,0x379b35f7,0x3a39bbd8,0xba15a311,0xbacb3af4,0x3b3faba7,0xb074ba6f,0xba093b7f,0xb9903b24,0x3bd7b7b2,0xbb5eae5f,0x38503929,
0xb7fe3b4f,0x3958ba7a,0xba76395d,0x3b4cb805,0x2c3826ad,0x33ebb109,0x36bbb55e,0x38a3b805,0x3b9ebbff,0x390cba9b,0x2ec3b625,0xb74231cf,
0xb83a2c9c,0xbbfe3ae8,0xb8d13b3d,0x35173122,0xb9903bf1,0x387a2d97,0x3b6abba7,0xb19eb7bd,0x3aeeb16c,0x3552bb81,0xbbe7381a,0x27763a00,
0x3463bbcf,0xbba539b8,0x3a25324b,0x2f8bbb6f,0xbbff343e,0x3a73353a,0xb546ba6f,0xb4323bff,0x32c63b9a,0x9cb6bbf4,0xb27c3bf6,0x366bbb9f,
0xbbfc3bff,0xbbc03be6,0xbb423b89,0xba853aeb,0x34e7a5e4,0x3a35b884,0x3bf5bb63,0x3b21bbde,0x3acbbbfb,0x29b1b80a,0xba6436d2,0xbb963be5,
0xb9c02fbd,0xbaa23bf8,0x360234ab,0x3be0bb01,0xb7fe3be2,0x3b8bb58d,0x30f0bade,0xbbff394a,0x3bb2b2f7,0xb4b7b999,0xb91f3bd8,0x3bf2b5eb,
0x281fbbb7,0xb8bc3b90,0x3b8eb8c1,0xbbb82884,0xbbd234ff,0x3c00aef5,0xbbd6ae5f,0x3b5434db,0xbaba3a4d,0xbb683b18,0xbbd63ba7,0xbc003bf3,
0x3b94ba89,0x3bc0bbfe,0x396bbade,0x3153b70a,0xbbf93ac1,0xb90c3b5c,0x3487324b,0x3b9cb994,0x3be4baf4,0x29b1b94f,0xbbbf38c1,0xb7213b47,
0xbb573b24,0x387a347b,0x39b3bbf6,0xba902d65,0x3a58bb4f,0xbb8b3109,0x338939f0,0x397dbbbc,0xb8f83b76,0x3ba5b884,0xbba39648,0x38f33889,
0x3699bb98,0xb8bc3ae8,0x39f8b9eb,0xbaf138ad,0x3855b8ee,0x360eb764,0x327cb4ab,0x251baf27,0xb523389e,0x33eb28e8,0x39e3b81a,0x3be3bb2f,
0x2d33b84a,0xba353648,0xbbac3bd8,0xb4f339bc,0x313b37e8,0x3bfeb9fc,0x3402ba6f,0xbb2a36a4,0xb65fb737,0xbaa23bae,0x399d2e5f,0x3894bbf9,
0x38e03682,0x3552bbe6,0xbbc6395d,0x39d2341a,0xba45b5c8,0x34b73a9b,0x34c3bc00,0xba493a97,0x3b4a350b,0xba73b80a,0x39543962,0xb7f3ba7e,
0xbbe43bfb,0xbb853bbd,0xbae53b3d,0xba093a7e,0xb65f2fbd,0xbaac3924,0xbc003ba7,0xbabd3bb0,0x3a58bbe2,0xaadeb6af,0xbad5381a,0xbb4c3bfc,
0x3a45b2f7,0x3a29bc00,0xb76fb24b,0xbbb33b59,0xb6993bb7,0x3bc5b6ff,0x2b43ba6f,0xbbef39da,0xbbdf34ff,0x36313902,0x387fbbf6,0xbc003759,
0xac38bb78,0xb8153bc8,0x3b42b95d,0xbbe33042,0x3b9eb676,0xbbf53294,0x3bf51648,0xbb9cb2ad,0xb13b2c9c,0xb576340e,0xb80f36d2,0xb94138ad,
0x3b57bbf1,0x386aba21,0x1fdbb4ab,0xb850346f,0x38e0b16c,0x3bfdbb45,0x382abade,0xb68dac06,0xb8f83bcf,0x391ba17f,0x3b16bbd8,0xb457b654,
0xbb4a343e,0xb3a23b32,0x3bfdb8c1,0xb010b974,0x31b6bb9a,0xbb603a3d,0x3a9e2e5f,0x251bbb1b,0x3bfcb5bc,0xbae1b371,0x36bb39f0,0x3153bbee,
0x34e73b52,0xae91bbd4,0xaec33c00,0x34f3bbd3,0x3bb235c8,0xbbf7b1e8,0x3bf81648,0xbbb331cf,0x3bff350b,0xbad8340e,0x36f4b9eb,0x30103be5,
0x3bd2344b,0xb60e3924,0xb865bbf6,0x3c0037bd,0x3b2c330f,0x33eb3b45,0xbbfeb8c7,0x3153b94a,0x3a193185,0x3a353c00,0xb7a63232,0xbb9cbb6f,
0x38a82fef,0x3bfe3b32,0x380f3adb,0xb7212884,0x35df2cce,0x3aa23902,0x3c003ba9,0x3a903b9f,0x302926ad,0x35523371,0x382a36dd,0x397d38db,
0xb4633b76,0x2dfbbbdd,0x2dc93c00,0xb457bbde,0xa81f3b98,0xb825bbbd,0x3b353962,0xbbefb122,0x32c63bb5,0xbb68ba21,0x3ab0ae2d,0xa51b3b01,
0x37153bce,0xbbc0b6af,0xa94dba6b,0x3be33a00,0x392e3be1,0xb90c217f,0xbb07bbd9,0x34f3b5eb,0x3a813bf0,0xa9b136ff,0xbae5b820,0xbb2abbff,
0x3b713bfa,0x387a3a3d,0x9fdb349f,0xb894b4db,0x3bef3bff,0x3b8b3bc8,0x3ad53b3a,0x39d23a5c,0x3b2cb5bc,0xba673830,0x396bb95d,0xb8403a5c,
0xb92ebb52,0x3bab385f,0xbbac9648,0x3933b85a,0xb8a8372c,0xb576bbed,0x3bbf3962,0xba093359,0x3b713af7,0xb86a34cf,0xb99dbbf6,0x3abd2f27,
0x3029b845,0x3bfd39df,0x33893a6b,0xbb4cb70a,0xbbf2ba8c,0xb91bbb6c,0x34c3b232,0x3bb339bc,0x35a538ea,0xb3a22ba7,0xb9f8b820,0xbbefbb47,
0x3a933a11,0x3b603b04,0x3bdc3ba9,0x3c003bf9,0x37153b78,0xb8ccbad1,0x39e339f0,0xbac7b8db,0x3a19b676,0xb4933ab3,0xb487bc00,0x3a153ab6,
0xba81bb27,0x3b85305b,0xb40239eb,0xb941bbc9,0xb5df37dd,0xbaacbba1,0x39b3ae2d,0x38503bf3,0x3bef3ac4,0x2ade3970,0xbbc6b8c7,0xb68dbb2f,
0xaf59b899,0x3a2935f7,0x3ba33bd9,0x34573994,0xbb7cba50,0xbbc5bbfc,0xb954badb,0xb010b6a4,0x388e3937,0x363137b2,0x3201349f,0xa51b2d65,
0xb1b63bb5,0x9cb6bbf8,0x32013bf6,0xb5d4bbb0,0xac38bbce,0x38cc3b81,0xbb83b8c7,0x3bcc2c06,0x34e73be1,0xbbabb999,0x3a39b232,0x2d003b59,
0xb83abbf0,0x3b85353a,0x30743adb,0xbbfbb974,0x39c03bfa,0xb86a2ef5,0xbb5ebba9,0x32deb759,0xbaeebbff,0xaadeb830,0x3a7636dd,0x3b7a3bee,
0x3bb23bff,0x391b3ab3,0x2dc9361a,0xb7d2b2ad,0xbbffbbfb,0xbbc5bbed,0xbb35bb87,0xba54bace,0xbbdfb44b,0x3c002d97,0xbbdc2e2d,0x3b73b46f,
0x3bfc330f,0xba67358d,0x3581ba6b,0x33283bfc,0xbb9eb185,0x3493b9b8,0x39073bd9,0xbbfab654,0x3acb2fef,0x35763b90,0xbbecb820,0x2c6ab9da,
0xb990acce,0xbaacbbf4,0x363cb49f,0x3bd03b1b,0x37fe26ad,0x3bfd3ad1,0x38b73b3a,0xb5b13042,0xb46325e4,0xba29b85f,0xbbf8bb65,0xbafbbbd3,
0x281fac9c,0x33a2305b,0x36f4356a,0x38e53835,0x383a3b27,0xb966ba60,0x3a643962,0xbb2ab835,0xb99037dd,0x3219bb18,0x36023bf6,0xba90ba41,
0xbaeebac4,0x3b3728e8,0xb0f03a6b,0xb9d2bb92,0x3463b899,0x3b133b5c,0xb91f3232,0xb8f3bc00,0x3bff3a50,0x30d739fc,0xbb8eb820,0xb7f3bb7f,
0x32c63937,0xb9a1b47b,0xbbd6bba9,0xb5d4ba1d,0xbb2cb9cd,0xbbebbbe6,0xb9e3bb3a,0xb328b805,0xb92eb9c9,0xb79bb884,0xb487b61a,0xad00b1cf,
0xbacb372c,0x39e7b8d6,0xb8d139eb,0x3721bace,0xb9c0baf7,0x3bda3764,0xbb6a2e2d,0x3894b8fd,0x37feb845,0x36e83bfe,0xbbe7b8c7,0x397db52f,
0x3bb23a8c,0xb77a3648,0xba25bbd9,0x3a492311,0xa81f38ea,0xbbe8b94f,0xb546badb,0x3af13599,0xbbd2ba11,0xb9afbbae,0x327cb49f,0x3b733929,
0xb715b982,0x308db109,0x396b36dd,0x3bcc3aeb,0x3a193986,0x3b0a3a9b,0x3bac3b65,0x3bfa3bde,0x30003000,0x30003000,0x30003000,0x30003000,
0x2f643000,0x2a1f2da8,0xaa1f0000,0xaf64ada8,0x2da83000,0xada80000,0xada8b000,0x2da88000,0x2a1f3000,0xaf64ada8,0x2f648000,0xaa1f2da8,
0x00003000,0x8000b000,0x00003000,0x8000b000,0xaa1f3000,0x2f64ada8,0xaf640000,0x2a1f2da8,0xada83000,0x2da88000,0x2da8b000,0xada80000,
0xaf643000,0xaa1f2da8,0x2a1f8000,0x2f64ada8,0x30003000,0x30003000,0x30003000,0x30003000,0xaf64b000,0xaa1fada8,0x2a1f8000,0x2f642da8,
0x2da83000,0xada80000,0xada8b000,0x2da88000,0xaa1fb000,0x2f642da8,0xaf640000,0x2a1fada8,0x00003000,0x8000b000,0x00003000,0x8000b000,
0x2a1fb000,0xaf642da8,0x2f648000,0xaa1fada8,0xada83000,0x2da88000,0x2da8b000,0xada80000,0x2f64b000,0x2a1fada8,0xaa1f0000,0xaf642da8,
0x80008000,0x80008000,0x80008000,0x80008000,0xaa1f8000,0xaf64ada8,0xaf64b000,0xaa1fada8,0xada88000,0xada8b000,0x2da88000,0x2da83000,
0xaf648000,0x2a1fada8,0x2a1f3000,0xaf64ada8,0xb0008000,0x30008000,0xb0008000,0x30008000,0xaf648000,0x2a1f2da8,0x2a1fb000,0xaf642da8,
0xada88000,0xada83000,0x2da88000,0x2da8b000,0xaa1f8000,0xaf642da8,0xaf643000,0xaa1f2da8,0x80008000,0x80008000,0x80008000,0x80008000,
0x2a1f8000,0x2f642da8,0x2f643000,0x2a1f2da8,0xada88000,0xada8b000,0x2da88000,0x2da83000,0x2f648000,0xaa1f2da8,0xaa1fb000,0x2f642da8,
0xb0008000,0x30008000,0xb0008000,0x30008000,0x2f648000,0xaa1fada8,0xaa1f3000,0x2f64ada8,0xada88000,0xada83000,0x2da88000,0x2da8b000,
0x2a1f8000,0x2f64ada8,0x2f64b000,0x2a1fada8,0xb0003000,0xb0003000,0xb0003000,0xb0003000,0xaf643000,0xaa1f2da8,0x2a1f0000,0x2f64ada8,
0xada83000,0x2da80000,0x2da8b000,0xada88000,0xaa1f3000,0x2f64ada8,0xaf648000,0x2a1f2da8,0x80003000,0x0000b000,0x80003000,0x0000b000,
0x2a1f3000,0xaf64ada8,0x2f640000,0xaa1f2da8,0x2da83000,0xada88000,0xada8b000,0x2da80000,0x2f643000,0x2a1f2da8,0xaa1f8000,0xaf64ada8,
0xb0003000,0xb0003000,0xb0003000,0xb0003000,0x2f64b000,0x2a1fada8,0xaa1f8000,0xaf642da8,0xada83000,0x2da80000,0x2da8b000,0xada88000,
0x2a1fb000,0xaf642da8,0x2f640000,0xaa1fada8,0x80003000,0x0000b000,0x80003000,0x0000b000,0xaa1fb000,0x2f642da8,0xaf648000,0x2a1fada8,
0x2da83000,0xada88000,0xada8b000,0x2da80000,0xaf64b000,0xaa1fada8,0x2a1f0000,0x2f642da8,0x80008000,0x80008000,0x80008000,0x80008000,
0x2a1f8000,0x2f64ada8,0x2f64b000,0x2a1fada8,0x2da88000,0x2da8b000,0xada88000,0xada83000,0x2f648000,0xaa1fada8,0xaa1f3000,0x2f64ada8,
0x30008000,0xb0008000,0x30008000,0xb0008000,0x2f648000,0xaa1f2da8,0xaa1fb000,0x2f642da8,0x2da88000,0x2da83000,0xada88000,0xada8b000,
0x2a1f8000,0x2f642da8,0x2f643000,0x2a1f2da8,0x80008000,0x80008000,0x80008000,0x80008000,0xaa1f8000,0xaf642da8,0xaf643000,0xaa1f2da8,
0x2da88000,0x2da8b000,0xada88000,0xada83000,0xaf648000,0x2a1f2da8,0x2a1fb000,0xaf642da8,0x30008000,0xb0008000,0x30008000,0xb0008000,
0xaf648000,0x2a1fada8,0x2a1f3000,0xaf64ada8,0x2da88000,0x2da83000,0xada88000,0xada8b000,0xaa1f8000,0xaf64ada8,0xaf64b000,0xaa1fada8,
0x00000000,0x00000000,0x00000000,0x00000000,0x2a1f0000,0x2f642da8,0x2f643000,0x2a1f2da8,0x2da80000,0x2da83000,0xada80000,0xada8b000,
0x2f640000,0xaa1f2da8,0xaa1fb000,0x2f642da8,0x30000000,0xb0000000,0x30000000,0xb0000000,0x2f640000,0xaa1fada8,0xaa1f3000,0x2f64ada8,
0x2da80000,0x2da8b000,0xada80000,0xada83000,0x2a1f0000,0x2f64ada8,0x2f64b000,0x2a1fada8,0x00000000,0x00000000,0x00000000,0x00000000,
0xaa1f0000,0xaf64ada8,0xaf64b000,0xaa1fada8,0x2da80000,0x2da83000,0xada80000,0xada8b000,0xaf640000,0x2a1fada8,0x2a1f3000,0xaf64ada8,
0x30000000,0xb0000000,0x30000000,0xb0000000,0xaf640000,0x2a1f2da8,0x2a1fb000,0xaf642da8,0x2da80000,0x2da8b000,0xada80000,0xada83000,
0xaa1f0000,0xaf642da8,0xaf643000,0xaa1f2da8,0x30003000,0x30003000,0x30003000,0x30003000,0x2f643000,0x2a1f2da8,0xaa1f0000,0xaf64ada8,
0x2da83000,0xada80000,0xada8b000,0x2da88000,0x2a1f3000,0xaf64ada8,0x2f648000,0xaa1f2da8,0x00003000,0x8000b000,0x00003000,0x8000b000,
0xaa1f3000,0x2f64ada8,0xaf640000,0x2a1f2da8,0xada83000,0x2da88000,0x2da8b000,0xada80000,0xaf643000,0xaa1f2da8,0x2a1f8000,0x2f64ada8,
0x30003000,0x30003000,0x30003000,0x30003000,0xaf64b000,0xaa1fada8,0x2a1f8000,0x2f642da8,0x2da83000,0xada80000,0xada8b000,0x2da88000,
0xaa1fb000,0x2f642da8,0xaf640000,0x2a1fada8,0x00003000,0x8000b000,0x00003000,0x8000b000,0x2a1fb000,0xaf642da8,0x2f648000,0xaa1fada8,
0xada83000,0x2da88000,0x2da8b000,0xada80000,0x2f64b000,0x2a1fada8,0xaa1f0000,0xaf642da8,0x00000000,0x00000000,0x00000000,0x00000000,
0xaa1f0000,0xaf642da8,0xaf643000,0xaa1f2da8,0xada80000,0xada83000,0x2da80000,0x2da8b000,0xaf640000,0x2a1f2da8,0x2a1fb000,0xaf642da8,
0xb0000000,0x30000000,0xb0000000,0x30000000,0xaf640000,0x2a1fada8,0x2a1f3000,0xaf64ada8,0xada80000,0xada8b000,0x2da80000,0x2da83000,
0xaa1f0000,0xaf64ada8,0xaf64b000,0xaa1fada8,0x00000000,0x00000000,0x00000000,0x00000000,0x2a1f0000,0x2f64ada8,0x2f64b000,0x2a1fada8,
0xada80000,0xada83000,0x2da80000,0x2da8b000,0x2f640000,0xaa1fada8,0xaa1f3000,0x2f64ada8,0xb0000000,0x30000000,0xb0000000,0x30000000,
0x2f640000,0xaa1f2da8,0xaa1fb000,0x2f642da8,0xada80000,0xada8b000,0x2da80000,0x2da83000,0x2a1f0000,0x2f642da8,0x2f643000,0x2a1f2da8,
0xb0003000,0xb0003000,0xb0003000,0xb0003000,0xaf643000,0xaa1f2da8,0x2a1f0000,0x2f64ada8,0xada83000,0x2da80000,0x2da8b000,0xada88000,
0xaa1f3000,0x2f64ada8,0xaf648000,0x2a1f2da8,0x80003000,0x0000b000,0x80003000,0x0000b000,0x2a1f3000,0xaf64ada8,0x2f640000,0xaa1f2da8,
0x2da83000,0xada88000,0xada8b000,0x2da80000,0x2f643000,0x2a1f2da8,0xaa1f8000,0xaf64ada8,0xb0003000,0xb0003000,0xb0003000,0xb0003000,
0x2f64b000,0x2a1fada8,0xaa1f8000,0xaf642da8,0xada83000,0x2da80000,0x2da8b000,0xada88000,0x2a1fb000,0xaf642da8,0x2f640000,0xaa1fada8,
0x80003000,0x0000b000,0x80003000,0x0000b000,0xaa1fb000,0x2f642da8,0xaf648000,0x2a1fada8,0x2da83000,0xada88000,0xada8b000,0x2da80000,
0xaf64b000,0xaa1fada8,0x2a1f0000,0x2f642da8};

constexpr int kThreads = 384;
constexpr int kCtas = 128;

constexpr uint32_t SM_BASE = 1024;
constexpr uint32_t QKV_STAGE = 32768;
constexpr uint32_t SLOT = 16384;
constexpr uint32_t SM_KV = 2 * SLOT;
constexpr uint32_t SM_SIG = 131072;
constexpr uint32_t SM_STG = 196608;
constexpr uint32_t SM_Q = SM_STG;
constexpr uint32_t SM_Y0 = 3 * SLOT;
constexpr uint32_t SM_YT = SM_STG + 16384;
constexpr uint32_t SM_TW = SM_STG + 24576, SM_ONES = SM_TW + 2048, SM_F1 = SM_ONES + 2048, SM_F2 = SM_F1 + 4096;
constexpr uint32_t SM_BAR = SM_F2 + 2048;
constexpr uint32_t SM_SC = SM_BAR + 640;
constexpr uint32_t SM_TOTAL = 232448;
constexpr uint32_t A_SLOTS = 0xA02B1, B_SLOTS = 0x97654;

enum Bar { B_QKV_EMPTY = 0, B_QKV_DONE = 4,
           B_OUT_EMPTY = 8,
           B_H_FULL = 16, B_YIN = 19, B_RDY0 = 21, B_Q_FULL = 22, B_ZEROED = 23,
           B_OUT_FULL = 24, B_PREP_FULL = 29,
           B_RDY1 = 32, B_STG_FREE = 33, B_OT_FREE = 36, B_Y_READY = 38, B_FLAGS1 = 39,
           B_SEG = 40, B_SIG_READY = 44,
           B_KVP = 48, B_O_WRITTEN = 49, B_SLOT_FREE = 51, B_CONV_DONE = 52,
           B_PREP_EMPTY = 56, B_KV_READY = 59,
           B_QKV_FULL = 64, B_FIRST = 68 };
constexpr uint32_t BAR_LOG2 = 0x13200044;

constexpr int KV_SLICE = 640;
constexpr int XCH_FLAG = 2 * SLOT + 17 * KV_SLICE;
constexpr int XCH_BYTES = 11 * 4096;

struct Params {
  CUtensorMap x, w, wk, wo, outa, k, v, q;
  const __nv_bfloat16* shift_k;
  const __nv_bfloat16* ssm_k;
  const __nv_bfloat16* ssm_d;
  const __nv_bfloat16* q_ptr;
  __nv_bfloat16* out_ptr;
  const __nv_bfloat16* wo_ptr;
  int zero;
};

__device__ __align__(128) uint8_t g_xch[kCtas][XCH_BYTES];
__device__ unsigned g_ready, g_epoch[kCtas];

#define TSTAMP(cond, i) do { } while (0)
#define GSTAMP(cond, i) do { } while (0)
#define LOOPSTAMP(id, cond, i) do { } while (0)

constexpr int kSpinLimit = 1 << 17;

DEVI void mbar_init(uint32_t a, uint32_t c) { asm volatile("mbarrier.init.shared::cta.b64 [%0], %1;" :: "r"(a), "r"(c) : "memory"); }
DEVI void mbar_expect(uint32_t a, uint32_t b) { asm volatile("mbarrier.arrive.expect_tx.shared::cta.b64 _, [%0], %1;" :: "r"(a), "r"(b) : "memory"); }
DEVI void mbar_arrive(uint32_t a) { asm volatile("mbarrier.arrive.shared::cta.b64 _, [%0];" :: "r"(a) : "memory"); }
DEVI void mbar_arrive_if(uint32_t a, bool pred) {
  asm volatile("{\n.reg .pred p;\nsetp.ne.b32 p, %1, 0;\n@p mbarrier.arrive.shared::cta.b64 _, [%0];\n}" :: "r"(a), "r"((int)pred) : "memory");
}
DEVI void mbar_wait(uint32_t a, uint32_t parity) {
  asm volatile("{\n.reg .pred p;\n.reg .u32 n;\nmov.u32 n, 0;\nW_LOOP:\n"
               "mbarrier.try_wait.parity.shared::cta.b64 p, [%0], %1;\nadd.u32 n, n, 1;\n"
               "setp.lt.and.u32 p, n, %2, !p;\n@p bra W_LOOP;\n}"
               :: "r"(a), "r"(parity), "n"(kSpinLimit) : "memory");
}
DEVI bool mbar_test(uint32_t a, uint32_t parity) {
  uint32_t ok;
  asm volatile("{\n.reg .pred p;\nmbarrier.test_wait.parity.shared::cta.b64 p, [%1], %2;\nselp.u32 %0, 1, 0, p;\n}" : "=r"(ok) : "r"(a), "r"(parity) : "memory");
  return ok;
}
DEVI bool elect() {
  uint32_t ok;
  asm volatile("{\n.reg .pred p;\nelect.sync _|p, 0xffffffff;\nselp.u32 %0, 1, 0, p;\n}" : "=r"(ok));
  return ok;
}
DEVI void flag_wait(const unsigned* p, unsigned target) {
  int n = 0; unsigned v;
  do {
    asm volatile("ld.acquire.gpu.global.u32 %0, [%1];" : "=r"(v) : "l"(p) : "memory");
  } while ((int)(v - target) < 0 && ++n < kSpinLimit);
}
DEVI uint32_t clock32() { uint32_t t; asm volatile("mov.u32 %0, %%clock;" : "=r"(t) :: "memory"); return t; }
DEVI void delay(uint32_t cycles) { const uint32_t t = clock32(); while (clock32() - t < cycles) { } }
DEVI void st_relaxed(void* p, uint32_t v) { asm volatile("st.relaxed.gpu.global.b32 [%0], %1;" :: "l"(p), "r"(v) : "memory"); }
DEVI uint32_t ld_relaxed(const void* p) { uint32_t v; asm volatile("ld.relaxed.gpu.global.b32 %0, [%1];" : "=r"(v) : "l"(p) : "memory"); return v; }
DEVI void ld_relaxed4(uint32_t* v, const void* p) {
  asm volatile("ld.relaxed.gpu.global.v4.b32 {%0,%1,%2,%3}, [%4];" : "=r"(v[0]), "=r"(v[1]), "=r"(v[2]), "=r"(v[3]) : "l"(p) : "memory");
}
template <int N> DEVI uint32_t umax(const uint32_t* v) {
  if constexpr (N == 1) return v[0];
  else if constexpr (N == 2) return max(v[0], v[1]);
  else if constexpr (N <= 6) return __vimax3_u32(v[0], v[1], umax<N - 2>(v + 2));
  else return __vimax3_u32(umax<N / 3 | 1>(v), umax<N / 3 | 1>(v + (N / 3 | 1)), umax<N - 2 * (N / 3 | 1)>(v + 2 * (N / 3 | 1)));
}
template <int N> DEVI bool all_arrived(const uint32_t* v) { return __all_sync(0xffffffffu, umax<N>(v) != 0xffffffffu); }
DEVI void flag_add(unsigned* p) {
  asm volatile("fence.release.gpu;\nred.relaxed.gpu.global.add.u32 [%0], 1;" :: "l"(p) : "memory");
}
DEVI void fence_async_smem() { asm volatile("fence.proxy.async.shared::cta;" ::: "memory"); }
DEVI void bar_sync(int id, int n) { asm volatile("bar.sync %0, %1;" :: "r"(id), "r"(n) : "memory"); }
DEVI void cluster_arrive() { asm volatile("barrier.cluster.arrive.relaxed.aligned;" ::: "memory"); }
DEVI void cluster_wait() { asm volatile("barrier.cluster.wait.aligned;" ::: "memory"); }
DEVI void wg_fence() { asm volatile("wgmma.fence.sync.aligned;" ::: "memory"); }
DEVI void wg_commit() { asm volatile("wgmma.commit_group.sync.aligned;" ::: "memory"); }
template <int N> DEVI void wg_wait() { asm volatile("wgmma.wait_group.sync.aligned %0;" :: "n"(N) : "memory"); }
template <int N> DEVI void pin(uint32_t* r) {
#pragma unroll
  for (int i = 0; i < N; i++) asm volatile("" : "+r"(r[i]) :: "memory");
}
template <int N> DEVI void pin(float* r) {
#pragma unroll
  for (int i = 0; i < N; i++) asm volatile("" : "+f"(r[i]) :: "memory");
}

DEVI void sched_fence(int zero, int id) { asm volatile("{\n.reg .pred p;\nsetp.eq.b32 p, %0, %1;\nS_LOOP:\n@p st.volatile.shared.b32 [%0], %0;\n@p bra S_LOOP;\n}" :: "r"(zero), "r"(id + 1) : "memory"); }
DEVI void pin_range(float* r, int i0, int i1) {
#pragma unroll
  for (int i = i0; i < i1; i++) asm volatile("" : "+f"(r[i]) :: "memory");
}
DEVI void keep(uint32_t& x) { asm volatile("" : "+r"(x) :: "memory"); }
DEVI void keep(int& x) { asm volatile("" : "+r"(x) :: "memory"); }
template <class T> DEVI void keep(T*& x) { asm volatile("" : "+l"(x) :: "memory"); }

DEVI void tma2d(uint32_t dst, const CUtensorMap* m, int c0, int c1, uint32_t bar) {
  asm volatile("cp.async.bulk.tensor.2d.shared::cluster.global.mbarrier::complete_tx::bytes [%0], [%1, {%3, %4}], [%2];"
               :: "r"(dst), "l"(m), "r"(bar), "r"(c0), "r"(c1) : "memory");
}
DEVI void tma2d_mc(uint32_t dst, const CUtensorMap* m, int c0, int c1, uint32_t bar) {
  asm volatile("cp.async.bulk.tensor.2d.shared::cluster.global.mbarrier::complete_tx::bytes.multicast::cluster [%0], [%1, {%3, %4}], [%2], %5;"
               :: "r"(dst), "l"(m), "r"(bar), "r"(c0), "r"(c1), "h"((uint16_t)3) : "memory");
}
DEVI void tma3d(uint32_t dst, const CUtensorMap* m, int c0, int c1, int c2, uint32_t bar) {
  asm volatile("cp.async.bulk.tensor.3d.shared::cluster.global.mbarrier::complete_tx::bytes [%0], [%1, {%3, %4, %5}], [%2];"
               :: "r"(dst), "l"(m), "r"(bar), "r"(c0), "r"(c1), "r"(c2) : "memory");
}
DEVI void tma3d_mc(uint32_t dst, const CUtensorMap* m, int c0, int c1, int c2, uint32_t bar) {
  asm volatile("cp.async.bulk.tensor.3d.shared::cluster.global.mbarrier::complete_tx::bytes.multicast::cluster [%0], [%1, {%3, %4, %5}], [%2], %6;"
               :: "r"(dst), "l"(m), "r"(bar), "r"(c0), "r"(c1), "r"(c2), "h"((uint16_t)3) : "memory");
}
DEVI void tma2d_store(const CUtensorMap* m, uint32_t src, int c0, int c1) {
  asm volatile("cp.async.bulk.tensor.2d.global.shared::cta.bulk_group [%0, {%2, %3}], [%1];" :: "l"(m), "r"(src), "r"(c0), "r"(c1) : "memory");
}
DEVI void bulk_load(uint32_t dst, const void* src, uint32_t bytes, uint32_t bar) {
  asm volatile("cp.async.bulk.shared::cluster.global.mbarrier::complete_tx::bytes [%0], [%1], %2, [%3];" :: "r"(dst), "l"(src), "r"(bytes), "r"(bar) : "memory");
}
DEVI void bulk_store(void* dst, uint32_t src, uint32_t bytes) {
  asm volatile("cp.async.bulk.global.shared::cta.bulk_group [%0], [%1], %2;" :: "l"(dst), "r"(src), "r"(bytes) : "memory");
}
DEVI uint32_t peer_addr(uint32_t a, int rank) { uint32_t r; asm("mapa.shared::cluster.u32 %0, %1, %2;" : "=r"(r) : "r"(a), "r"(rank)); return r; }
DEVI void bulk_to_peer(uint32_t dst, uint32_t src, uint32_t bytes, uint32_t bar, int rank) {
  asm volatile("cp.async.bulk.shared::cluster.shared::cta.mbarrier::complete_tx::bytes [%0], [%1], %2, [%3];"
               :: "r"(peer_addr(dst, rank)), "r"(src), "r"(bytes), "r"(peer_addr(bar, rank)) : "memory");
}
DEVI void l2_prefetch(const void* p, uint32_t bytes) {
  asm volatile("cp.async.bulk.prefetch.L2.global [%0], %1;" :: "l"(p), "r"(bytes) : "memory");
}
DEVI void l2_prefetch2d(const CUtensorMap* m, int c0, int c1) {
  asm volatile("cp.async.bulk.prefetch.tensor.2d.L2.global [%0, {%1, %2}];" :: "l"(m), "r"(c0), "r"(c1) : "memory");
}
DEVI void l2_prefetch3d(const CUtensorMap* m, int c0, int c1, int c2) {
  asm volatile("cp.async.bulk.prefetch.tensor.3d.L2.global [%0, {%1, %2, %3}];" :: "l"(m), "r"(c0), "r"(c1), "r"(c2) : "memory");
}
DEVI void bulk_commit() { asm volatile("cp.async.bulk.commit_group;" ::: "memory"); }
DEVI void bulk_wait_read() { asm volatile("cp.async.bulk.wait_group.read 0;" ::: "memory"); }
DEVI void prefetch_map(const CUtensorMap* m) { asm volatile("prefetch.tensormap [%0];" :: "l"(m) : "memory"); }
DEVI void arrive_both(uint32_t bar, int lane, bool pred = true) {
  asm volatile("{\n.reg .pred p;\n.reg .b32 r;\nsetp.ne.b32 p, %2, 0;\nmapa.shared::cluster.u32 r, %0, %1;\n@p mbarrier.arrive.shared::cluster.b64 _, [r];\n}"
               :: "r"(bar), "r"(lane & 1), "r"((int)(pred && lane < 2)) : "memory");
}

DEVI uint64_t make_desc(uint32_t off, uint32_t lbo, uint32_t sbo, uint32_t mode) {
  const uint32_t lo = (off >> 4) + (SM_BASE >> 4) + ((lbo >> 4) << 16), hi = (sbo >> 4) | (mode << 30);
  return ((uint64_t)hi << 32) | lo;
}
DEVI uint32_t pack_bf16(float lo, float hi) { uint32_t r; asm("cvt.rn.bf16x2.f32 %0, %1, %2;" : "=r"(r) : "f"(hi), "f"(lo)); return r; }
DEVI void stsm4(uint32_t addr, uint32_t r0, uint32_t r1, uint32_t r2, uint32_t r3) {
  asm volatile("stmatrix.sync.aligned.m8n8.x4.shared.b16 [%0], {%1,%2,%3,%4};" :: "r"(addr), "r"(r0), "r"(r1), "r"(r2), "r"(r3) : "memory");
}
DEVI void stsm4_t(uint32_t addr, uint32_t r0, uint32_t r1, uint32_t r2, uint32_t r3) {
  asm volatile("stmatrix.sync.aligned.m8n8.x4.trans.shared.b16 [%0], {%1,%2,%3,%4};" :: "r"(addr), "r"(r0), "r"(r1), "r"(r2), "r"(r3) : "memory");
}
DEVI void ldsm4(uint32_t* r, uint32_t addr) {
  asm volatile("ldmatrix.sync.aligned.m8n8.x4.shared.b16 {%0,%1,%2,%3}, [%4];" : "=r"(r[0]), "=r"(r[1]), "=r"(r[2]), "=r"(r[3]) : "r"(addr) : "memory");
}
DEVI void ldsm4_t(uint32_t* r, uint32_t addr) {
  asm volatile("ldmatrix.sync.aligned.m8n8.x4.trans.shared.b16 {%0,%1,%2,%3}, [%4];" : "=r"(r[0]), "=r"(r[1]), "=r"(r[2]), "=r"(r[3]) : "r"(addr) : "memory");
}
DEVI uint4 lds128(uint32_t a) {
  uint4 v; asm volatile("ld.shared.v4.b32 {%0,%1,%2,%3}, [%4];" : "=r"(v.x), "=r"(v.y), "=r"(v.z), "=r"(v.w) : "r"(a) : "memory"); return v;
}
DEVI uint32_t bmul2(uint32_t a, uint32_t b) { uint32_t r; asm("mul.rn.bf16x2 %0, %1, %2;" : "=r"(r) : "r"(a), "r"(b)); return r; }
DEVI uint32_t bfma2(uint32_t a, uint32_t b, uint32_t c) { uint32_t r; asm("fma.rn.bf16x2 %0, %1, %2, %3;" : "=r"(r) : "r"(a), "r"(b), "r"(c)); return r; }
DEVI float bf_lo(uint32_t w) { return __uint_as_float(w << 16); }
DEVI float bf_hi(uint32_t w) { return __uint_as_float(w & 0xffff0000u); }
DEVI uint32_t elu1(float a0, float a1) {
  constexpr float L = 1.4426950408889634f;
  float e0, e1;
  asm("ex2.approx.ftz.f32 %0, %1;" : "=f"(e0) : "f"(-fabsf(fmaf(a0, L, -L))));
  asm("ex2.approx.ftz.f32 %0, %1;" : "=f"(e1) : "f"(-fabsf(fmaf(a1, L, -L))));
  return pack_bf16(fmaxf(e0, a0), fmaxf(e1, a1));
}
DEVI float rcp(float x) { float r; asm("rcp.approx.ftz.f32 %0, %1;" : "=f"(r) : "f"(x)); return r; }
DEVI uint32_t add_eps(uint32_t x) { uint32_t r; asm("add.rn.bf16x2 %0, %1, %2;" : "=r"(r) : "r"(x), "r"(0x35863586u)); return r; }

DEVI uint32_t hmul(uint32_t a, uint32_t b) { uint32_t r; asm("mul.rn.f16x2 %0, %1, %2;" : "=r"(r) : "r"(a), "r"(b)); return r; }
DEVI uint32_t hfma(uint32_t a, uint32_t b, uint32_t c) { uint32_t r; asm("fma.rn.f16x2 %0, %1, %2, %3;" : "=r"(r) : "r"(a), "r"(b), "r"(c)); return r; }
DEVI uint32_t hneg(uint32_t a) { uint32_t r; asm("neg.f16x2 %0, %1;" : "=r"(r) : "r"(a)); return r; }
DEVI uint32_t hadd(uint32_t a, uint32_t b) { uint32_t r; asm("add.rn.f16x2 %0, %1, %2;" : "=r"(r) : "r"(a), "r"(b)); return r; }
DEVI uint32_t hsub(uint32_t a, uint32_t b) { uint32_t r; asm("sub.rn.f16x2 %0, %1, %2;" : "=r"(r) : "r"(a), "r"(b)); return r; }
struct Cx { uint32_t re, im; };
DEVI Cx cmul(Cx a, Cx b) { return {hfma(a.re, b.re, hneg(hmul(a.im, b.im))), hfma(a.re, b.im, hmul(a.im, b.re))}; }
DEVI Cx cfma(Cx a, Cx b, Cx c) { return {hfma(a.re, b.re, hfma(hneg(a.im), b.im, c.re)), hfma(a.re, b.im, hfma(a.im, b.re, c.im))}; }
DEVI Cx rot(Cx a, Cx t) {
  const uint32_t x = hfma(hneg(t.re), a.im, a.re), y = hfma(t.im, x, a.im);
  return {hfma(hneg(t.re), y, x), y};
}
struct Fft {
  uint32_t fa[8];
  Cx tw[2];
  uint32_t vld;
  uint64_t dF2a, dF2b;
  uint32_t vst;
  DEVI void stage1(uint32_t* d1, uint32_t slot) const {
    wg_fence();
    fft1_init(d1, fa[0], fa[1], fa[2], fa[3], make_desc(slot, 4096, 1024, 1));
    fft1_acc(d1, fa[4], fa[5], fa[6], fa[7], make_desc(slot + 2048, 4096, 1024, 1));
    wg_commit();
  }
  DEVI void stage2(uint32_t* d, const Cx* t) const {
    wg_fence();
    fft2_init(d, t[0].re, t[1].re, t[2].re, t[3].re, dF2a);
    fft2_acc(d, t[0].im, t[1].im, t[2].im, t[3].im, dF2b);
    wg_commit();
  }
  template <int PR> DEVI void fwd(const uint32_t* d1, uint32_t* d2) const {
    Cx t[4];
#pragma unroll
    for (int e = 0; e < 4; e++) {
      const int j = 8 * (PR & 1) + 4 * (e >> 1) + 2 * (PR >> 1) + (e & 1);
      t[e] = rot({d1[2 * j], d1[2 * j + 1]}, tw[e >> 1]);
    }
    stage2(d2 + 8 * PR, t);
  }
  static DEVI Cx U(const uint32_t* d2, int p, int hi) { return {d2[16 * (p >> 1) + 2 * hi + (p & 1)], d2[16 * (p >> 1) + 4 + 2 * hi + (p & 1)]}; }
  static DEVI Cx H(const uint32_t* d2, int p, int hi) { return U(d2 + 8, p, hi); }
  DEVI void prod01(const uint32_t* d2, Cx* p1, uint32_t* d3) const {
    Cx z[4];
#pragma unroll
    for (int hi = 0; hi < 2; hi++) {
      const Cx p0 = cmul(H(d2, 0, hi), U(d2, 0, hi));
      p1[hi] = cfma(H(d2, 1, hi), U(d2, 0, hi), cmul(H(d2, 0, hi), U(d2, 1, hi)));
      z[2 * hi] = {p0.im, p0.re};
      z[2 * hi + 1] = {hsub(p1[hi].im, p0.re), hadd(p1[hi].re, p0.im)};
    }
    stage2(d3, z);
  }
  DEVI void prod23(const uint32_t* d2, const Cx* p1, uint32_t* d3) const {
    Cx z[4];
#pragma unroll
    for (int hi = 0; hi < 2; hi++) {
      const Cx p2 = cfma(H(d2, 2, hi), U(d2, 0, hi), cfma(H(d2, 0, hi), U(d2, 2, hi), cmul(H(d2, 1, hi), U(d2, 1, hi))));
      const Cx z3 = cfma(H(d2, 3, hi), U(d2, 0, hi), cfma(H(d2, 2, hi), U(d2, 1, hi),
                    cfma(H(d2, 1, hi), U(d2, 2, hi), cfma(H(d2, 0, hi), U(d2, 3, hi), {p2.im, hneg(p2.re)}))));
      z[2 * hi] = {hsub(p2.im, p1[hi].re), hadd(p2.re, p1[hi].im)};
      z[2 * hi + 1] = {z3.im, z3.re};
    }
    stage2(d3 + 8, z);
  }
  template <int PB> DEVI void inv(const uint32_t* d3, uint32_t slot) const {
    Cx v[4];
#pragma unroll
    for (int e = 0; e < 4; e++) {
      const int r = 8 * PB + 2 * (e & 1) + (e >> 1);
      v[e] = rot({d3[r], d3[r + 4]}, tw[e & 1]);
    }
    stsm4(slot + (vst ^ (PB * 64)), v[0].im, v[1].im, v[2].im, v[3].im);
    stsm4(slot + 1024 + (vst ^ (PB * 64)), v[0].re, v[1].re, v[2].re, v[3].re);
  }
  DEVI void last_load(uint32_t* a, uint32_t slot, int wg) const {
    bar_sync(2 + wg, 128);
#pragma unroll
    for (int ks = 0; ks < 4; ks++) ldsm4_t(a + 4 * ks, vld + slot + ks * 2048);
  }
  DEVI void last_mma(float* dy, const uint32_t* a) const {
    wg_fence();
    fft3_init(dy, a[0], a[1], a[2], a[3], make_desc(SM_F1, 128, 1024, 0));
#pragma unroll
    for (int ks = 1; ks < 4; ks++) fft3_acc(dy, a[4 * ks], a[4 * ks + 1], a[4 * ks + 2], a[4 * ks + 3], make_desc(SM_F1 + ks * 256, 128, 1024, 0));
    wg_commit();
  }
  DEVI void last(float* dy, uint32_t slot, int wg) const { uint32_t a[16]; last_load(a, slot, wg); last_mma(dy, a); }
  static DEVI void store_y(const float* dy, uint32_t a) {
    stsm4_t(a, pack_bf16(dy[0], dy[1]), pack_bf16(dy[2], dy[3]), pack_bf16(dy[4], dy[5]), pack_bf16(dy[6], dy[7]));
    stsm4_t(a + 512, pack_bf16(dy[8], dy[9]), pack_bf16(dy[10], dy[11]), pack_bf16(dy[12], dy[13]), pack_bf16(dy[14], dy[15]));
  }
};
DEVI uint32_t normalize(uint32_t* x, uint32_t dst) {
  uint32_t m = x[0];
#pragma unroll
  for (int i = 1; i < 32; i++) asm("max.xorsign.abs.bf16x2 %0, %0, %1;" : "+r"(m) : "r"(x[i]));
  const uint32_t e = min(__reduce_max_sync(0xffffffffu, max(m & 0x7fffu, (m >> 16) & 0x7fffu)) >> 7, 252u);
  if (e > 140) {
#pragma unroll
    for (int i = 0; i < 32; i++) x[i] = bmul2(x[i], 15u * 0x00800080u);
  }
  const uint32_t sc = (e > 140 ? 253u - e : 141u - e) * 0x00800080u;
#pragma unroll
  for (int i = 0; i < 8; i++) {
    uint32_t y[4];
#pragma unroll
    for (int n = 0; n < 4; n++) {
      const uint32_t w = bmul2(x[4 * i + n], sc);
      y[n] = (w & 0x7fff7fffu) * 7u + w;
    }
    stsm4((dst ^ ((i >> 1) << 4)) + (i & 1) * 2048, y[0], y[1], y[2], y[3]);
  }
  return e;
}
#define HSTART 3
#define PSTART 5
#define PF0 28
#define PD1 600
#define PD2 500
#define PD3 900
#define FDELAY 100
#define C1DELAY 200
#define FORCE_REDO 0
static_assert(HSTART <= 4 && PF0 >= HSTART + 19 && PF0 <= 28, "producer schedule");

__global__ void __cluster_dims__(2, 1, 1) __launch_bounds__(kThreads, 1)
fused_kernel(const __grid_constant__ Params P) {
  extern __shared__ __align__(1024) uint8_t smem[];
  if (threadIdx.x == 0) { prefetch_map(&P.x); prefetch_map(&P.w); prefetch_map(&P.wk); prefetch_map(blockIdx.x & 1 ? &P.v : &P.k); }
  const uint32_t sb = __shfl_sync(0xffffffffu, (uint32_t)__cvta_generic_to_shared(smem), 0);
  const int tid = threadIdx.x, lane = tid & 31;
  const int warp = __shfl_sync(0xffffffffu, tid >> 5, 0);
  const int bc = blockIdx.x >> 1, late = ((bc - 36) * 37) >> 8;
  const int rp = bc < 4 ? 0 : bc < 36 ? (bc - 4) & 7 : bc - 35 - 7 * late, j = bc < 4 ? 4 + bc : bc < 36 ? (bc - 4) >> 3 : 4 + late;
  const int rho = blockIdx.x & 1, cl = 8 * rp + j, cta = 2 * cl + rho, r = rp * 2 + rho;
  auto bar = [&](int i) { return sb + SM_BAR + 8u * i; };
  TSTAMP(tid == 0, 0); GSTAMP(tid == 0, 30);
  auto load_stage = [&](int it) {
    const uint32_t st = sb + (it & 3) * QKV_STAGE, fb = bar(B_QKV_FULL + (it & 3));
    mbar_expect(fb, QKV_STAGE);
    tma2d_mc(st + 24576 + rho * 4096, &P.wk, 1024 + 128 * j + 64 * rho, 32 * it, fb);
    tma3d_mc(st + 8192 + rho * 8192, &P.w, 0, 32 * it, 32 * rho + 2 * j, fb);
    tma2d(st, &P.x, 32 * it, 128 * r, fb);
  };
  if (warp == 8 && elect()) {
    mbar_init(bar(B_FIRST), 1);
    mbar_expect(bar(B_FIRST), 16384);
    tma2d(sb, &P.x, 0, 128 * r, bar(B_FIRST));
    tma3d(sb + 24576, &P.w, 0, 0, 16 + 2 * j, bar(B_FIRST));
    mbar_init(bar(B_QKV_FULL), 1);
    mbar_expect(bar(B_QKV_FULL), 16384);
    tma3d(sb + 8192, &P.w, 0, 0, 2 * j, bar(B_QKV_FULL));
    tma3d(sb + 16384, &P.w, 0, 0, 32 + 2 * j, bar(B_QKV_FULL));
    for (int i = 1; i < 4; i++) mbar_init(bar(B_QKV_FULL + i), 1);
    asm volatile("fence.mbarrier_init.release.cluster;" ::: "memory");
  }
  LOOPSTAMP(3, tid == 256, 13);
  __syncwarp();
  cluster_arrive();

  if (warp < 8) {
    asm volatile("setmaxnreg.inc.sync.aligned.u32 224;");
    const int wg = warp >> 2, wq = warp & 3;
    const int zero = __shfl_sync(0xffffffffu, P.zero, 0);
    const uint32_t orow = wq * 2048 + (lane & 15) * 128, ox = ((lane >> 4) ^ (lane & 7)) << 4;
    float aq[64];
    Fft F;
    uint32_t a1[32];
    {
      float ak[64], avq[128];
      auto k_step = [&](uint32_t st, int kk) {
        mma_tn(ak, make_desc(st + 24576 + wg * 4096 + kk * 2048, 4096, 1024, 1), make_desc(st + kk * 32, 16, 512, 2));
      };
      auto vq_step = [&](uint32_t st, int kk) {
        mma_nt256(avq, make_desc(st + wg * 4096 + kk * 32, 16, 512, 2), make_desc(st + 8192 + kk * 2048, 4096, 1024, 1));
      };
#pragma unroll
      for (int i = 0; i < 64; i++) { ak[i] = 1.f; avq[i] = 1.f; avq[64 + i] = 0.f; }
      pin<64>(ak); pin<128>(avq);
      cluster_wait();
      cluster_arrive();
      cluster_wait();
      LOOPSTAMP(3, tid == 0, 17);
      mbar_wait(bar(B_FIRST), 0);
      TSTAMP(tid == 0, 1);
      wg_fence();
      k_step(0, 0); k_step(0, 1);
      wg_commit();
      mbar_wait(bar(B_QKV_FULL), 0);
      wg_fence();
      vq_step(0, 0); vq_step(0, 1);
      wg_commit();
#pragma unroll 1
      for (int it = 1; it < 29; ++it) {
        mbar_wait(bar(B_QKV_FULL + (it & 3)), (it >> 2) & 1);
        TSTAMP(tid == 0 && it == 4, 6); TSTAMP(tid == 0 && it == 12, 29); LOOPSTAMP(1, tid == 0 && it < 27, 1 + it); LOOPSTAMP(3, tid == 0 && it < 12, 1 + it);
        const uint32_t st = (it & 3) * QKV_STAGE;
        wg_fence();
        k_step(st, 0);
        wg_commit();
        wg_wait<1>();
        arrive_both(bar(B_QKV_EMPTY + ((it - 1) & 3)), lane);
        wg_fence();
        vq_step(st, 0);
        k_step(st, 1);
        vq_step(st, 1);
        wg_commit();
      }
#pragma unroll 1
      for (int s = 1; s < 4; ++s) {
        mbar_wait(bar(B_QKV_FULL + s), 1);
        wg_fence();
        k_step(s * QKV_STAGE, 0);
        k_step(s * QKV_STAGE, 1);
        wg_commit();
      }
      uint32_t pk[32];
      auto phi_k = [&](int i0, int i1) {
#pragma unroll
        for (int i = i0; i < i1; i++) { pk[i] = elu1(ak[2 * i], ak[2 * i + 1]); asm volatile("" : "+r"(pk[i]) :: "memory"); }
        sched_fence(zero, i0);
      };
#pragma unroll
      for (int n = 0; n < 6; n++) {
        wg_fence();
        vq_step((1 + (n >> 1)) * QKV_STAGE, n & 1);
        wg_commit();
        if (n == 0) {
          wg_wait<1>();
          pin<64>(ak);
          TSTAMP(tid == 0, 2);
          bar_sync(1, 256);
        }
        phi_k(n ? 6 * n - 4 : 0, 6 * n + 2);
      }
      mbar_wait(bar(B_SIG_READY), 0);
      ldsm4_t(F.fa, sb + SM_F1 + (lane >> 4) * 1024 + wq * 256 + (lane & 15) * 16);
      ldsm4_t(F.fa + 4, sb + SM_F1 + 2048 + (lane >> 4) * 1024 + wq * 256 + (lane & 15) * 16);
      const uint4 tw = lds128(sb + SM_TW + (tid & 127) * 16);
      F.tw[0] = {tw.x, tw.y}; F.tw[1] = {tw.z, tw.w};
      F.vld = sb + ((lane >> 4) * 8 + (lane & 7)) * 128 + (((2 * wq + ((lane >> 3) & 1)) ^ (lane & 7)) << 4);
      F.dF2a = make_desc(SM_F2, 128, 512, 0) + (uint64_t)zero * 0x100000001ull;
      F.dF2b = F.dF2a + 16;
      F.vst = sb + (16 * wq + (lane & 7)) * 128 + (((lane >> 3) ^ (lane & 7)) << 4);
      wg_wait<0>();
      pin<128>(avq);
      arrive_both(bar(B_QKV_DONE), lane);
      TSTAMP(tid == 0, 3);
#pragma unroll
      for (int t = 0; t < 8; t++) {
        const float* b = avq + 64 + 8 * t;
        stsm4(sb + (t >> 2) * SLOT + wg * 8192 + orow + (ox ^ ((t & 3) << 5)), pack_bf16(b[0], b[1]), pack_bf16(b[2], b[3]), pack_bf16(b[4], b[5]), pack_bf16(b[6], b[7]));
      }
#pragma unroll
      for (int i = 0; i < 64; i++) aq[i] = avq[i];
      fence_async_smem();
      bar_sync(1, 256);
      float dkv[36];
#pragma unroll
      for (int ks = 0; ks < 8; ks++) {
        const uint32_t va = wg * SLOT + ks * 2048;
        const uint64_t db = make_desc(va, SM_ONES - va, 1024, 1);
        uint32_t a[4];
        pin<4>(pk + 4 * ks);
#pragma unroll
        for (int i = 0; i < 4; i++) a[i] = add_eps(pk[4 * ks + i]);
        wg_fence();
        if (ks == 0) mma_kv_init(dkv, a[0], a[1], a[2], a[3], db);
        else mma_kv_acc(dkv, a[0], a[1], a[2], a[3], db);
      }
      wg_commit();
      uint8_t* box = g_xch[warp * 16 + j] + 2 * SLOT + r * KV_SLICE + lane * 16;
      uint8_t* zbox = box + (lane & 1) * 8 * XCH_BYTES + 512 + (lane & 28) - lane * 16;
      keep(box); keep(zbox);
      mbar_wait(bar(B_ZEROED), 0);
      wg_wait<0>();
      pin<36>(dkv);
      F.stage1(a1, SM_SIG + wg * 8192);
      TSTAMP(tid == 0, 4);
      auto put = [&](const float* d) {
#pragma unroll
        for (int m = 0; m < 2; m++)
          asm volatile("st.relaxed.gpu.global.v4.b32 [%0], {%1,%2,%3,%4};" :: "l"(box + m * 8 * XCH_BYTES), "r"(pack_bf16(d[2 * m], d[2 * m + 1])),
                       "r"(pack_bf16(d[2 * m + 4], d[2 * m + 5])), "r"(pack_bf16(d[2 * m + 8], d[2 * m + 9])), "r"(pack_bf16(d[2 * m + 12], d[2 * m + 13])) : "memory");
      };
      if (wq < 2) put(dkv); else put(dkv + 16);
      asm volatile("{\n.reg .pred p;\nsetp.eq.b32 p, %2, 0;\n@p st.relaxed.gpu.global.b32 [%0], %1;\n}" :: "l"(zbox), "f"(lane & 1 ? dkv[34] : dkv[32]), "r"(lane & 2) : "memory");
      __syncwarp();
      mbar_arrive_if(bar(B_KVP), lane == 0);
      TSTAMP(tid == 0, 5);
    }

    uint32_t pq[32];
    auto phi_q = [&](int i0, int i1) {
      pin_range(aq, 2 * i0, 2 * i1);
#pragma unroll
      for (int i = i0; i < i1; i++) { pq[i] = add_eps(elu1(aq[2 * i], aq[2 * i + 1])); keep(pq[i]); }
    };
    uint32_t a2[32];
    float by[16];
    auto conv_pair = [&](uint32_t sa, uint32_t ya, uint32_t first) {
      const uint32_t sc = sa + SLOT;
      uint32_t b1[32], b2[32], a3[16], b3[16];
      float ay[16];
      Cx pa[2], pb[2];
      F.stage1(b1, sc);
      F.prod01(a2, pa, a3);
      F.prod23(a2, pa, a3);
      uint32_t va[16];
      wg_wait<1>(); pin<32>(b1); pin<8>(a3);
      F.fwd<0>(b1, b2); F.fwd<1>(b1, b2);
      F.inv<0>(a3, sa);
      F.fwd<2>(b1, b2);
      wg_wait<3>(); pin<8>(a3 + 8);
      F.inv<1>(a3, sa);
      F.fwd<3>(b1, b2);
      F.last_load(va, sa, wg);
      wg_wait<2>(); pin<16>(b2);
      F.prod01(b2, pb, b3);
      F.last_mma(ay, va);
      wg_wait<2>(); pin<16>(b2 + 16);
      F.prod23(b2, pb, b3);
      mbar_wait(bar(B_RDY1), first);
      wg_wait<1>(); pin<8>(b3); pin<16>(ay);
      mbar_arrive_if(bar(B_SLOT_FREE), lane == 0);
      F.inv<0>(b3, sc);
      Fft::store_y(ay, ya);
      wg_wait<0>(); pin<8>(b3 + 8);
      F.inv<1>(b3, sc);
    };
    const bool ylocal = (wq >> 1) == rho;
    const uint32_t yoff = sb + (wq & 1) * 1024 + ((lane ^ wg ^ (2 * rho)) << 4);
    const uint32_t ya0 = yoff + (ylocal ? SM_Y0 + wg * 8192 : SM_YT + wg * 4096), ya1 = (yoff ^ 64) + (ylocal ? SM_SIG + wg * 8192 : SM_YT + wg * 4096);
    auto pair_done = [&](uint32_t ya, int seg) {
      pin<16>(by);
      Fft::store_y(by, (ya ^ 32) + 2048);
      __syncwarp();
      mbar_arrive_if(bar(B_SEG + 2 * seg + wg), lane == 0);
    };
    const uint32_t s0 = SM_SIG + wg * 8192, s1 = s0 + 2 * SLOT;
    phi_q(0, 2);
    wg_wait<0>(); pin<32>(a1);
    bar_sync(2 + wg, 128);
    F.fwd<0>(a1, a2); phi_q(2, 5);
    F.fwd<1>(a1, a2); phi_q(5, 8);
    F.fwd<2>(a1, a2); phi_q(8, 11);
    F.fwd<3>(a1, a2); phi_q(11, 13);
    wg_wait<0>(); pin<32>(a2);
#pragma unroll 1
    for (uint32_t sa = s0;; sa += 2 * SLOT + P.zero) {
      conv_pair(sa, sa == s1 ? ya1 : ya0, sa != s1);
      if (sa == s1) break;
      F.stage1(a1, s1);
      phi_q(13, 17);
      F.last(by, s0 + SLOT, wg);
      phi_q(17, 32);
      wg_wait<0>();
      pair_done(ya0, 0);
      TSTAMP(tid == 0, 7);
      float dn[4][20];
      pin<32>(a1);
      bar_sync(2 + wg, 128);
      F.fwd<0>(a1, a2); F.fwd<1>(a1, a2); F.fwd<2>(a1, a2);
      mbar_wait(bar(B_KV_READY), 0);
      TSTAMP(tid == 0, 8);
      auto head_mma = [&](int h) {
        wg_fence();
        const uint64_t db = make_desc(SM_KV + h * 2560, 640, 128, 0);
        const uint32_t* a = pq + 8 * h;
        mma_o_init(dn[h], a[0], a[1], a[2], a[3], db);
        mma_o_acc(dn[h], a[4], a[5], a[6], a[7], db + (1280 >> 4));
        wg_commit();
      };
      auto head_store = [&](int h) {
        pin<20>(dn[h]);
        const float i0 = rcp(dn[h][16] + 1e-6f), i1 = rcp(dn[h][18] + 1e-6f);
        const uint32_t p0 = pack_bf16(i0, i0), p1 = pack_bf16(i1, i1);
#pragma unroll
        for (int hf = 0; hf < 2; hf++) {
          const float* a = dn[h] + 8 * hf;
          const uint32_t dst = sb + (h >> 1) * SLOT + wg * 8192 + orow + (ox ^ (((h & 1) * 2 + hf) << 5));
          uint32_t o[4];
#pragma unroll
          for (int i = 0; i < 4; i++) o[i] = bmul2(pack_bf16(a[2 * i], a[2 * i + 1]), i & 1 ? p1 : p0);
          stsm4(dst, o[0], o[1], o[2], o[3]);
#pragma unroll
          for (int i = 0; i < 4; i++) pq[8 * h + 4 * hf + i] = o[i];
        }
        if (h & 1) { __syncwarp(); mbar_arrive_if(bar(B_O_WRITTEN + (h >> 1)), lane == 0); }
      };
      head_mma(0); head_mma(1);
      wg_wait<1>(); head_store(0);
      mbar_wait(bar(B_KV_READY + 1), 0);
      head_mma(2);
      wg_wait<1>(); head_store(1);
      head_mma(3);
      wg_wait<1>(); head_store(2);
      F.fwd<3>(a1, a2);
      wg_wait<1>(); head_store(3);
      wg_wait<0>();
      pin<32>(a2);
    }

    float acc[64];
    auto stage_mma = [&](int s, int kk) {
      mma_nt(acc, make_desc(((A_SLOTS >> (4 * s)) & 15) * SLOT + wg * 8192 + kk * 32, 16, 1024, 1),
             make_desc(((B_SLOTS >> (4 * s)) & 15) * SLOT + kk * 2048, 8192, 1024, 1));
    };
    {
      auto own_mma = [&](int n) {
        const uint64_t db = make_desc((4 + (n >> 2)) * SLOT + (n & 3) * 2048, 8192, 1024, 1);
        if (n == 0) mma_own_init(acc, pq[0], pq[1], pq[2], pq[3], db);
        else mma_own_acc(acc, pq[4 * n], pq[4 * n + 1], pq[4 * n + 2], pq[4 * n + 3], db);
      };
      mbar_wait(bar(B_OUT_FULL), 0);
      wg_fence();
      own_mma(0);
      wg_commit();
      F.last(by, s1 + SLOT, wg);
      wg_fence();
      own_mma(1);
      wg_commit();
      wg_wait<1>();
      pair_done(ya1, 1);
      mbar_arrive_if(bar(B_CONV_DONE), lane == 0);
      cluster_arrive();
      wg_fence();
      own_mma(2); own_mma(3);
      wg_commit();
      mbar_wait(bar(B_OUT_FULL + 1), 0);
      wg_fence();
      own_mma(4);
      wg_commit();
      wg_wait<1>();
      arrive_both(bar(B_OUT_EMPTY), lane);
      wg_fence();
      own_mma(5); own_mma(6); own_mma(7);
      wg_commit();
      int s = 2, sprev = 1;
      uint32_t ph = 0;
#pragma unroll 1
      for (int ks = 2; ks < 12; ++ks) {
        mbar_wait(bar(B_OUT_FULL + s), ph);
        LOOPSTAMP(2, tid == 0, 1 + ks);
        TSTAMP(tid == 0 && ks == 2, 13); TSTAMP(tid == 0 && ks == 9, 14);
        wg_fence();
        stage_mma(s, 0);
        wg_commit();
        wg_wait<1>();
        arrive_both(bar(B_OUT_EMPTY + sprev), lane);
        wg_fence();
#pragma unroll
        for (int kk = 1; kk < 4; kk++) stage_mma(s, kk);
        wg_commit();
        sprev = s;
        if (++s == 5) { s = 0; ph ^= 1; }
      }
      asm volatile("{\n.reg .pred p;\nsetp.ne.b32 p, %0, 0;\n@p bar.sync 1, 256;\n}" :: "r"(wg) : "memory");
#pragma unroll 1
      for (int ks = 12; ks < 16; ++ks) {
        mbar_wait(bar(B_OUT_FULL + s), ks == 15);
        wg_fence();
#pragma unroll
        for (int kk = 0; kk < 4; kk++) stage_mma(s, kk);
        wg_commit();
        if (++s == 5) s = 0;
      }
      asm volatile("{\n.reg .pred p;\nsetp.eq.b32 p, %0, 0;\n@p bar.arrive 1, 256;\n}" :: "r"(wg) : "memory");
    }
    wg_wait<0>(); pin<64>(acc);
    TSTAMP(tid == 0, 15); TSTAMP(tid == 128, 16);
#pragma unroll
    for (int hf = 0; hf < 2; hf++) {
      const uint32_t dst = sb + hf * SLOT + wg * 8192;
#pragma unroll
      for (int t = 0; t < 4; t++) {
        const float* a = acc + 32 * hf + 8 * t;
        stsm4(dst + orow + (ox ^ (t << 5)), pack_bf16(a[0], a[1]), pack_bf16(a[2], a[3]), pack_bf16(a[4], a[5]), pack_bf16(a[6], a[7]));
      }
      fence_async_smem();
      __syncwarp();
      if (elect()) { tma2d_store(&P.outa, dst + wq * 2048, 128 * j + 64 * hf, 128 * r + 16 * warp); bulk_commit(); }
    }
    const bool stale = __any_sync(0xffffffffu, acc[0] != acc[0] || acc[2] != acc[2] || FORCE_REDO);
    if (elect()) bulk_wait_read();
    TSTAMP(tid == 128, 17);
    __syncwarp();
    cluster_wait();
    TSTAMP(tid == 128, 28); GSTAMP(tid == 128, 31);
    if (stale) {
      __threadfence();
#pragma unroll
      for (int i = 0; i < 64; i++) acc[i] = 0.f;
      const int row = warp * 16 + (lane >> 2);
#pragma unroll 1
      for (int k = 0; k < 1024; k += 2) {
        const uint8_t* src = g_xch[r * 8 + (k >> 7)] + ((k >> 6) & 1) * SLOT + row * 128 + ((((k >> 3) ^ row) & 7) << 4) + (k & 7) * 2;
        uint32_t a[2];
        int n = 0;
        do { a[0] = ld_relaxed(src); a[1] = ld_relaxed(src + 1024); } while (!all_arrived<2>(a) && ++n < kSpinLimit);
#pragma unroll 1
        for (int e = 0; e < 2; e++) {
          const float a0 = e ? bf_hi(a[0]) : bf_lo(a[0]), a1 = e ? bf_hi(a[1]) : bf_lo(a[1]);
          const uint32_t* wrow = reinterpret_cast<const uint32_t*>(P.wo_ptr + (k + e) * 1024 + 128 * j) + (lane & 3);
#pragma unroll
          for (int i = 0; i < 16; i++) {
            const uint32_t w = __ldg(wrow + 4 * i);
            acc[4 * i] += a0 * bf_lo(w); acc[4 * i + 1] += a0 * bf_hi(w);
            acc[4 * i + 2] += a1 * bf_lo(w); acc[4 * i + 3] += a1 * bf_hi(w);
          }
        }
      }
      uint32_t* op = reinterpret_cast<uint32_t*>(P.out_ptr + (128 * r + row) * 2048 + 128 * j) + (lane & 3);
#pragma unroll
      for (int i = 0; i < 32; i++) op[(i & 1) * 8192 + (i >> 1) * 4] = pack_bf16(acc[2 * i], acc[2 * i + 1]);
    }
  } else {
    asm volatile("setmaxnreg.dec.sync.aligned.u32 56;");
    auto fetch_stage = [&](int it) {
      if ((it & 7) == rp && elect()) {
        l2_prefetch2d(&P.wk, 1024 + 128 * j + 64 * rho, 32 * it);
        l2_prefetch3d(&P.w, 0, 32 * it, 32 * rho + 2 * j);
      }
      if ((it & 7) == j && elect()) l2_prefetch2d(&P.x, 32 * it, 128 * r);
    };
    if (warp == 8) {
      cluster_wait();
      cluster_arrive();
      LOOPSTAMP(3, tid == 256, 15);
#pragma unroll 1
      for (int it = 1; it < 4; it++) {
        if (elect()) load_stage(it);
        fetch_stage(it + 3);
      }
      LOOPSTAMP(3, tid == 256, 16);
      __syncwarp();
      cluster_wait();
    } else {
      if (elect()) {
#pragma unroll 1
        for (int g = warp - 9; g < 8; g += 3)
          for (int i = 0; i < 8; i++) mbar_init(bar(8 * g + i), 1u << ((BAR_LOG2 >> (4 * g)) & 7));
        if (warp == 11) for (int i = 0; i < 7; i++) mbar_expect(bar(B_H_FULL + i), i < 2 ? 12288 : i < 5 ? 8192 : i == 5 ? 16 : 16384);
        asm volatile("fence.mbarrier_init.release.cluster;" ::: "memory");
      }
      LOOPSTAMP(3, tid == 288, 14);
      __syncwarp();
      cluster_wait();
      cluster_arrive();
#pragma unroll
      for (int i = 0; i < 3; i++) asm volatile("st.shared.v4.b32 [%0], {%1,%1,%1,%1};" :: "r"(sb + SM_F1 + i * 1536 + (tid - 288) * 16), "r"(0xffffffffu) : "memory");
      fence_async_smem();
      asm volatile("bar.arrive 5, 128;" ::: "memory");
      if ((sb & 0xffffff) != SM_BASE) __trap();
      cluster_wait();
    }
    auto chunk = [&](int ks) { const int c = ks >= 9, t = ks - 2 - 7 * c; return ks < 2 ? 2 * j + ks : 2 * (t + (t >= j)) + c; };
    auto load_wo = [&](uint32_t dst, int c, uint32_t bytes, uint32_t fb) {
      mbar_expect(fb, bytes);
      tma2d_mc(dst + rho * 8192, &P.wo, 128 * j + 64 * rho, c * 64, fb);
    };
    uint8_t* const xch = g_xch[r * 8 + j];
    if (warp == 8) {
      int ck = 0, cw = 0, cph = 1;
      const CUtensorMap* kvmap = rho ? &P.v : &P.k;
#pragma unroll 1
      for (int it = HSTART; it < 32 || (ck < 20 && it < kSpinLimit); ++it) {
        if (it >= 4 && it < 32) {
          mbar_wait(bar(B_QKV_EMPTY + (it & 3)), ((it >> 2) - 1) & 1);
          if (elect()) load_stage(it);
          LOOPSTAMP(3, lane == 0 && it < 12, 15 + it);
        }
        if (it >= 4 && it < 29) fetch_stage(it + 3);
        const int n = it - HSTART;
        if (n >= 0 && n < 8) {
          if (elect()) bulk_load(sb + SM_SIG + n * 8192 + 4096, P.ssm_k + (size_t)(cta * 8 + n) * 2048, 4096, bar(B_H_FULL + (n >= 3) + (n >= 6)));
        } else if (n >= 8 && n < 19) {
          if (n == 8) bar_sync(5, 128);
          if (elect()) bulk_store(xch + (n - 8) * 4096, sb + SM_F1, 4096);
        } else if (it >= PF0 && it < PF0 + 4) {
          if (elect()) l2_prefetch(it < PF0 + 2 ? P.wo_ptr + cta * 8192 + (it - PF0) * 4096 : P.q_ptr + (512 + (it - PF0 - 2) * 1024 + cta * 4) * 1024, 8192);
        }
        if (ck < 16 && it >= PSTART && __all_sync(0xffffffffu, mbar_test(bar(B_PREP_EMPTY + cw), cph))) {
          if (elect()) {
            mbar_expect(bar(B_PREP_FULL + cw), 8704);
            tma3d_mc(sb + SM_STG + cw * 8704 + rho * 4608, kvmap, cl * 16, ck * 8 - 1 + rho, 0, bar(B_PREP_FULL + cw));
          }
          ++ck;
          if (++cw == 3) { cw = 0; cph ^= 1; }
        } else if (ck >= 16 && ck < 20 && __all_sync(0xffffffffu, mbar_test(bar(B_STG_FREE), 0))) {
          if (elect()) tma2d(sb + SM_Q + (ck - 16) * 4096, &P.q, cl * 16, rho * 1024 + (ck - 16) * 128, bar(B_Q_FULL));
          ++ck;
        }
      }
      if (elect()) {
        bulk_commit();
        bulk_wait_read();
        mbar_expect(bar(B_SIG_READY), 10240);
        bulk_load(sb + SM_TW, g_tables, 10240, bar(B_SIG_READY));
        TSTAMP(true, 9);
        flag_add(&g_ready);
        TSTAMP(true, 10);
        prefetch_map(&P.wo); prefetch_map(&P.outa);
        const unsigned epoch = ld_relaxed(&g_epoch[cta]) + 1;
        g_epoch[cta] = epoch;
        flag_wait(&g_ready, kCtas * epoch);
        mbar_arrive(bar(B_ZEROED));
        TSTAMP(true, 11);
      }
      __syncwarp();
      mbar_wait(bar(B_QKV_DONE), 0);
#pragma unroll 1
      for (int ks = 0; ks < 4; ++ks) if (elect()) load_wo(sb + (4 + ks) * SLOT, chunk(ks), ks < 2 ? SLOT : 2 * SLOT, bar(B_OUT_FULL + ks));
    } else {
      const int at = tid - 288, aw = warp - 9, ch0 = cta * 8;
      {
        const uint32_t stg = sb + SM_STG + aw * 8704, pf = bar(B_PREP_FULL + aw), pe = bar(B_PREP_EMPTY + aw);
        const uint4 wv = __ldg(reinterpret_cast<const uint4*>(P.shift_k + (ch0 + 2 * (lane & 3)) * 4));
        const float skip = __bfloat162float(P.ssm_d[ch0 + (lane & 7)]);
        const uint32_t w0 = __byte_perm(wv.x, wv.z, 0x5410), w1 = __byte_perm(wv.x, wv.z, 0x7632);
        const uint32_t w2 = __byte_perm(wv.y, wv.w, 0x5410), w3 = __byte_perm(wv.y, wv.w, 0x7632);
        auto swz32 = [](uint32_t a) { return a ^ ((a >> 3) & 16); };
        const uint32_t kl = (lane >> 3) * 288 + (lane & 7) * 32 + rho * 16;
        const uint32_t ka = stg + swz32(kl + 32), kh = stg + swz32(kl + 12 * 288), va = stg + 4608 + swz32(lane * 32 + rho * 16);
        const uint32_t ua = sb + SM_SIG + (lane & 7) * 8192 + (((lane >> 3) ^ (lane & 7)) << 4);
        if (at == 0) prefetch_map(&P.q);
        uint32_t eh = 0;
#pragma unroll 1
        for (int ck = aw, rd = 0; rd < 9; ck += 3, ++rd) {
          if (rd == 6) {
            bar_sync(4, 96);
            if (at == 64) mbar_arrive(bar(B_STG_FREE));
          }
          const int c = rd < 6 ? ck : ck - 18;
          if (c < 8) {
            uint32_t x[32], dst = sb + SM_SIG + c * 8192;
            if (rd < 6) {
              mbar_wait(bar(B_H_FULL + rd), 0);
#pragma unroll
              for (int i = 0; i < 8; i++) ldsm4(x + 4 * i, dst + 4096 + i * 512 + lane * 16);
              const float d = __shfl_sync(0xffffffffu, skip, c);
              if (lane == 0) x[0] = pack_bf16(bf_lo(x[0]) + d, bf_hi(x[0]));
              dst += 4096 + (lane >> 1) * 128 + ((((lane & 1) * 4) ^ ((lane >> 1) & 7)) << 4);
            } else {
#pragma unroll
              for (int i = 0; i < 8; i++) ldsm4_t(x + 4 * i, dst + i * 512 + ((lane ^ c) << 4));
              dst += (lane >> 4) * 1024 + (lane & 7) * 128 + ((((lane >> 1) & 4) ^ (lane & 7)) << 4);
            }
            const uint32_t e = normalize(x, dst);
            if (rd < 6) {
              eh |= e << (8 * rd);
            } else {
              const int f = min(max((int)(e + (eh & 255)) - 125, 0), 254);
              eh >>= 8;
              if (lane == 0) asm volatile("st.shared.b16 [%0], %1;" :: "r"(sb + SM_SC + rho * 16 + 2 * c), "h"((uint16_t)(f << 7)) : "memory");
            }
          }
          if (ck < 16) {
            mbar_wait(pf, rd & 1);
            uint32_t k[20], v[16];
            ldsm4(k, kh);
#pragma unroll
            for (int m = 0; m < 4; m++) { ldsm4(k + 4 + 4 * m, (ka ^ ((m & 1) << 4)) + m * 1152); ldsm4(v + 4 * m, va + m * 1024); }
            arrive_both(pe + ((k[3] | k[4] | k[8] | k[12] | k[16] | v[0] | v[4] | v[8] | v[12]) & P.zero), lane, ck < 13);
#pragma unroll
            for (int m = 0; m < 4; m++) {
              uint32_t u[4];
#pragma unroll
              for (int n = 0; n < 4; n++) {
                const uint32_t* kk = k + 4 + 4 * m + n;
                u[n] = bmul2(bfma2(kk[0], w0, bfma2(kk[-1], w1, bfma2(kk[-2], w2, bmul2(kk[-3], w3)))), v[4 * m + n]);
              }
              stsm4_t((ua ^ (m << 6)) + ck * 256, u[0], u[1], u[2], u[3]);
            }
          }
        }
        fence_async_smem();
        __syncwarp();
        if (lane == 0) mbar_arrive(bar(B_SIG_READY));
        bar_sync(4, 96);
        if (at == 32) {
          const uint4 s = lds128(sb + SM_SC + rho * 16);
          asm volatile("st.async.weak.shared::cluster.mbarrier::complete_tx::bytes.v4.b32 [%0], {%1,%2,%3,%4}, [%5];"
                       :: "r"(peer_addr(sb + SM_SC + rho * 16, rho ^ 1)), "r"(s.x), "r"(s.y), "r"(s.z), "r"(s.w), "r"(peer_addr(bar(B_RDY0), rho ^ 1)) : "memory");
        }
        TSTAMP(at == 0, 20);
      }
    }
    __syncwarp();
    {
      const int a4 = warp - 8;
      const uint8_t* part = xch + 2 * SLOT + (lane >> 3) * 4 * KV_SLICE + (a4 * 8 + (lane & 7)) * 16;
      const uint8_t* zpart = xch + 2 * SLOT + (lane & 15) * KV_SLICE + 512 + (a4 * 2 + (lane >> 4)) * 4;
      uint8_t* red = xch + 2 * SLOT + 16 * KV_SLICE + (a4 * 8 + (lane & 7)) * 16 + (lane >> 3) * 4;
      uint8_t* zred = xch + 2 * SLOT + 16 * KV_SLICE + 512 + (a4 * 2 + (lane >> 4)) * 4;
      const uint8_t* all = g_xch[a4 * 32 + j] + 2 * SLOT + 16 * KV_SLICE + lane * 16;
      const uint8_t* zall = all + 512 + (lane & 28) - lane * 16;
      keep(part); keep(zpart); keep(red); keep(zred); keep(all); keep(zall);
      uint32_t v[20];
      int n = 0;
      mbar_wait(bar(B_KVP), 0);
      delay(PD1);
      auto load1 = [&](uint32_t* d) {
#pragma unroll
        for (int i = 0; i < 4; i++) ld_relaxed4(d + 4 * i, part + i * KV_SLICE);
        d[16] = ld_relaxed(zpart);
      };
      do load1(v); while (!all_arrived<17>(v) && ++n < kSpinLimit);
      TSTAMP(tid == 288, 21);
      float lo[4], hi[4], z = __uint_as_float(v[16]);
#pragma unroll
      for (int b = 0; b < 4; b++) {
        lo[b] = (bf_lo(v[b]) + bf_lo(v[4 + b])) + (bf_lo(v[8 + b]) + bf_lo(v[12 + b]));
        hi[b] = (bf_hi(v[b]) + bf_hi(v[4 + b])) + (bf_hi(v[8 + b]) + bf_hi(v[12 + b]));
      }
      const bool u16 = lane & 16, u8 = lane & 8;
#pragma unroll
      for (int b = 0; b < 2; b++) {
        lo[b] = (u16 ? lo[b + 2] : lo[b]) + __shfl_xor_sync(0xffffffffu, u16 ? lo[b] : lo[b + 2], 16);
        hi[b] = (u16 ? hi[b + 2] : hi[b]) + __shfl_xor_sync(0xffffffffu, u16 ? hi[b] : hi[b + 2], 16);
      }
      const float l = (u8 ? lo[1] : lo[0]) + __shfl_xor_sync(0xffffffffu, u8 ? lo[0] : lo[1], 8);
      const float h = (u8 ? hi[1] : hi[0]) + __shfl_xor_sync(0xffffffffu, u8 ? hi[0] : hi[1], 8);
      st_relaxed(red, pack_bf16(l, h));
#pragma unroll
      for (int o = 8; o; o >>= 1) z += __shfl_xor_sync(0xffffffffu, z, o);
      if ((lane & 15) == 0) st_relaxed(zred, pack_bf16(z, z));
      TSTAMP(tid == 288, 22);
      n = 0;
      delay(PD2);
      auto load2 = [&](uint32_t* d) {
#pragma unroll
        for (int i = 0; i < 4; i++) {
          ld_relaxed4(d + 4 * i, all + i * 8 * XCH_BYTES);
          d[16 + i] = ld_relaxed(zall + i * 8 * XCH_BYTES);
        }
      };
      do load2(v); while (!all_arrived<20>(v) && ++n < kSpinLimit);
#pragma unroll
      for (int i = 0; i < 4; i++) {
        const uint32_t dst = sb + SM_KV + (a4 * 4 + i) * 640;
        stsm4(dst + lane * 16, v[4 * i], v[4 * i + 1], v[4 * i + 2], v[4 * i + 3]);
        asm volatile("st.shared.b32 [%0], %1;" :: "r"(dst + 512 + lane * 4), "r"(v[16 + i]) : "memory");
      }
      fence_async_smem();
      __syncwarp();
      if (lane == 0) mbar_arrive(bar(B_KV_READY + (a4 >> 1)));
      TSTAMP(tid == 288, 23);
    }
    if (warp != 10) cluster_arrive();
    if (warp == 8) {
      mbar_wait(bar(B_RDY1), 0);
      if (elect()) load_wo(sb + 9 * SLOT, chunk(4), 2 * SLOT, bar(B_OUT_FULL + 4));
      int c = chunk(4);
      uint32_t s8 = 0, ph = 0;
#pragma unroll 1
      for (int ks = 5; ks < 16; ++ks) {
        c = ks == 9 ? 1 : c + 2;
        if ((c >> 1) == j) c += 2;
        uint32_t fb = bar(B_OUT_FULL) + s8, dst = sb + 4 * SLOT + s8 * (SLOT / 8) + (s8 >> 5) * SLOT;
        keep(fb); keep(dst); keep(c);
        mbar_wait(bar(B_OUT_EMPTY) + s8, ph);
        if (elect()) load_wo(dst, c, 2 * SLOT, fb);
        s8 += 8;
        if (s8 == 40) { s8 = 0; ph ^= 1; }
      }
    } else {
      auto wait_chunks = [&](unsigned mask) {
        unsigned ready;
        int n = 0;
        do {
          ready = __ballot_sync(0xffffffffu, ld_relaxed(g_xch[r * 8 + ((lane >> 1) & 7)] + XCH_FLAG) + 1 > (lane & 1));
        } while ((~ready & mask) && ++n < kSpinLimit);
        return ready;
      };
      if (warp == 9) {
        if (elect()) {
#pragma unroll 1
          for (int c = 0; c < 2; c++) {
            mbar_wait(bar(B_O_WRITTEN + c), 0);
            TSTAMP(c == 0, 19);
            fence_async_smem();
            bulk_store(xch + c * SLOT, sb + c * SLOT, SLOT);
            bulk_commit();
            bulk_wait_read();
            mbar_arrive(bar(B_OT_FREE + c));
            delay(FDELAY);
            st_relaxed(xch + XCH_FLAG, c);
            if (!c) delay(C1DELAY);
            TSTAMP(c == 1, 25);
          }
        }
        __syncwarp();
        wait_chunks(0xaaaa);
        if (lane == 0) mbar_arrive(bar(B_FLAGS1));
      } else if (warp == 10) {
        mbar_wait(bar(B_Q_FULL), 0);
        mbar_wait(bar(B_RDY0), 0);
        mbar_wait(bar(B_QKV_DONE), 0);
#pragma unroll 1
        for (int n = 0; n < 4; n++) {
          const int w = n & 1;
          mbar_wait(bar(B_SEG + n), 0);
          fence_async_smem();
          if (elect()) bulk_to_peer(sb + (n < 2 ? SM_Y0 : SM_SIG) + w * 8192 + 4096, sb + SM_YT + w * 4096, 4096, bar(B_YIN + (n >> 1)), rho ^ 1);
          if (w) {
            mbar_wait(bar(B_YIN + (n >> 1)), 0);
            if (lane == 0) asm volatile("mbarrier.arrive.shared::cluster.b64 _, [%0];" :: "r"(n < 2 ? peer_addr(bar(B_RDY1), rho ^ 1) : bar(B_Y_READY)) : "memory");
          }
        }
        __syncwarp();
        cluster_arrive();
        TSTAMP(lane == 0, 26);
      } else {
        mbar_wait(bar(B_OUT_FULL), 0);
        mbar_wait(bar(B_OUT_FULL + 1), 0);
        mbar_wait(bar(B_O_WRITTEN), 0);
        delay(PD3);
        unsigned ready = 0;
        const uint8_t* const first = g_xch[r * 8 + (j == 0)];
        const uint8_t* src = first;
        auto next_tile = [&]() { src += XCH_BYTES; if (src == xch) src += XCH_BYTES; };
        constexpr uint64_t kFirst = (B_O_WRITTEN + 1) | B_OT_FREE << 8 | B_SLOT_FREE << 16 | (B_OT_FREE + 1) << 24 | (uint64_t)B_CONV_DONE << 32;
#pragma unroll 1
        for (int ks = 2; ks < 7; ++ks) {
          const int s = ks < 5 ? ks : ks - 5;
          const unsigned need = ks < 4 ? 1u << chunk(ks) : 0x5555u;
          if (~ready & need) ready = wait_chunks(need);
          mbar_wait(bar((int)(kFirst >> (8 * ks - 16)) & 255), ks == 4);
          if (ks == 4 || ks == 6) fence_async_smem();
          if (elect()) bulk_load(sb + ((A_SLOTS >> (4 * s)) & 15) * SLOT, src, SLOT, bar(B_OUT_FULL + s));
          TSTAMP(ks == 2 && lane == 0, 18);
          next_tile();
        }
        uint32_t s8 = 16, ph = 0, half = 0;
#pragma unroll 1
        for (int ks = 7; ks < 16; ++ks) {
          if (ks == 9) { mbar_wait(bar(B_FLAGS1), 0); src = first; half = SLOT; }
          uint32_t fb = bar(B_OUT_FULL) + s8, dst = sb + ((A_SLOTS >> (s8 >> 1)) & 15) * SLOT;
          const uint8_t* p = src + half;
          keep(fb); keep(dst); keep(p);
          mbar_wait(bar(B_OUT_EMPTY) + s8, ph);
          if (elect()) bulk_load(dst, p, SLOT, fb);
          next_tile();
          s8 += 8;
          if (s8 == 40) { s8 = 0; ph ^= 1; }
        }
      }
    }
    if (warp == 9 || warp == 10) {
      const int yc = (lane & 1) + ((lane >> 2) & 2) + (lane & 2) * 2, ysrc = (lane >> 2) & 1;
      const uint32_t ya = sb + (yc & 4 ? SM_SIG : SM_Y0) + (yc & 1) * 8192 + (yc & 2) * 1024 + (ysrc ^ rho) * 4096 +
                          (lane >> 4) * 128 + ((yc ^ (2 * ysrc)) << 4);
      uint32_t s0, s1;
      mbar_wait(bar(B_Y_READY), 0);
      asm volatile("ld.shared.v2.b32 {%0,%1}, [%2];" : "=r"(s0), "=r"(s1) : "r"(sb + SM_SC + (lane & 3) * 8) : "memory");
#pragma unroll 1
      for (int n = warp - 9; n < 8; n += 2) {
        __nv_bfloat16* op = P.out_ptr + (rho * 1024 + n * 128 + (lane >> 2)) * 2048 + 1024 + cl * 16 + (lane & 3) * 4;
        const uint32_t qa = sb + SM_Q + (n & 3) * 4096 + lane * 8;
        asm volatile("cp.async.wait_group 1;" ::: "memory");
        __syncwarp();
#pragma unroll 1
        for (int u0 = 0; u0 < 8; u0 += 2) {
          uint32_t y[2][4], q[2][4];
#pragma unroll
          for (int u = 0; u < 2; u++) {
            ldsm4_t(y[u], (ya ^ ((u0 + u) << 4)) + n * 256);
#pragma unroll
            for (int m = 0; m < 2; m++)
              asm volatile("ld.shared.v2.b32 {%0,%1}, [%2];" : "=r"(q[u][2 * m]), "=r"(q[u][2 * m + 1]) : "r"(qa + (u0 + u) * 512 + m * 256) : "memory");
          }
#pragma unroll
          for (int u = 0; u < 2; u++)
#pragma unroll
            for (int m = 0; m < 2; m++)
              asm volatile("st.global.v2.b32 [%0], {%1,%2};" :: "l"(op + (u * 16 + m * 8) * 2048),
                           "r"(bmul2(q[u][2 * m], bmul2(y[u][2 * m], s0))), "r"(bmul2(q[u][2 * m + 1], bmul2(y[u][2 * m + 1], s1))) : "memory");
          op += 32 * 2048;
        }
        __syncwarp();
        if (n < 4) {
          const __nv_bfloat16* qp = P.q_ptr + (rho * 1024 + n * 128 + 512 + (lane >> 1)) * 1024 + cl * 16 + (lane & 1) * 8;
#pragma unroll
          for (int i = 0; i < 8; i++)
            asm volatile("cp.async.cg.shared.global [%0], [%1], 16;" :: "r"(qa + lane * 8 + i * 512), "l"(qp + i * 16384) : "memory");
        }
        asm volatile("cp.async.commit_group;" ::: "memory");
      }
      TSTAMP(tid == 320, 24);
    }
    __syncwarp();
    cluster_wait();
  }
}

typedef CUresult (*EncodeFn)(CUtensorMap*, CUtensorMapDataType, cuuint32_t, void*, const cuuint64_t*, const cuuint64_t*,
                             const cuuint32_t*, const cuuint32_t*, CUtensorMapInterleave, CUtensorMapSwizzle,
                             CUtensorMapL2promotion, CUtensorMapFloatOOBfill);

void encode(EncodeFn fn, CUtensorMap* m, const void* p, int rank, const cuuint64_t* dims, const cuuint64_t* strides,
            const cuuint32_t* box, CUtensorMapSwizzle sw) {
  const cuuint32_t es[3] = {1, 1, 1};
  fn(m, CU_TENSOR_MAP_DATA_TYPE_BFLOAT16, rank, const_cast<void*>(p), dims, strides, box, es, CU_TENSOR_MAP_INTERLEAVE_NONE, sw,
     CU_TENSOR_MAP_L2_PROMOTION_NONE, CU_TENSOR_MAP_FLOAT_OOB_FILL_NONE);
}
void encode2d(EncodeFn fn, CUtensorMap* m, const void* p, uint64_t cols, uint64_t rows, uint32_t bc, uint32_t br, CUtensorMapSwizzle sw) {
  const cuuint64_t dims[2] = {cols, rows}, strides[1] = {cols * 2};
  const cuuint32_t box[2] = {bc, br};
  encode(fn, m, p, 2, dims, strides, box, sw);
}
void encode3d(EncodeFn fn, CUtensorMap* m, const void* p, uint32_t nblk) {
  const cuuint64_t dims[3] = {1024, 128, 16}, strides[2] = {2048 * 16, 2048};
  const cuuint32_t box[3] = {16, nblk, 16};
  encode(fn, m, p, 3, dims, strides, box, CU_TENSOR_MAP_SWIZZLE_32B);
}

}

extern "C" void kernel_launch(void* const* d_in, const int* in_sizes, int n_in, void* d_out, int out_size) {
  static EncodeFn fn = nullptr;
  if (!fn) {
    cudaDriverEntryPointQueryResult qr;
    cudaGetDriverEntryPoint("cuTensorMapEncodeTiled", (void**)&fn, cudaEnableDefault, &qr);
    cudaFuncSetAttribute(fused_kernel, cudaFuncAttributeMaxDynamicSharedMemorySize, SM_TOTAL);
  }
  Params P;
  encode2d(fn, &P.x, d_in[0], 1024, 2048, 32, 128, CU_TENSOR_MAP_SWIZZLE_64B);
  {
    const cuuint64_t dims[3] = {64, 1024, 48}, strides[2] = {6144, 128};
    const cuuint32_t box[3] = {64, 32, 2};
    encode(fn, &P.w, d_in[1], 3, dims, strides, box, CU_TENSOR_MAP_SWIZZLE_128B);
  }
  encode2d(fn, &P.wk, d_in[1], 3072, 1024, 64, 32, CU_TENSOR_MAP_SWIZZLE_128B);
  encode2d(fn, &P.wo, d_in[2], 1024, 1024, 64, 64, CU_TENSOR_MAP_SWIZZLE_128B);
  encode2d(fn, &P.outa, d_out, 2048, 2048, 64, 16, CU_TENSOR_MAP_SWIZZLE_128B);
  encode3d(fn, &P.k, d_in[4], 9);
  encode3d(fn, &P.v, d_in[5], 8);
  encode2d(fn, &P.q, d_in[3], 1024, 2048, 16, 128, CU_TENSOR_MAP_SWIZZLE_NONE);
  P.shift_k = (const __nv_bfloat16*)d_in[6];
  P.ssm_k = (const __nv_bfloat16*)d_in[7];
  P.ssm_d = (const __nv_bfloat16*)d_in[8];
  P.zero = 0;
  P.q_ptr = (const __nv_bfloat16*)d_in[3];
  P.out_ptr = (__nv_bfloat16*)d_out;
  P.wo_ptr = (const __nv_bfloat16*)d_in[2];
  fused_kernel<<<kCtas, kThreads, SM_TOTAL>>>(P);
}
```
